```python
import torch

def _softmax(x, axis=-1):
    return torch.softmax(x, dim=axis)

def _gelu(x):
    return torch.nn.functional.gelu(x, approximate='tanh')

def _silu(x):
    return torch.nn.functional.silu(x)

def _sigmoid(x):
    return torch.sigmoid(x)

def _layernorm(x, axis=-1, eps=1e-05):
    m = x.mean(dim=axis, keepdim=True)
    v = x.var(dim=axis, keepdim=True, unbiased=False)
    return (x - m) / torch.sqrt(v + eps)

def _scatter_add(tgt, idx, src, axis=0):
    return tgt.clone().index_add_(axis, idx, src)

def _segment_sum(src, seg, n):
    out = torch.zeros((n,) + src.shape[1:], dtype=src.dtype)
    return out.index_add_(0, seg, src)

def _pad(x, pw):
    flat = tuple((v for pair in reversed(pw) for v in pair))
    return torch.nn.functional.pad(x, flat)
kernel_name = 'adaLN_cond__memory_aug_recurrent_mem_tr__glu_gated_swiglu__prompt'

def setup_inputs():

    _w = lambda a: (lambda t: t.to(torch.bfloat16) if t.is_floating_point() else t)(torch.as_tensor(a))

    def _A_setup():
        B, S, Dm = (1, 2048, 1024)
        H, Dh = (32, 128)
        M, seg = (8, 32)
        seg = min(seg, S)
        S = S // seg * seg
        return {'x': _w((lambda *s: torch.randn(*s, dtype=torch.bfloat16) * 0.05)(B, S, Dm)), 'mem0': _w((lambda *s: torch.randn(*s, dtype=torch.bfloat16) * 0.8)(B, M, Dm)), 'Wq': _w((lambda *s: torch.randn(*s, dtype=torch.bfloat16) * 0.8)(Dm, H, Dh) * Dm ** (-0.5)), 'Wk': _w((lambda *s: torch.randn(*s, dtype=torch.bfloat16) * 0.8)(Dm, H, Dh) * Dm ** (-0.5)), 'Wv': _w((lambda *s: torch.randn(*s, dtype=torch.bfloat16) * 0.8)(Dm, H, Dh) * Dm ** (-0.5)), 'Wo': _w((lambda *s: torch.randn(*s, dtype=torch.bfloat16) * 0.8)(H, Dh, Dm) * (H * Dh) ** (-0.5)), 'seg_len': seg}
    _A_in = _A_setup()

    def _B_setup():
        B, S, D, F = (1, 2048, 1024, 3584)
        return {'x': _w((lambda *s: torch.randn(*s, dtype=torch.bfloat16) * 0.05)(B, S, D)), 'w1': _w((lambda *s: torch.randn(*s, dtype=torch.bfloat16) * 0.4)(D, F) * (2.0 / D) ** 0.5), 'w3': _w((lambda *s: torch.randn(*s, dtype=torch.bfloat16) * 0.4)(D, F) * (2.0 / D) ** 0.5), 'w2': _w((lambda *s: torch.randn(*s, dtype=torch.bfloat16) * 0.4)(F, D) * (2.0 / F) ** 0.5)}
    _B_in = _B_setup()
    return {'A_x': _A_in['x'], 'A_mem0': _A_in['mem0'], 'A_Wq': _A_in['Wq'], 'A_Wk': _A_in['Wk'], 'A_Wv': _A_in['Wv'], 'A_Wo': _A_in['Wo'], 'A_seg_len': _A_in['seg_len'], 'B_x': _B_in['x'], 'B_w1': _B_in['w1'], 'B_w3': _B_in['w3'], 'B_w2': _B_in['w2'], 'c': _w((lambda *s: torch.randn(*s, dtype=torch.bfloat16) * 0.1)(1, 1024) * 8.0), 'w_mod': _w((lambda *s: torch.randn(*s, dtype=torch.bfloat16) * 0.1)(1024, 6 * 1024) * 1024 ** (-0.5) * 8.0)}

def reference(A_x, A_mem0, A_Wq, A_Wk, A_Wv, A_Wo, A_seg_len, B_x, B_w1, B_w3, B_w2, c, w_mod):

    def _A_ref(x, mem0, Wq, Wk, Wv, Wo, seg_len):
        B, S, Dm = x.shape
        H, Dh = (Wq.shape[1], Wq.shape[2])
        M = mem0.shape[1]
        scale = Dh ** (-0.5)
        n_seg = S // seg_len
        L = M + seg_len
        idx = torch.arange(L)
        mask = (idx[:, None] < M) | (idx[:, None] >= idx[None, :])
        mem = mem0
        outs = []
        for s in range(n_seg):
            xs = x[:, s * seg_len:(s + 1) * seg_len, :].clone()
            h = torch.concatenate([mem, xs], axis=1)
            q = torch.einsum('btd,dhe->bhte', h, Wq)
            k = torch.einsum('btd,dhe->bhte', h, Wk)
            v = torch.einsum('btd,dhe->bhte', h, Wv)
            scores = torch.einsum('bhqe,bhke->bhqk', q, k) * scale
            scores = torch.where(mask[None, None], scores, -1000000000.0)
            p = _softmax(scores, axis=-1)
            o = torch.einsum('bhqk,bhke->bhqe', p, v)
            o = torch.einsum('bhte,hed->btd', o, Wo)
            mem = o[:, :M, :].clone()
            outs.append(o[:, M:, :])
        return torch.concatenate(outs, axis=1)

    def _B_ref(x, w1, w3, w2):
        gate = torch.einsum('bsd,df->bsf', x, w1)
        up = torch.einsum('bsd,df->bsf', x, w3)
        h = _silu(gate) * up
        out = torch.einsum('bsf,fd->bsd', h, w2)
        return out
    x = A_x
    mod = (_silu(c) @ w_mod).reshape(c.shape[0], 6, 1, -1)
    sa, ca, ga, sb, cb, gb = (mod[:, 0].clone(), mod[:, 1].clone(), mod[:, 2].clone(), mod[:, 3].clone(), mod[:, 4].clone(), mod[:, 5].clone())
    h = _layernorm(x, axis=-1) * (1 + ca) + sa
    x = x + ga * _A_ref(h, A_mem0, A_Wq, A_Wk, A_Wv, A_Wo, A_seg_len)
    h = _layernorm(x, axis=-1) * (1 + cb) + sb
    x = x + gb * _B_ref(h, B_w1, B_w3, B_w2)
    return x
```

```cpp
#include <cuda_runtime.h>
#include <cuda_bf16.h>
#include <cuda.h>
#include <stdint.h>
#include <type_traits>

namespace {

constexpr int S_ = 2048, D_ = 1024, NSEG = 64, F_ = 3584;

__device__ __align__(1024) uint8_t g_h[S_ * D_ * 2];
__device__ __align__(1024) uint8_t g_att[S_ * 4096 * 2];
__device__ __align__(1024) uint8_t g_act[S_ * F_ * 2];
__device__ __align__(1024) uint8_t g_w13s[28 * 16 * 32768];
__device__ __align__(1024) float g_stat[S_ * 2];
__device__ __align__(1024) float g_uv[F_ * 4];
__device__ __align__(1024) float g_gate[2 * D_];
__device__ __align__(1024) float g_slot[4 * 3 * 8 * 4 * 32 * 4];
__device__ __align__(128) __nv_bfloat16 g_mod[6 * D_];
__device__ __align__(128) float g_modp[3 * 2 * D_];
__device__ __align__(128) uint32_t g_flags[1024];
constexpr int FL_S1 = 0, FL_S2 = 32, FL_MOD = 64, FL_HEAD = 96, FL_EXIT = 128, FL_WS = 160, FL_GO = 192, FL_ATT = 256, FL_XT = 384, FL_OUT = 512, FL_F1 = 640, FL_STAT = 768;

__device__ __forceinline__ uint32_t smem_u32(const void* p) { return (uint32_t)__cvta_generic_to_shared(p); }
__device__ __forceinline__ uint32_t mapa(uint32_t a, uint32_t r) { uint32_t o; asm("mapa.shared::cluster.u32 %0, %1, %2;" : "=r"(o) : "r"(a), "r"(r)); return o; }
__device__ __forceinline__ uint32_t pack2(float a, float b) { uint32_t r; asm("cvt.rn.bf16x2.f32 %0, %1, %2;" : "=r"(r) : "f"(b), "f"(a)); return r; }
__device__ __forceinline__ float bf_lo(uint32_t w) { return __uint_as_float(w << 16); }
__device__ __forceinline__ float bf_hi(uint32_t w) { return __uint_as_float(w & 0xffff0000u); }
__device__ __forceinline__ float ex2(float x) { float y; asm("ex2.approx.ftz.f32 %0, %1;" : "=f"(y) : "f"(x)); return y; }
__device__ __forceinline__ float rcp(float x) { float y; asm("rcp.approx.ftz.f32 %0, %1;" : "=f"(y) : "f"(x)); return y; }
__device__ __forceinline__ uint32_t clk32() { uint64_t c; asm volatile("mov.u64 %0, %%clock64;" : "=l"(c) :: "memory"); return (uint32_t)c; }

__device__ __forceinline__ void mbar_init(uint32_t b, uint32_t n) { asm volatile("mbarrier.init.shared::cta.b64 [%0], %1;" :: "r"(b), "r"(n) : "memory"); }
__device__ __forceinline__ void mbar_arrive(uint32_t b) { asm volatile("mbarrier.arrive.shared::cta.b64 _, [%0];" :: "r"(b) : "memory"); }
__device__ __forceinline__ void mbar_expect(uint32_t b, uint32_t n) { asm volatile("mbarrier.arrive.expect_tx.shared::cta.b64 _, [%0], %1;" :: "r"(b), "r"(n) : "memory"); }
__device__ __forceinline__ uint32_t mbar_try(uint32_t b, uint32_t par) {
  uint32_t ok;
  asm volatile("{\n.reg .pred p;\nmbarrier.try_wait.parity.shared::cta.b64 p, [%1], %2;\nselp.u32 %0, 1, 0, p;\n}" : "=r"(ok) : "r"(b), "r"(par) : "memory");
  return ok;
}
__device__ __forceinline__ void mbar_wait(uint32_t b, uint32_t par) {
  asm volatile("{\n.reg .pred p;\n"
               "LOOP:\n"
               "mbarrier.try_wait.parity.shared::cta.b64 p, [%0], %1;\n"
               "@!p bra.uni LOOP;\n}" :: "r"(b), "r"(par) : "memory");
}
__device__ __forceinline__ void mbar_wait_safe(uint32_t b, uint32_t par) {
  uint32_t c = 0;
  while (!mbar_try(b, par)) { if (++c > 4000000u) __trap(); }
}
__device__ __forceinline__ bool elect_one() {
  uint32_t p;
  asm volatile("{\n.reg .pred p;\nelect.sync _|p, 0xffffffff;\nselp.u32 %0, 1, 0, p;\n}" : "=r"(p));
  return p;
}
__device__ __forceinline__ void sched_fence(uint32_t x, uint32_t y) { asm volatile("{\n.reg .pred p;\nsetp.eq.u32 p, %0, %1;\n@p trap;\n}" :: "r"(x), "r"(y) : "memory"); }
template <class T> __device__ __forceinline__ T opaque32(T x) { asm volatile("" : "+r"(x)); return x; }
template <class T> __device__ __forceinline__ T opaque64(T x) { asm volatile("" : "+l"(x)); return x; }
template <int ID, int N> __device__ __forceinline__ void bar_sync() { asm volatile("bar.sync %0, %1;" :: "n"(ID), "n"(N) : "memory"); }
template <int ID, int N> __device__ __forceinline__ void bar_arrive() { asm volatile("bar.arrive %0, %1;" :: "n"(ID), "n"(N) : "memory"); }
__device__ __forceinline__ void fence_async_smem() { asm volatile("fence.proxy.async.shared::cta;" ::: "memory"); }
__device__ __forceinline__ void fence_async_all() { asm volatile("fence.proxy.async;" ::: "memory"); }
__device__ __forceinline__ void fence_gpu() { asm volatile("fence.acq_rel.gpu;" ::: "memory"); }
__device__ __forceinline__ void red_add_u32(uint32_t* p, uint32_t v) { asm volatile("red.relaxed.gpu.global.add.u32 [%0], %1;" :: "l"(p), "r"(v) : "memory"); }
__device__ __forceinline__ uint32_t ld_acquire(const uint32_t* p) { uint32_t v; asm volatile("ld.acquire.gpu.global.u32 %0, [%1];" : "=r"(v) : "l"(p) : "memory"); return v; }
__device__ __forceinline__ void wait_flag(const uint32_t* p, uint32_t target) {
  uint32_t c = 0;
  while (ld_acquire(p) < target) { if (++c > 20000000u) __trap(); __nanosleep(20); }
}

__device__ __forceinline__ void tma2d(uint32_t dst, const CUtensorMap* m, int c0, int c1, uint32_t bar) {
  asm volatile("cp.async.bulk.tensor.2d.shared::cluster.global.mbarrier::complete_tx::bytes [%0], [%1, {%3, %4}], [%2];"
               :: "r"(dst), "l"(m), "r"(bar), "r"(c0), "r"(c1) : "memory");
}
__device__ __forceinline__ void tma2d_prefetch(const CUtensorMap* m, int c0, int c1) {
  asm volatile("cp.async.bulk.prefetch.tensor.2d.L2.global [%0, {%1, %2}];" :: "l"(m), "r"(c0), "r"(c1) : "memory");
}
__device__ __forceinline__ void bulk_g2s(uint32_t dst, const void* src, uint32_t bytes, uint32_t bar) {
  asm volatile("cp.async.bulk.shared::cluster.global.mbarrier::complete_tx::bytes [%0], [%1], %2, [%3];"
               :: "r"(dst), "l"(src), "r"(bytes), "r"(bar) : "memory");
}
__device__ __forceinline__ void bulk_s2s(uint32_t dst, uint32_t src, uint32_t bytes, uint32_t bar) {
  asm volatile("cp.async.bulk.shared::cluster.shared::cta.mbarrier::complete_tx::bytes [%0], [%1], %2, [%3];"
               :: "r"(dst), "r"(src), "r"(bytes), "r"(bar) : "memory");
}
__device__ __forceinline__ void st_async1(uint32_t dst, uint32_t a, uint32_t bar) {
  asm volatile("st.async.shared::cluster.mbarrier::complete_tx::bytes.b32 [%0], %1, [%2];" :: "r"(dst), "r"(a), "r"(bar) : "memory");
}
__device__ __forceinline__ void st_async2(uint32_t dst, uint32_t a, uint32_t b, uint32_t bar) {
  asm volatile("st.async.shared::cluster.mbarrier::complete_tx::bytes.v2.b32 [%0], {%1, %2}, [%3];" :: "r"(dst), "r"(a), "r"(b), "r"(bar) : "memory");
}
__device__ __forceinline__ void st_async4(uint32_t dst, const uint32_t* r, uint32_t bar) {
  asm volatile("st.async.shared::cluster.mbarrier::complete_tx::bytes.v4.b32 [%0], {%1, %2, %3, %4}, [%5];"
               :: "r"(dst), "r"(r[0]), "r"(r[1]), "r"(r[2]), "r"(r[3]), "r"(bar) : "memory");
}
__device__ __forceinline__ void sts32(uint32_t a, uint32_t v) { asm volatile("st.shared.b32 [%0], %1;" :: "r"(a), "r"(v) : "memory"); }
__device__ __forceinline__ void sts64(uint32_t a, uint32_t x, uint32_t y) { asm volatile("st.shared.v2.b32 [%0], {%1, %2};" :: "r"(a), "r"(x), "r"(y) : "memory"); }
__device__ __forceinline__ void sts128(uint32_t a, uint32_t x, uint32_t y, uint32_t z, uint32_t w) {
  asm volatile("st.shared.v4.b32 [%0], {%1, %2, %3, %4};" :: "r"(a), "r"(x), "r"(y), "r"(z), "r"(w) : "memory");
}
__device__ __forceinline__ void lds128(uint32_t* r, uint32_t a) {
  asm volatile("ld.shared.v4.b32 {%0, %1, %2, %3}, [%4];" : "=r"(r[0]), "=r"(r[1]), "=r"(r[2]), "=r"(r[3]) : "r"(a) : "memory");
}
__device__ __forceinline__ uint32_t lds32(uint32_t a) { uint32_t r; asm volatile("ld.shared.b32 %0, [%1];" : "=r"(r) : "r"(a) : "memory"); return r; }
__device__ __forceinline__ void lds64(uint32_t* r, uint32_t a) {
  asm volatile("ld.shared.v2.b32 {%0, %1}, [%2];" : "=r"(r[0]), "=r"(r[1]) : "r"(a) : "memory");
}
__device__ __forceinline__ void lds128f(float* r, uint32_t a) {
  asm volatile("ld.shared.v4.f32 {%0, %1, %2, %3}, [%4];" : "=f"(r[0]), "=f"(r[1]), "=f"(r[2]), "=f"(r[3]) : "r"(a) : "memory");
}
__device__ __forceinline__ void lds64f(float* r, uint32_t a) {
  asm volatile("ld.shared.v2.f32 {%0, %1}, [%2];" : "=f"(r[0]), "=f"(r[1]) : "r"(a) : "memory");
}
__device__ __forceinline__ void ldsm4(uint32_t* r, uint32_t a) {
  asm volatile("ldmatrix.sync.aligned.m8n8.x4.shared.b16 {%0, %1, %2, %3}, [%4];" : "=r"(r[0]), "=r"(r[1]), "=r"(r[2]), "=r"(r[3]) : "r"(a) : "memory");
}
__device__ __forceinline__ void ldsm4t(uint32_t* r, uint32_t a) {
  asm volatile("ldmatrix.sync.aligned.m8n8.x4.trans.shared.b16 {%0, %1, %2, %3}, [%4];" : "=r"(r[0]), "=r"(r[1]), "=r"(r[2]), "=r"(r[3]) : "r"(a) : "memory");
}
__device__ __forceinline__ void ldsm2(uint32_t* r, uint32_t a) {
  asm volatile("ldmatrix.sync.aligned.m8n8.x2.shared.b16 {%0, %1}, [%2];" : "=r"(r[0]), "=r"(r[1]) : "r"(a) : "memory");
}
__device__ __forceinline__ void stsm4(uint32_t a, const uint32_t* r) {
  asm volatile("stmatrix.sync.aligned.m8n8.x4.shared.b16 [%0], {%1, %2, %3, %4};" :: "r"(a), "r"(r[0]), "r"(r[1]), "r"(r[2]), "r"(r[3]) : "memory");
}
__device__ __forceinline__ uint32_t hadd2(uint32_t a, uint32_t b) { uint32_t t; asm("add.rn.bf16x2 %0, %1, %2;" : "=r"(t) : "r"(a), "r"(b)); return t; }
__device__ __forceinline__ uint32_t hmax2(uint32_t a, uint32_t b) { uint32_t t; asm("max.bf16x2 %0, %1, %2;" : "=r"(t) : "r"(a), "r"(b)); return t; }
__device__ __forceinline__ void ldsm2t(uint32_t* r, uint32_t a) {
  asm volatile("ldmatrix.sync.aligned.m8n8.x2.trans.shared.b16 {%0, %1}, [%2];" : "=r"(r[0]), "=r"(r[1]) : "r"(a) : "memory");
}
__device__ __forceinline__ uint32_t movm(uint32_t x) { uint32_t y; asm volatile("movmatrix.sync.aligned.m8n8.trans.b16 %0, %1;" : "=r"(y) : "r"(x)); return y; }
__device__ __forceinline__ void hmma(float* d, uint32_t a0, uint32_t a1, uint32_t a2, uint32_t a3, uint32_t b0, uint32_t b1) {
  asm volatile("mma.sync.aligned.m16n8k16.row.col.f32.bf16.bf16.f32 {%0,%1,%2,%3}, {%4,%5,%6,%7}, {%8,%9}, {%0,%1,%2,%3};"
               : "+f"(d[0]), "+f"(d[1]), "+f"(d[2]), "+f"(d[3]) : "r"(a0), "r"(a1), "r"(a2), "r"(a3), "r"(b0), "r"(b1));
}
__device__ __forceinline__ void hmma0(float* d, uint32_t a0, uint32_t a1, uint32_t a2, uint32_t a3, uint32_t b0, uint32_t b1) {
  asm volatile("mma.sync.aligned.m16n8k16.row.col.f32.bf16.bf16.f32 {%0,%1,%2,%3}, {%4,%5,%6,%7}, {%8,%9}, {%10,%10,%10,%10};"
               : "=f"(d[0]), "=f"(d[1]), "=f"(d[2]), "=f"(d[3]) : "r"(a0), "r"(a1), "r"(a2), "r"(a3), "r"(b0), "r"(b1), "f"(0.f));
}
__device__ __forceinline__ void hmma_k8(float* d, uint32_t a0, uint32_t a1, uint32_t b0) {
  asm volatile("mma.sync.aligned.m16n8k8.row.col.f32.bf16.bf16.f32 {%0,%1,%2,%3}, {%4,%5}, {%6}, {%0,%1,%2,%3};"
               : "+f"(d[0]), "+f"(d[1]), "+f"(d[2]), "+f"(d[3]) : "r"(a0), "r"(a1), "r"(b0));
}
__host__ __device__ constexpr uint64_t mkdesc(uint32_t addr, uint32_t lbo, uint32_t sbo, uint32_t sw) {
  return (uint64_t)((addr & 0x3FFFF) >> 4) | ((uint64_t)(lbo >> 4) << 16) | ((uint64_t)(sbo >> 4) << 32) | ((uint64_t)sw << 62);
}
#define WG_FENCE() asm volatile("wgmma.fence.sync.aligned;" ::: "memory")
#define WG_COMMIT() asm volatile("wgmma.commit_group.sync.aligned;" ::: "memory")
#define WG_WAIT(n) asm volatile("wgmma.wait_group.sync.aligned " #n ";" ::: "memory")
template <int N> __device__ __forceinline__ void reg_fence(float* d) {
#pragma unroll
  for (int i = 0; i < N; i++) asm volatile("" : "+f"(d[i]) :: "memory");
}
template <int N> __device__ __forceinline__ void zero_regs(float* d) {
#pragma unroll
  for (int i = 0; i < N; i++) asm volatile("mov.b32 %0, 0;" : "=f"(d[i]));
}
template <int SD>
__device__ __forceinline__ void wg_rs32(float* d, uint32_t a0, uint32_t a1, uint32_t a2, uint32_t a3, uint64_t b) {
  asm volatile("wgmma.mma_async.sync.aligned.m64n32k16.f32.bf16.bf16 {%0,%1,%2,%3,%4,%5,%6,%7,%8,%9,%10,%11,%12,%13,%14,%15}, {%16,%17,%18,%19}, %20, %21, 1, 1, 0;"
               : "+f"(d[0]), "+f"(d[1]), "+f"(d[2]), "+f"(d[3]), "+f"(d[4]), "+f"(d[5]), "+f"(d[6]), "+f"(d[7]),
                 "+f"(d[8]), "+f"(d[9]), "+f"(d[10]), "+f"(d[11]), "+f"(d[12]), "+f"(d[13]), "+f"(d[14]), "+f"(d[15])
               : "r"(a0), "r"(a1), "r"(a2), "r"(a3), "l"(b), "n"(SD));
}
template <int TB>
__device__ __forceinline__ void wg_ss40(float* d, uint64_t a, uint64_t b) {
  asm volatile("wgmma.mma_async.sync.aligned.m64n40k16.f32.bf16.bf16 {%0,%1,%2,%3,%4,%5,%6,%7,%8,%9,%10,%11,%12,%13,%14,%15,%16,%17,%18,%19}, %20, %21, 1, 1, 1, 1, %22;"
               : "+f"(d[0]), "+f"(d[1]), "+f"(d[2]), "+f"(d[3]), "+f"(d[4]), "+f"(d[5]), "+f"(d[6]), "+f"(d[7]),
                 "+f"(d[8]), "+f"(d[9]), "+f"(d[10]), "+f"(d[11]), "+f"(d[12]), "+f"(d[13]), "+f"(d[14]), "+f"(d[15]),
                 "+f"(d[16]), "+f"(d[17]), "+f"(d[18]), "+f"(d[19])
               : "l"(a), "l"(b), "n"(TB));
}
template <int T>
__device__ __forceinline__ void wg_ss32(float* d, uint64_t a, uint64_t b) {
  asm volatile("wgmma.mma_async.sync.aligned.m64n32k16.f32.bf16.bf16 {%0,%1,%2,%3,%4,%5,%6,%7,%8,%9,%10,%11,%12,%13,%14,%15}, %16, %17, 1, 1, 1, %18, %18;"
               : "+f"(d[0]), "+f"(d[1]), "+f"(d[2]), "+f"(d[3]), "+f"(d[4]), "+f"(d[5]), "+f"(d[6]), "+f"(d[7]),
                 "+f"(d[8]), "+f"(d[9]), "+f"(d[10]), "+f"(d[11]), "+f"(d[12]), "+f"(d[13]), "+f"(d[14]), "+f"(d[15])
               : "l"(a), "l"(b), "n"(T));
}

constexpr int R_TAIL = 0;
constexpr int R_WO = 65536;
constexpr int R_QK = R_WO + 86016;
constexpr int R_P = R_QK + 10240;
constexpr int R_GA = R_P + 6400;
constexpr int R_M2 = R_GA + 16384;
constexpr int R_M1 = R_M2 + 7168;
constexpr int R_GB = R_M1 + 9216;
constexpr int R_VT = R_GB + 16384;
constexpr int R_VM = R_VT + 8192;
constexpr int R_XS = R_VM + 2048;
constexpr int R_OX = R_XS + 1280;
constexpr int R_BAR = R_OX + 2048;
constexpr int R_TRC = R_BAR + 256;
constexpr int R_SMEM = R_TRC + 1024;
constexpr int B_MB = 0, B_XS = 32, B_VM = 40, B_VT = 48, B_TS = 56, B_FA = 64, B_FB = 72, B_TAIL = 80, B_WO = 88, B_STG = 96, B_WM = 128, B_X = 136;
constexpr int NB_A = 1, NB_B = 2, NB_X = 3, NB_C = 4, NB_D = 5, NB_E = 6, NB_F = 7, NB_G = 8, NB_H = 9, NB_S = 10, NB_E2 = 11, NB_P = 12, NB_W0 = 13;

#define POLL_DELAY 750
#define POLL_DELAY1 700
#define POLL_STAG 150
#define POLL_K0 20
#define PF1 2
#define PF2 2
#define PF3 2
#define PF4 0
#define RF_FIRST 0
#define BX_I 5
#define NCH 4
#define TOP2 0
#define CX_I 13
#define ATT_LATE 0
#define V_FENCE 1
#define SELF_STAS 1
#define Q_FENCE 1
#define ND_K 3
#define TRACE(i)
#define TS(i)

__device__ __forceinline__ int rot_chunk(int c, int rank) {
  int G = c;
  if (c < 9) { G = c + 3 * rank; if (G >= 9) G -= 9; }
  return G;
}
__device__ __forceinline__ int wo_tile(int i, int rank) {
  if (i < 12) return 12 * rank + i;
  const int r = i - 12 + 9 * rank;
  return r < 16 ? 48 + r : 20 + r;
}
__device__ __forceinline__ void load_chunk(uint32_t dst, int seg, int G, uint32_t bar) {
  mbar_expect(bar, 4096);
  bulk_g2s(dst, g_h + (size_t)(seg * 16 + G) * 4096, 4096, bar);
}
__device__ __forceinline__ void load_red(uint32_t* v, const float* p) {
#pragma unroll
  for (int j = 0; j < 2; j++)
    asm volatile("ld.relaxed.gpu.global.v4.u32 {%0, %1, %2, %3}, [%4];"
                 : "=r"(v[4 * j]), "=r"(v[4 * j + 1]), "=r"(v[4 * j + 2]), "=r"(v[4 * j + 3]) : "l"(p + j * 256) : "memory");
}
__device__ __forceinline__ bool red_done(const uint32_t* v) { return __all_sync(0xffffffffu, (v[3] & v[7]) == 0x42000000u); }
__device__ __forceinline__ uint32_t finish_red(uint32_t* v, const float* p) {
  uint32_t tries = 0;
  if (__builtin_expect(!red_done(v), 0)) {
    do { if (++tries > 20000000u) __trap(); load_red(v, p); } while (!red_done(v));
  }
  return tries;
}
__device__ __forceinline__ void exp10(float* sv, const uint32_t* x) {
  constexpr float SC = 0.08838834764831845f * 1.4426950408889634f;
  uint32_t m2 = hmax2(hmax2(hmax2(x[0], x[1]), hmax2(x[2], x[3])), x[4]);
  m2 = hmax2(m2, __shfl_xor_sync(0xffffffffu, m2, 1));
  m2 = hmax2(m2, __shfl_xor_sync(0xffffffffu, m2, 2));
  const float nm = -fmaxf(bf_lo(m2), bf_hi(m2)) * SC;
#pragma unroll
  for (int j = 0; j < 5; j++) { sv[2 * j] = ex2(fmaf(bf_lo(x[j]), SC, nm)); sv[2 * j + 1] = ex2(fmaf(bf_hi(x[j]), SC, nm)); }
}

__device__ __forceinline__ uint32_t arm_size(int w, bool isC) {
  return w == 0 ? (isC ? 1280 : 640) : w == 1 ? (isC ? 0 : 2048) : w == 2 ? (isC ? 0 : 8192) : (isC ? 0 : 1792);
}
struct RDesc { uint64_t tok[32], tail_b[16], tail_a[32]; };

template <int WG>
__device__ __forceinline__ void r_main(const uint32_t (&W)[48][4], const RDesc& dsc, int head, uint32_t rank, int lane_, int w) {
  const uint32_t sb = (rank << 24) + 0x400, bars = sb + R_BAR;
  const uint32_t to1 = rank == 0 ? 2u << 24 : 0u - (1u << 24), to2 = rank == 2 ? 0u - (2u << 24) : 1u << 24;
  const bool isC = rank == 2;
  const int lane = opaque32(lane_), warp = WG * 4 + w;
  const int gl = rot_chunk(4 * (lane & 3) + w, rank);
  const int g0 = __shfl_sync(0xffffffffu, gl, 0), g1 = __shfl_sync(0xffffffffu, gl, 1), g2 = __shfl_sync(0xffffffffu, gl, 2);
  const uint32_t arm_bytes = arm_size(w, isC);

#define L16 opaque32(sb + opaque32(lane) * 16)
#define L8 opaque32(sb + opaque32(lane) * 8)
#define L4 opaque32(sb + opaque32(lane) * 4)
#define LV opaque32(sb + R_VT + ((opaque32(lane) >> 3) & 1) * 512 + (opaque32(lane) >> 4) * 128 + (opaque32(lane) & 7) * 16)
#define SLOT(st) opaque64(slot0 + ((st) & 3) * 12288 + ((st) & 4) * 32)
  float* const slot0 = opaque64(g_slot + (rank * 1024 + warp * 128 + lane) * 4);
  const uint32_t woa = opaque32(sb + R_WO + warp * 12288 + ((lane >> 4) * 8 + (lane & 7)) * 32 + ((((lane >> 3) ^ (lane >> 2)) & 1) << 4));
  const bool has_wo = WG == 0 || isC || w < 3;
  float acc[20];
  uint32_t pk[8] = {0u, 0u, 0u, 0u, 0u, 0u, 0u, 0u};

  auto forward = [&](auto rd, const uint32_t* v, int st, uint32_t tries) {
    constexpr int RD = decltype(rd)::value;
    uint32_t u[6];
#pragma unroll
    for (int j = 0; j < 6; j++) u[j] = movm(v[4 * (j / 3) + j % 3]);
    const bool all3 = RD == 0 || w < 3;
    if (RD == 0) {
      const uint32_t a = L16 + R_M1 + w * 768, a2 = L8 + R_M1 + 512 + w * 768;
      st_async4(a + to1 + 3072, u, bars + to1 + B_MB + 8); st_async2(a2 + to1 + 3072, u[4], u[5], bars + to1 + B_MB + 8);
      sts128(a, u[0], u[1], u[2], u[3]); sts64(a2, u[4], u[5]);
      __syncwarp();
      if (elect_one()) mbar_arrive(bars + B_MB);
      st_async4(a + to2 + 6144, u, bars + to2 + B_MB + 16); st_async2(a2 + to2 + 6144, u[4], u[5], bars + to2 + B_MB + 16);
    } else {
      const uint32_t a = L4 + R_M2 + rank * 2304 + w * 768;
#pragma unroll
      for (int j = 0; j < 6; j++) if (j < 2 || all3) st_async1(a + to1 + j * 128, u[j], bars + to1 + B_MB + 24);
#pragma unroll
      for (int j = 0; j < 6; j++) if (j < 2 || all3) st_async1(a + to2 + j * 128, u[j], bars + to2 + B_MB + 24);
      if (SELF_STAS) {
#pragma unroll
        for (int j = 0; j < 6; j++) if (j < 2 || all3) st_async1(a + j * 128, u[j], bars + B_MB + 24);
      } else {
#pragma unroll
        for (int j = 0; j < 6; j++) if (j < 2 || all3) sts32(a + j * 128, u[j]);
        __syncwarp();
        if (elect_one()) mbar_arrive(bars + B_MB + 24);
      }
    }
  };

  auto send_vt = [&]() {
    if (elect_one()) {
      const uint32_t src = sb + R_VT + warp * 1024;
      bulk_s2s(src + to1, src, 1024, bars + to1 + B_VT);
      bulk_s2s(src + to2, src, 1024, bars + to2 + B_VT);
    }
  };
  auto store_att = [&](int sg) {
    uint32_t* op = reinterpret_cast<uint32_t*>(g_att + (size_t)((sg >> 2) * 64 + head * 2 + rank) * 16384 + (2 * w * 16 + (sg & 3) * 4) * 128) + opaque32(lane);
#pragma unroll
    for (int j = 0; j < 8; j++) op[(j & 1) * 512 + (j >> 1) * 32] = pk[j];
  };

  if (WG == 0) bar_arrive<NB_G, 256>();
#pragma unroll 1
  for (int s = -1; s < NSEG; s++) {
    const uint32_t par = (s + 1) & 1;
    const uint32_t last = s == NSEG - 1;
    TRACE(0);
    {
      float c[NCH][4];
      uint32_t b[3][6];
      const uint32_t ma = L16, m8 = L8;
#pragma unroll
      for (int i = 0; i < 18; i++) {
        if (i < 16) {
          if (i % 4 == 0 && !(i == 4 && TOP2)) mbar_wait(bars + B_MB + (i / 4) * 8, par ^ 1);
          if (i == 0 && TOP2) mbar_wait(bars + B_MB + 8, par ^ 1);
          if (i % 4 == 0) TRACE(1 + i / 4);
          if (i < 12) { lds128(b[i % 3], ma + R_M1 + i * 768); lds64(b[i % 3] + 4, m8 + R_M1 + 512 + i * 768); }
          else { ldsm4(b[i % 3], ma + R_M2 + 4096 + (i - 12) * 768); ldsm2(b[i % 3] + 4, ma + R_M2 + 4096 + 512 + (i - 12) * 768); }
          if (WG == 1 && i == BX_I) {
            bar_sync<NB_G, 256>();
            if (!last && elect_one()) load_chunk(sb + R_GB + w * 4096, s + 1, g0, bars + B_FB);
          }
          if (i == CX_I) {
            if (isC && s >= 0) send_vt();
            if (WG == 1 && ATT_LATE && !isC && s > 0) store_att(s - 1);
          }
          __syncwarp();
        }
        if (i >= 2) {
          const int j = i - 2;
#pragma unroll
          for (int q = 0; q < 3; q++) {
            const uint32_t* f = W[3 * j + q];
            if (3 * j + q < NCH) hmma0(c[3 * j + q], f[0], f[1], f[2], f[3], b[j % 3][2 * q], b[j % 3][2 * q + 1]);
            else hmma(c[(3 * j + q) % NCH], f[0], f[1], f[2], f[3], b[j % 3][2 * q], b[j % 3][2 * q + 1]);
          }
        }
        if (i == 14) zero_regs<16>(acc);
        if (i == 16) mbar_wait(bars + B_FA, last);
      }
#pragma unroll
      for (int j = 0; j < 4; j++) acc[16 + j] = NCH == 3 ? (c[0][j] + c[1][j]) + c[2][j] : (c[0][j] + c[1][j]) + (c[2][j] + c[NCH - 1][j]);
    }
    TRACE(5);
    bar_sync<NB_H, 256>();
    WG_FENCE();
#pragma unroll
    for (int k = 0; k < 16; k++) wg_ss40<0>(acc, dsc.tail_a[WG * 16 + k], dsc.tail_b[k]);
    WG_COMMIT();
    uint32_t vt[4][4];
    {
      const uint32_t a = opaque32(L4 + w * 256 + (isC ? WG * 1024 + R_VM : R_QK + 4096 + WG * 5120));
      const uint32_t qa = L16 + R_QK, xa = opaque32(LV + w * 2048 + (WG == 0 ? 0 : (opaque32(lane) & 8) * 64 + R_QK + 5120 - R_VT));
      const uint32_t d = opaque32(L4 + R_XS + rank * 640 + w * 256);
      if (s == 0) {
        mbar_wait_safe(bars + B_WO, 0);
        TS(10);
        if (WG == 1 && head == 0 && rank == 0 && w == 0 && elect_one()) red_add_u32(&g_flags[FL_GO], 1);
      }
      mbar_wait(bars + B_FB, last);
      if (WG == 0) mbar_wait(bars + B_VT, par);
      WG_WAIT(0);
      reg_fence<20>(acc);
      TRACE(6);
      const uint32_t p0 = pack2(acc[16], acc[17]), p1 = pack2(acc[18], acc[19]);
      sts32(a, p0); sts32(a + 128, p1);
      if (isC) {
        st_async1(a + to1, p0, bars + B_VM + to1); st_async1(a + to1 + 128, p1, bars + B_VM + to1);
        st_async1(a + to2, p0, bars + B_VM + to2); st_async1(a + to2 + 128, p1, bars + B_VM + to2);
      }
      if (WG == 0) {
        bar_arrive<NB_A, 256>();
        if (Q_FENCE && !isC) fence_async_smem();
#pragma unroll
        for (int i = 0; i < 4; i++) ldsm4(vt[i], xa + (i >> 1) * 1024 + (i & 1) * 256);
        bar_sync<NB_S, 256>();
      } else {
        bar_sync<NB_A, 256>();
        if (!isC) {
          if (w < 3) {
            uint32_t q[8], k[4][4];
            ldsm4t(q, qa + 4096); ldsm4t(k[0], xa); ldsm4t(k[1], xa + 256);
            ldsm4t(q + 4, qa + 4096 + 512); ldsm4t(k[2], xa + 512); ldsm4t(k[3], xa + 768);
            float x[4], y[4];
            hmma0(x, k[0][0], k[0][1], k[0][2], k[0][3], q[0], q[1]); hmma0(y, k[1][0], k[1][1], k[1][2], k[1][3], q[2], q[3]);
            hmma(x, k[2][0], k[2][1], k[2][2], k[2][3], q[4], q[5]); hmma(y, k[3][0], k[3][1], k[3][2], k[3][3], q[6], q[7]);
            const uint32_t s0 = pack2(x[0] + y[0], x[1] + y[1]), s1 = pack2(x[2] + y[2], x[3] + y[3]);
            st_async1(d + to1, s0, bars + B_XS + to1);
            st_async1(d + to2, s0, bars + B_XS + to2);
            if (w < 2) { st_async1(d + to1 + 128, s1, bars + B_XS + to1); st_async1(d + to2 + 128, s1, bars + B_XS + to2); sts32(d + 128, s1); }
            sts32(d, s0);
          }
        }
        bar_arrive<NB_S, 256>();
      }
    }
    if (WG == 1) {
      if (!last && elect_one()) load_chunk(sb + R_GA + w * 4096, s + 1, g1, bars + B_FA);
      {
        if (w > 0 && elect_one()) mbar_expect(bars + B_MB + 8 * w, w < 3 ? 3072 : SELF_STAS ? 28 * 256 : isC ? 18 * 256 : 19 * 256);
      }
      fence_async_smem();
      bar_sync<NB_B, 256>();
    }
    TRACE(7);
    WG_FENCE();
#pragma unroll
    for (int k = 0; k < 16; k++) wg_rs32<1>(acc, W[k][0], W[k][1], W[k][2], W[k][3], dsc.tok[16 + k]);
    WG_COMMIT();
    uint32_t wa[3][4];
    const uint32_t oxa = L16 + R_OX;
    if (WG == 0) {
      const uint32_t vma = oxa - (R_OX - R_VM) + w * 512, oa = opaque32(L4 + w * 512 + R_OX);
      TRACE(8);
      mbar_wait(bars + B_XS, par);
      TRACE(9);
      float sv[10];
      {
        uint32_t x[10];
        ldsm4t(x, oxa - (R_OX - R_XS)); ldsm4t(x + 4, oxa - (R_OX - R_XS) + 512); ldsm2t(x + 8, oxa - (R_OX - R_XS) + 1024);
        bar_arrive<NB_B, 256>();
#pragma unroll
        for (int j = 0; j < 5; j++) x[j] = hadd2(x[j], x[j + 5]);
        exp10(sv, x);
      }
      WG_WAIT(0);
      bar_arrive<NB_X, 256>();
      mbar_wait(bars + B_VM, par);
      uint32_t vm[4];
      ldsm4(vm, vma);
      uint32_t pb[5];
#pragma unroll
      for (int j = 0; j < 5; j++) pb[j] = pack2(sv[2 * j], sv[2 * j + 1]);
      TRACE(10);
      float o0[4], o1[4], sm[4];
      const uint32_t ONE = 0x3f803f80u;
      hmma0(o0, vt[0][0], vt[0][1], vt[0][2], vt[0][3], pb[0], pb[1]);
      hmma0(o1, vt[2][0], vt[2][1], vt[2][2], vt[2][3], pb[0], pb[1]);
      hmma0(sm, ONE, ONE, ONE, ONE, pb[0], pb[1]);
      hmma(sm, ONE, ONE, ONE, ONE, pb[2], pb[3]);
      hmma(o0, vt[1][0], vt[1][1], vt[1][2], vt[1][3], pb[2], pb[3]);
      hmma(o1, vt[3][0], vt[3][1], vt[3][2], vt[3][3], pb[2], pb[3]);
      hmma_k8(sm, ONE, ONE, pb[4]);
      hmma_k8(o0, vm[0], vm[1], pb[4]);
      hmma_k8(o1, vm[2], vm[3], pb[4]);
#pragma unroll
      for (int i = 0; i < 3; i++) ldsm4t(wa[i], woa + i * 4096);
      __syncwarp();
      const float i0 = rcp(sm[0]), i1 = rcp(sm[1]);
      sts32(oa, pack2(o0[0] * i0, o0[1] * i1)); sts32(oa + 128, pack2(o0[2] * i0, o0[3] * i1));
      sts32(oa + 256, pack2(o1[0] * i0, o1[1] * i1)); sts32(oa + 384, pack2(o1[2] * i0, o1[3] * i1));
      TRACE(11);
      bar_sync<NB_C, 128>();
    } else {
      if (!isC) {
        constexpr uint64_t dQ = mkdesc(0x400 + R_QK, 128, 1024, 0), dK = mkdesc(0x400 + R_QK + 5120, 128, 1024, 0);
        float sc[16];
        zero_regs<16>(sc);
        WG_FENCE();
#pragma unroll
        for (int k = 0; k < 4; k++) wg_ss32<1>(sc, dK + k * 16, dQ + k * 16);
        WG_COMMIT();
        const uint32_t top = rank == 0 ? to2 : to1, e = L4 + R_P + w * 256;
        WG_WAIT(0);
        bar_sync<NB_X, 256>();
        if (!last && elect_one()) load_chunk(sb + R_GB + w * 4096, s + 1, g2, bars + B_FB);
        reg_fence<16>(sc);
        if (w < 3) {
#pragma unroll
          for (int j = 0; j < 8; j++) {
            if ((j & 1) ? (j > 1 && (w == 0 || (w == 1 && j == 7))) : (j >= 4 || w != 1)) {
              const uint32_t t = pack2(sc[2 * j], sc[2 * j + 1]), o = (j >> 1) * 768 + (j & 1) * 128;
              st_async1(e + top + 3072 + o, t, bars + top + B_TS);
              sts32(e + o, t);
            }
          }
          __syncwarp();
          if (elect_one()) mbar_arrive(bars + B_TS);
        }
      } else {
        WG_WAIT(0);
        bar_sync<NB_X, 256>();
        if (!last && elect_one()) load_chunk(sb + R_GB + w * 4096, s + 1, g2, bars + B_FB);
      }
      TRACE(8);
      mbar_wait(bars + B_FA, 1);
      TRACE(11);
    }
    if (has_wo) {
      float* rslot = SLOT(s);
      uint32_t ob[4][4];
      float c[3][4];
      if (WG == 1) {
#pragma unroll
        for (int i = 0; i < 3; i++) ldsm4t(wa[i], woa + i * 4096);
        bar_sync<NB_D, 256>();
      }
      ldsm4t(ob[0], oxa);
      __syncwarp();
#pragma unroll
      for (int k = 0; k < 8; k++) {
        uint32_t nx[3][4];
        if ((k & 1) == 0 && k < 6) { ldsm4t(ob[(k >> 1) + 1], oxa + ((k >> 1) + 1) * 512); __syncwarp(); }
#pragma unroll
        for (int i = 0; i < 3; i++) {
          const uint32_t* o = ob[k >> 1] + (k & 1) * 2;
          if (k < 7) { ldsm4t(nx[i], woa + i * 4096 + (k + 1) * 512); if (i == 2) __syncwarp(); }
          if (k == 0) hmma0(c[i], wa[i][0], wa[i][1], wa[i][2], wa[i][3], o[0], o[1]);
          else hmma(c[i], wa[i][0], wa[i][1], wa[i][2], wa[i][3], o[0], o[1]);
#pragma unroll
          for (int q = 0; q < 4; q++) if (k < 7) wa[i][q] = nx[i][q];
        }
        if (k == ND_K && WG == 0) bar_arrive<NB_D, 256>();
      }
      const float* cv = &c[0][0];
      uint32_t r[6];
#pragma unroll
      for (int j = 0; j < 6; j++) r[j] = pack2(cv[2 * j], cv[2 * j + 1]);
      asm volatile("{\n.reg .pred p;\nsetp.lt.s32 p, %8, 0;\n@p bra.uni SKIP;\n"
                   "red.relaxed.gpu.global.add.noftz.v4.bf16x2 [%0], {%1, %2, %3, %7};\n"
                   "red.relaxed.gpu.global.add.noftz.v4.bf16x2 [%0+1024], {%4, %5, %6, %7};\nSKIP:\n}"
                   :: "l"(rslot), "r"(r[0]), "r"(r[1]), "r"(r[2]), "r"(r[3]), "r"(r[4]), "r"(r[5]), "r"(0x3f800000), "r"(s) : "memory");
    } else {
      bar_arrive<NB_D, 256>();
      if ((s & 3) == 0) {
        fence_gpu();
        if (s > 0 && elect_one()) red_add_u32(&g_flags[FL_ATT + 2 * (s - 4)], 1);
      }
      if (rank == 0 || head < 16)
        reinterpret_cast<uint4*>(g_slot)[((s + 2) & 3) * 3072 + ((s - 2) & 4) * 8 + rank * 2048 + head * 64 + opaque32(lane)] = make_uint4(0, 0, 0, 0);
    }
    const uint32_t t_red = clk32();
    uint32_t v[8];
    const float* slot = SLOT(s);
    TRACE(13);
    if (WG == 0) {
      if (!isC) {
        const int ln = opaque32(lane), kg = w - (ln >> 3);
        const uint32_t r16 = sb + R_P + w * 768 + (ln & 7) * 16;
        const uint32_t ta = r16 + (kg >= 0 ? kg * 128 : 640);
        const int dg = (ln >> 2) - 2 * (ln & 3);
        const uint32_t keep = dg > 0 ? 0xffffffffu : dg == 0 ? 0x0000ffffu : 0u;
        mbar_wait(bars + B_TS, par);
        uint32_t x[6], y[4];
        ldsm4t(x, ta); ldsm4t(y, ta + 3072); ldsm2t(x + 4, r16 + 512 + ((ln >> 3) & 1) * 3072);
#pragma unroll
        for (int j = 0; j < 5; j++) x[j] = hadd2(x[j], j < 4 ? y[j] : x[5]);
        x[0] = (x[0] & keep) | (0xff80ff80u & ~keep);
        float sv[10];
        exp10(sv, x);
        float sum = (((sv[0] + sv[1]) + (sv[2] + sv[3])) + ((sv[4] + sv[5]) + (sv[6] + sv[7]))) + (sv[8] + sv[9]);
        sum += __shfl_xor_sync(0xffffffffu, sum, 1);
        sum += __shfl_xor_sync(0xffffffffu, sum, 2);
        const float inv = rcp(sum);
#pragma unroll
        for (int j = 0; j < 5; j++) x[j] = pack2(sv[2 * j] * inv, sv[2 * j + 1] * inv);
        stsm4(r16 + (kg & 3) * 128, x);
        sts32(sb + ln * 4 + w * 768 + R_P + 512, x[4]);
        fence_async_smem();
        bar_arrive<NB_P, 256>();
      }
      while (clk32() - t_red < POLL_DELAY) {}
      load_red(v, slot);
      bar_sync<NB_E, 256>();
    } else {
      mbar_wait(bars + B_FB, 1);
    }
    TRACE(14);
    float ao[16];
    if (WG == 1) zero_regs<16>(ao);
    WG_FENCE();
#pragma unroll
    for (int k = 0; k < 32; k++) {
      if (WG == 0 && k == 16) WG_COMMIT();
      wg_rs32<1>(acc, W[16 + k][0], W[16 + k][1], W[16 + k][2], W[16 + k][3], dsc.tok[k]);
    }
    WG_COMMIT();
    TRACE(12);
    if (WG == 1) {
      if (!isC) {
        constexpr uint64_t dP = mkdesc(0x400 + R_P, 128, 768, 0);
        const uint64_t dV = mkdesc(0x400 + R_VT, 128, 512, 0) + rank * 256, dM = mkdesc(0x400 + R_VM, 0, 128, 0) + rank * 64;
        bar_sync<NB_P, 256>();
        WG_FENCE();
        wg_ss32<0>(ao, dV, dP); wg_ss32<0>(ao, dV + 16, dP + 16); wg_ss32<0>(ao, dM, dP + 32);
        WG_COMMIT();
      }
      bar_arrive<NB_E, 256>();
      if (elect_one()) mbar_expect(bars + B_XS + 8 * w, arm_bytes);
      while (clk32() - t_red < POLL_DELAY1) {}
      load_red(v, slot);
      bar_arrive<NB_W0, 128>();
    } else {
      WG_WAIT(1);
      bar_arrive<NB_F, 256>();
      sched_fence(head, 100);
      v[3] = opaque32(v[3]);
      const uint32_t tries = finish_red(v, slot);
      forward(std::integral_constant<int, 0>(), v, s, tries);
      TRACE(16);
    }
    WG_WAIT(0);
    reg_fence<16>(acc);
    if (WG == 0) bar_arrive<NB_G, 256>();
    TRACE(15);
    {
      uint32_t pq[8];
#pragma unroll
      for (int j = 0; j < 8; j++) pq[j] = pack2(acc[2 * j], acc[2 * j + 1]);
      if (WG == 1) {
        reg_fence<16>(ao);
#pragma unroll
        for (int j = 0; j < 8; j++) pk[j] = pack2(ao[2 * j], ao[2 * j + 1]);
      }
      if (!isC) {
        const uint32_t q = L4 + w * 256 + R_QK + WG * 5120;
#pragma unroll
        for (int j = 0; j < 8; j++) sts32(q + (j >> 1) * 1024 + (j & 1) * 128, pq[j]);
        if (WG == 1 && !ATT_LATE && s >= 0) store_att(s);
      } else {
        const uint32_t a = LV + warp * 1024;
        stsm4(a, pq); stsm4(a + 256, pq + 4);
      }
    }
    TRACE(17);
    if (WG == 1) {
      auto refill = [&]() {
        bar_sync<NB_F, 256>();
        if (s < NSEG - 2 && elect_one()) load_chunk(sb + R_GA + w * 4096, s + 2, 12 + w, bars + B_FA);
      };
      if (RF_FIRST) refill();
      if (has_wo) { v[3] = opaque32(v[3]); const uint32_t tries = finish_red(v, slot); forward(std::integral_constant<int, 1>(), v, s, tries); }
      if (!RF_FIRST) refill();
      TRACE(16);
    }
    if (isC && V_FENCE) { fence_async_smem(); __syncwarp(); }
    TRACE(18);
  }
  if (WG == 1 && ATT_LATE && !isC) store_att(NSEG - 1);
  if (WG == 1) bar_sync<NB_G, 256>();
  mbar_wait_safe(bars + B_MB + 8, 0); mbar_wait_safe(bars + B_MB + 16, 0); mbar_wait_safe(bars + B_MB + 24, 0);
#undef L16
#undef L8
#undef L4
#undef SLOT
#undef LV
}

__global__ void __cluster_dims__(3, 1, 1) __launch_bounds__(256, 1)
kernel_R(const __grid_constant__ CUtensorMap tmq, const __grid_constant__ CUtensorMap tmk, const __grid_constant__ CUtensorMap tmv,
         const __grid_constant__ CUtensorMap tmo, const __grid_constant__ CUtensorMap tmm, const __nv_bfloat16* __restrict__ x,
         const __nv_bfloat16* __restrict__ mem0, const __nv_bfloat16* __restrict__ cvec, const __grid_constant__ RDesc dsc) {
  extern __shared__ __align__(1024) uint8_t smem[];
  const uint32_t sb = smem_u32(smem);
  uint32_t rank; asm("mov.u32 %0, %%cluster_ctarank;" : "=r"(rank));
  rank = __shfl_sync(0xffffffffu, rank, 0);
  const int cta = blockIdx.x, head = __shfl_sync(0xffffffffu, cta / 3, 0);
  const int tid = threadIdx.x, lane = tid & 31;
  const int warp = __shfl_sync(0xffffffffu, tid >> 5, 0);
  const int wg = warp >> 2, w = warp & 3;
  const uint32_t bars = sb + R_BAR;
  const CUtensorMap* tmw = rank == 2 ? &tmv : (wg == 0 ? &tmq : &tmk);
  const int fcol = head * 128 + (rank == 2 ? wg * 64 : (int)rank * 64);

  asm volatile("griddepcontrol.launch_dependents;");
  uint32_t W[48][4];
  {
    if (sb != (rank << 24) + 0x400) __trap();
    if (tid == 0) {
      sts64(bars + 248, rank, head);
      mbar_init(bars + B_MB, 4); mbar_init(bars + B_MB + 8, 1); mbar_init(bars + B_MB + 16, 1); mbar_init(bars + B_MB + 24, SELF_STAS ? 1 : rank == 2 ? 5 : 4);
      for (int i = B_XS; i <= B_X; i += 8) mbar_init(bars + i, i == B_FA || i == B_FB || (i == B_TS && rank < 2) ? 4 : 1);
      asm volatile("fence.mbarrier_init.release.cluster;" ::: "memory");
      fence_async_smem();
    }
    __syncthreads();
    asm volatile("barrier.cluster.arrive.relaxed.aligned;" ::: "memory");
    TS(0);
    const int nwm = rank == 0 ? 6 : 5, wm0 = rank == 0 ? 0 : 5 * rank + 1, nrg = cta < 64 ? 3 : 2;
    if (elect_one()) {
      if (warp == 0) { mbar_expect(bars + B_WM, nwm * 8192); mbar_expect(bars + B_X, nrg * 16384); }
      if (warp < nwm) tma2d(sb + R_GA + warp * 8192, &tmm, head * 64, (wm0 + warp) * 64, bars + B_WM);
#pragma unroll 1
      for (int r = 0; r < nrg; r++) bulk_g2s(sb + R_TAIL + (r * 8 + warp) * 2064, x + (size_t)((cta + 96 * r) * 8 + warp) * D_, 2048, bars + B_X);
      if (w == 0) mbar_expect(bars + B_STG + wg * 16, 49152);
      if (w < 2) tma2d(sb + R_WO + wg * 49152 + w * 8192, tmw, fcol, rot_chunk(w, rank) * 64, bars + B_STG + wg * 16);
    }
    float* scr = reinterpret_cast<float*>(smem + R_VT);
#pragma unroll 1
    for (int i = tid; i < nwm * 64; i += 256) {
      const float c = __bfloat162float(cvec[wm0 * 64 + i]);
      scr[i] = __bfloat162float(__float2bfloat16(c / (1.f + __expf(-c))));
    }
    if (tid < 128) {
      uint32_t e[4] = {0u, 0u, 0u, 0u};
      if (cta >= 72 && (tid & 32)) {
        const uint16_t* mp = reinterpret_cast<const uint16_t*>(mem0) + 2 * (lane & 3) * D_ + (lane >> 2);
#pragma unroll
        for (int q = 0; q < 3; q++) {
          const int n = 3 * (tid >> 6) + q, col = wo_tile(3 * (cta & 7) + (n >> 1), (cta - 72) >> 3) * 16 + 8 * (n & 1);
          e[q] = mp[col] | (uint32_t)mp[col + D_] << 16;
        }
        e[3] = 0x42000000u;
      }
      reinterpret_cast<uint4*>(g_slot)[cta * 128 + tid] = make_uint4(e[0], e[1], e[2], e[3]);
    }
    __syncthreads();
    TS(1);
    mbar_wait_safe(bars + B_WM, 0);
    if (elect_one()) tma2d(sb + R_WO + wg * 49152 + (2 + w) * 8192, tmw, fcol, rot_chunk(2 + w, rank) * 64, bars + B_STG + wg * 16);
    {
      float a[8];
#pragma unroll
      for (int j = 0; j < 8; j++) a[j] = 0.f;
#pragma unroll 2
      for (int i = 0; i < 2 * nwm; i++) {
        uint32_t u[4];
        lds128(u, sb + R_GA + i * 4096 + tid * 16);
        const float sc = scr[i * 32 + (tid >> 3)];
#pragma unroll
        for (int j = 0; j < 4; j++) { a[2 * j] += sc * bf_lo(u[j]); a[2 * j + 1] += sc * bf_hi(u[j]); }
      }
#pragma unroll
      for (int j = 0; j < 8; j++) { a[j] += __shfl_xor_sync(0xffffffffu, a[j], 8); a[j] += __shfl_xor_sync(0xffffffffu, a[j], 16); }
      if (lane < 8) {
        sts128(sb + R_VT + 1536 + warp * 256 + lane * 32, __float_as_uint(a[0]), __float_as_uint(a[1]), __float_as_uint(a[2]), __float_as_uint(a[3]));
        sts128(sb + R_VT + 1552 + warp * 256 + lane * 32, __float_as_uint(a[4]), __float_as_uint(a[5]), __float_as_uint(a[6]), __float_as_uint(a[7]));
      }
    }
    __syncthreads();
    TS(2);
    if (warp == 7) {
      float t0 = 0.f, t1 = 0.f;
#pragma unroll
      for (int i = 0; i < 8; i++) { float t[2]; lds64f(t, sb + R_VT + 1536 + i * 256 + lane * 8); t0 += t[0]; t1 += t[1]; }
      reinterpret_cast<float2*>(g_modp + rank * 2048 + head * 64)[lane] = make_float2(t0, t1);
      fence_gpu();
      __syncwarp();
      if (lane == 0) red_add_u32(&g_flags[FL_S1], 1);
      __syncwarp();
    }
    mbar_wait_safe(bars + B_X, 0);
#pragma unroll 1
    for (int r = 0; r < nrg; r++) {
      float f[32];
#pragma unroll
      for (int i = 0; i < 4; i++) {
        uint32_t u[4];
        lds128(u, sb + R_TAIL + (r * 8 + warp) * 2064 + i * 512 + lane * 16);
#pragma unroll
        for (int j = 0; j < 4; j++) { f[8 * i + 2 * j] = bf_lo(u[j]); f[8 * i + 2 * j + 1] = bf_hi(u[j]); }
      }
      float t = 0.f;
#pragma unroll
      for (int i = 0; i < 32; i++) t += f[i];
#pragma unroll
      for (int o = 1; o < 32; o <<= 1) t += __shfl_xor_sync(0xffffffffu, t, o);
      const float mean = t * (1.f / D_);
      t = 0.f;
#pragma unroll
      for (int i = 0; i < 32; i++) t = fmaf(f[i] - mean, f[i] - mean, t);
#pragma unroll
      for (int o = 1; o < 32; o <<= 1) t += __shfl_xor_sync(0xffffffffu, t, o);
      const float rstd = rsqrtf(t * (1.f / D_) + 1e-5f);
      if (lane == 0) sts64(sb + R_VT + 3584 + (r * 8 + warp) * 8, __float_as_uint(rstd), __float_as_uint(-mean * rstd));
    }
    TS(3);
    if (w < PF1 && elect_one()) tma2d_prefetch(tmw, fcol, rot_chunk(6 + w, rank) * 64);
    if (tid == 0) wait_flag(&g_flags[FL_S1], 96);
    __syncthreads();
    TS(4);
    {
      float4 p[6];
#pragma unroll
      for (int i = 0; i < 6; i++) p[i] = __ldcg(reinterpret_cast<const float4*>(g_modp + (i >> 1) * 2048) + 2 * tid + (i & 1));
      if (w < PF2 && elect_one()) tma2d_prefetch(tmw, fcol, (9 + w) * 64);
      sts128(sb + R_VT + 5120 + tid * 16, pack2(p[0].x + p[2].x + p[4].x, p[0].y + p[2].y + p[4].y), pack2(p[0].z + p[2].z + p[4].z, p[0].w + p[2].w + p[4].w),
             pack2(p[1].x + p[3].x + p[5].x, p[1].y + p[3].y + p[5].y), pack2(p[1].z + p[3].z + p[5].z, p[1].w + p[3].w + p[5].w));
    }
    __syncthreads();
#pragma unroll 2
    for (int it = 0; it < 4 * nrg; it++) {
      const int r = it >> 2, rg = cta + 96 * r, c = 16 * warp + (lane >> 3) + 4 * (it & 3);
      uint32_t a[4], b[4], u[4], o[4];
      float t[2];
      lds128(u, sb + R_TAIL + (r * 8 + (lane & 7)) * 2064 + c * 16);
      lds128(a, sb + R_VT + 5120 + c * 16); lds128(b, sb + R_VT + 7168 + c * 16);
      lds64f(t, sb + R_VT + 3584 + (r * 8 + (lane & 7)) * 8);
#pragma unroll
      for (int j = 0; j < 4; j++)
        o[j] = pack2(fmaf(fmaf(bf_lo(u[j]), t[0], t[1]), 1.f + bf_lo(b[j]), bf_lo(a[j])), fmaf(fmaf(bf_hi(u[j]), t[0], t[1]), 1.f + bf_hi(b[j]), bf_hi(a[j])));
      *reinterpret_cast<uint4*>(g_h + (size_t)(rg >> 2) * 65536 + (lane & 7) * 16 + (c & 7) * 128 +
                                (c < 96 ? (c >> 3) * 4096 + (rg & 3) * 1024 : 49152 + (rg & 3) * 4096 + ((c >> 3) - 12) * 1024)) =
          make_uint4(o[0], o[1], o[2], o[3]);
    }
    TS(5);
    __syncthreads();
    TS(6);
    if (w < PF3 && elect_one()) tma2d(sb + R_TAIL + warp * 8192, tmw, fcol, 768 + w * 64, bars + B_TAIL);
    if (warp == 3 && lane == 0) { fence_gpu(); red_add_u32(&g_flags[FL_S2], 1); }
    __syncwarp();

    const uint32_t a0 = opaque32(sb + R_WO + wg * 49152 + ((lane >> 4) * 8 + (lane & 7)) * 128 + (((2 * w + ((lane >> 3) & 1)) ^ (lane & 7)) << 4));
    mbar_wait_safe(bars + B_STG + wg * 16, 0);
    TS(7);
#pragma unroll
    for (int i = 0; i < 24; i++) ldsm4t(W[i], a0 + i * 2048);
    if (tid == 0) wait_flag(&g_flags[FL_S2], 96);
    __syncthreads();
    asm volatile("fence.proxy.async.global;" ::: "memory");
    if (elect_one()) {
      if (wg == 0) load_chunk(sb + R_GA + w * 4096, 0, 12 + w, bars + B_FA);
      if (w == 0) mbar_expect(bars + B_STG + wg * 16 + 8, 49152);
#pragma unroll 1
      for (int c = w; c < 6; c += 4) tma2d(sb + R_WO + wg * 49152 + c * 8192, tmw, fcol, rot_chunk(6 + c, rank) * 64, bars + B_STG + wg * 16 + 8);
      if (warp == 0) mbar_expect(bars + B_TAIL, 65536);
      if (w >= PF3) tma2d(sb + R_TAIL + warp * 8192, tmw, fcol, 768 + w * 64, bars + B_TAIL);
      if (wg == 1) mbar_expect(bars + B_XS + 8 * w, w == 2 ? 0 : arm_size(w, rank == 2));
#pragma unroll 1
      for (int i = warp; i < PF4; i += 8) tma2d_prefetch(&tmo, 16 * wo_tile(i, rank), head * 128);
    }
    TS(8);
    mbar_wait_safe(bars + B_STG + wg * 16 + 8, 0);
    TS(9);
#pragma unroll
    for (int i = 0; i < 24; i++) ldsm4t(W[24 + i], a0 + i * 2048);
    __syncthreads();
    if (elect_one()) {
      const int n = rank == 2 ? 22 : 21;
      if (warp == 0) mbar_expect(bars + B_WO, n * 4096);
#pragma unroll 1
      for (int i = warp; i < n; i += 8) tma2d(sb + R_WO + i * 4096, &tmo, 16 * wo_tile(i, rank), head * 128, bars + B_WO);
    }
    sts32(sb + R_P + warp * 768 + 640 + lane * 4, wg == 0 ? 0u : 0xff80ff80u);
    mbar_wait_safe(bars + B_TAIL, 0);
    asm volatile("barrier.cluster.wait.aligned;\nbarrier.cluster.arrive.relaxed.aligned;\nbarrier.cluster.wait.aligned;" ::: "memory");
  }
  uint32_t rh[2];
  lds64(rh, bars + 248);
  rh[0] = __shfl_sync(0xffffffffu, rh[0], 0); rh[1] = __shfl_sync(0xffffffffu, rh[1], 0);
  if (wg == 0) r_main<0>(W, dsc, rh[1], rh[0], lane, w);
  else r_main<1>(W, dsc, rh[1], rh[0], lane, w);
  __syncthreads();
  if (rank < 2 && threadIdx.x == 0) { fence_gpu(); red_add_u32(&g_flags[FL_ATT + 8 * 15], 1); }
  asm volatile("barrier.cluster.arrive.release.aligned;\nbarrier.cluster.wait.acquire.aligned;" ::: "memory");
}

template <int TA> __device__ __forceinline__ void wg_ss256(float* d, uint64_t a, uint64_t b) {
  asm volatile("wgmma.mma_async.sync.aligned.m64n256k16.f32.bf16.bf16 {%0,%1,%2,%3,%4,%5,%6,%7,%8,%9,%10,%11,%12,%13,%14,%15,%16,%17,%18,%19,%20,%21,%22,%23,%24,%25,%26,%27,%28,%29,%30,%31,%32,%33,%34,%35,%36,%37,%38,%39,%40,%41,%42,%43,%44,%45,%46,%47,%48,%49,%50,%51,%52,%53,%54,%55,%56,%57,%58,%59,%60,%61,%62,%63,%64,%65,%66,%67,%68,%69,%70,%71,%72,%73,%74,%75,%76,%77,%78,%79,%80,%81,%82,%83,%84,%85,%86,%87,%88,%89,%90,%91,%92,%93,%94,%95,%96,%97,%98,%99,%100,%101,%102,%103,%104,%105,%106,%107,%108,%109,%110,%111,%112,%113,%114,%115,%116,%117,%118,%119,%120,%121,%122,%123,%124,%125,%126,%127}, %128, %129, 1, 1, 1, %130, 1;"
               : "+f"(d[0]), "+f"(d[1]), "+f"(d[2]), "+f"(d[3]), "+f"(d[4]), "+f"(d[5]), "+f"(d[6]), "+f"(d[7]),
                 "+f"(d[8]), "+f"(d[9]), "+f"(d[10]), "+f"(d[11]), "+f"(d[12]), "+f"(d[13]), "+f"(d[14]), "+f"(d[15]),
                 "+f"(d[16]), "+f"(d[17]), "+f"(d[18]), "+f"(d[19]), "+f"(d[20]), "+f"(d[21]), "+f"(d[22]), "+f"(d[23]),
                 "+f"(d[24]), "+f"(d[25]), "+f"(d[26]), "+f"(d[27]), "+f"(d[28]), "+f"(d[29]), "+f"(d[30]), "+f"(d[31]),
                 "+f"(d[32]), "+f"(d[33]), "+f"(d[34]), "+f"(d[35]), "+f"(d[36]), "+f"(d[37]), "+f"(d[38]), "+f"(d[39]),
                 "+f"(d[40]), "+f"(d[41]), "+f"(d[42]), "+f"(d[43]), "+f"(d[44]), "+f"(d[45]), "+f"(d[46]), "+f"(d[47]),
                 "+f"(d[48]), "+f"(d[49]), "+f"(d[50]), "+f"(d[51]), "+f"(d[52]), "+f"(d[53]), "+f"(d[54]), "+f"(d[55]),
                 "+f"(d[56]), "+f"(d[57]), "+f"(d[58]), "+f"(d[59]), "+f"(d[60]), "+f"(d[61]), "+f"(d[62]), "+f"(d[63]),
                 "+f"(d[64]), "+f"(d[65]), "+f"(d[66]), "+f"(d[67]), "+f"(d[68]), "+f"(d[69]), "+f"(d[70]), "+f"(d[71]),
                 "+f"(d[72]), "+f"(d[73]), "+f"(d[74]), "+f"(d[75]), "+f"(d[76]), "+f"(d[77]), "+f"(d[78]), "+f"(d[79]),
                 "+f"(d[80]), "+f"(d[81]), "+f"(d[82]), "+f"(d[83]), "+f"(d[84]), "+f"(d[85]), "+f"(d[86]), "+f"(d[87]),
                 "+f"(d[88]), "+f"(d[89]), "+f"(d[90]), "+f"(d[91]), "+f"(d[92]), "+f"(d[93]), "+f"(d[94]), "+f"(d[95]),
                 "+f"(d[96]), "+f"(d[97]), "+f"(d[98]), "+f"(d[99]), "+f"(d[100]), "+f"(d[101]), "+f"(d[102]), "+f"(d[103]),
                 "+f"(d[104]), "+f"(d[105]), "+f"(d[106]), "+f"(d[107]), "+f"(d[108]), "+f"(d[109]), "+f"(d[110]), "+f"(d[111]),
                 "+f"(d[112]), "+f"(d[113]), "+f"(d[114]), "+f"(d[115]), "+f"(d[116]), "+f"(d[117]), "+f"(d[118]), "+f"(d[119]),
                 "+f"(d[120]), "+f"(d[121]), "+f"(d[122]), "+f"(d[123]), "+f"(d[124]), "+f"(d[125]), "+f"(d[126]), "+f"(d[127])
               : "l"(a), "l"(b), "n"(TA));
}
template <int TA> __device__ __forceinline__ void wg_ss128(float* d, uint64_t a, uint64_t b) {
  asm volatile("wgmma.mma_async.sync.aligned.m64n128k16.f32.bf16.bf16 {%0,%1,%2,%3,%4,%5,%6,%7,%8,%9,%10,%11,%12,%13,%14,%15,%16,%17,%18,%19,%20,%21,%22,%23,%24,%25,%26,%27,%28,%29,%30,%31,%32,%33,%34,%35,%36,%37,%38,%39,%40,%41,%42,%43,%44,%45,%46,%47,%48,%49,%50,%51,%52,%53,%54,%55,%56,%57,%58,%59,%60,%61,%62,%63}, %64, %65, 1, 1, 1, %66, 1;"
               : "+f"(d[0]), "+f"(d[1]), "+f"(d[2]), "+f"(d[3]), "+f"(d[4]), "+f"(d[5]), "+f"(d[6]), "+f"(d[7]),
                 "+f"(d[8]), "+f"(d[9]), "+f"(d[10]), "+f"(d[11]), "+f"(d[12]), "+f"(d[13]), "+f"(d[14]), "+f"(d[15]),
                 "+f"(d[16]), "+f"(d[17]), "+f"(d[18]), "+f"(d[19]), "+f"(d[20]), "+f"(d[21]), "+f"(d[22]), "+f"(d[23]),
                 "+f"(d[24]), "+f"(d[25]), "+f"(d[26]), "+f"(d[27]), "+f"(d[28]), "+f"(d[29]), "+f"(d[30]), "+f"(d[31]),
                 "+f"(d[32]), "+f"(d[33]), "+f"(d[34]), "+f"(d[35]), "+f"(d[36]), "+f"(d[37]), "+f"(d[38]), "+f"(d[39]),
                 "+f"(d[40]), "+f"(d[41]), "+f"(d[42]), "+f"(d[43]), "+f"(d[44]), "+f"(d[45]), "+f"(d[46]), "+f"(d[47]),
                 "+f"(d[48]), "+f"(d[49]), "+f"(d[50]), "+f"(d[51]), "+f"(d[52]), "+f"(d[53]), "+f"(d[54]), "+f"(d[55]),
                 "+f"(d[56]), "+f"(d[57]), "+f"(d[58]), "+f"(d[59]), "+f"(d[60]), "+f"(d[61]), "+f"(d[62]), "+f"(d[63])
               : "l"(a), "l"(b), "n"(TA));
}
template <int TA> __device__ __forceinline__ void wg_ss256_first(float* d, uint64_t a, uint64_t b) {
  asm volatile("wgmma.mma_async.sync.aligned.m64n256k16.f32.bf16.bf16 {%0,%1,%2,%3,%4,%5,%6,%7,%8,%9,%10,%11,%12,%13,%14,%15,%16,%17,%18,%19,%20,%21,%22,%23,%24,%25,%26,%27,%28,%29,%30,%31,%32,%33,%34,%35,%36,%37,%38,%39,%40,%41,%42,%43,%44,%45,%46,%47,%48,%49,%50,%51,%52,%53,%54,%55,%56,%57,%58,%59,%60,%61,%62,%63,%64,%65,%66,%67,%68,%69,%70,%71,%72,%73,%74,%75,%76,%77,%78,%79,%80,%81,%82,%83,%84,%85,%86,%87,%88,%89,%90,%91,%92,%93,%94,%95,%96,%97,%98,%99,%100,%101,%102,%103,%104,%105,%106,%107,%108,%109,%110,%111,%112,%113,%114,%115,%116,%117,%118,%119,%120,%121,%122,%123,%124,%125,%126,%127}, %128, %129, 0, 1, 1, %130, 1;"
               : "=f"(d[0]), "=f"(d[1]), "=f"(d[2]), "=f"(d[3]), "=f"(d[4]), "=f"(d[5]), "=f"(d[6]), "=f"(d[7]),
                 "=f"(d[8]), "=f"(d[9]), "=f"(d[10]), "=f"(d[11]), "=f"(d[12]), "=f"(d[13]), "=f"(d[14]), "=f"(d[15]),
                 "=f"(d[16]), "=f"(d[17]), "=f"(d[18]), "=f"(d[19]), "=f"(d[20]), "=f"(d[21]), "=f"(d[22]), "=f"(d[23]),
                 "=f"(d[24]), "=f"(d[25]), "=f"(d[26]), "=f"(d[27]), "=f"(d[28]), "=f"(d[29]), "=f"(d[30]), "=f"(d[31]),
                 "=f"(d[32]), "=f"(d[33]), "=f"(d[34]), "=f"(d[35]), "=f"(d[36]), "=f"(d[37]), "=f"(d[38]), "=f"(d[39]),
                 "=f"(d[40]), "=f"(d[41]), "=f"(d[42]), "=f"(d[43]), "=f"(d[44]), "=f"(d[45]), "=f"(d[46]), "=f"(d[47]),
                 "=f"(d[48]), "=f"(d[49]), "=f"(d[50]), "=f"(d[51]), "=f"(d[52]), "=f"(d[53]), "=f"(d[54]), "=f"(d[55]),
                 "=f"(d[56]), "=f"(d[57]), "=f"(d[58]), "=f"(d[59]), "=f"(d[60]), "=f"(d[61]), "=f"(d[62]), "=f"(d[63]),
                 "=f"(d[64]), "=f"(d[65]), "=f"(d[66]), "=f"(d[67]), "=f"(d[68]), "=f"(d[69]), "=f"(d[70]), "=f"(d[71]),
                 "=f"(d[72]), "=f"(d[73]), "=f"(d[74]), "=f"(d[75]), "=f"(d[76]), "=f"(d[77]), "=f"(d[78]), "=f"(d[79]),
                 "=f"(d[80]), "=f"(d[81]), "=f"(d[82]), "=f"(d[83]), "=f"(d[84]), "=f"(d[85]), "=f"(d[86]), "=f"(d[87]),
                 "=f"(d[88]), "=f"(d[89]), "=f"(d[90]), "=f"(d[91]), "=f"(d[92]), "=f"(d[93]), "=f"(d[94]), "=f"(d[95]),
                 "=f"(d[96]), "=f"(d[97]), "=f"(d[98]), "=f"(d[99]), "=f"(d[100]), "=f"(d[101]), "=f"(d[102]), "=f"(d[103]),
                 "=f"(d[104]), "=f"(d[105]), "=f"(d[106]), "=f"(d[107]), "=f"(d[108]), "=f"(d[109]), "=f"(d[110]), "=f"(d[111]),
                 "=f"(d[112]), "=f"(d[113]), "=f"(d[114]), "=f"(d[115]), "=f"(d[116]), "=f"(d[117]), "=f"(d[118]), "=f"(d[119]),
                 "=f"(d[120]), "=f"(d[121]), "=f"(d[122]), "=f"(d[123]), "=f"(d[124]), "=f"(d[125]), "=f"(d[126]), "=f"(d[127])
               : "l"(a), "l"(b), "n"(TA));
}
template <int TA> __device__ __forceinline__ void wg_ss128_first(float* d, uint64_t a, uint64_t b) {
  asm volatile("wgmma.mma_async.sync.aligned.m64n128k16.f32.bf16.bf16 {%0,%1,%2,%3,%4,%5,%6,%7,%8,%9,%10,%11,%12,%13,%14,%15,%16,%17,%18,%19,%20,%21,%22,%23,%24,%25,%26,%27,%28,%29,%30,%31,%32,%33,%34,%35,%36,%37,%38,%39,%40,%41,%42,%43,%44,%45,%46,%47,%48,%49,%50,%51,%52,%53,%54,%55,%56,%57,%58,%59,%60,%61,%62,%63}, %64, %65, 0, 1, 1, %66, 1;"
               : "=f"(d[0]), "=f"(d[1]), "=f"(d[2]), "=f"(d[3]), "=f"(d[4]), "=f"(d[5]), "=f"(d[6]), "=f"(d[7]),
                 "=f"(d[8]), "=f"(d[9]), "=f"(d[10]), "=f"(d[11]), "=f"(d[12]), "=f"(d[13]), "=f"(d[14]), "=f"(d[15]),
                 "=f"(d[16]), "=f"(d[17]), "=f"(d[18]), "=f"(d[19]), "=f"(d[20]), "=f"(d[21]), "=f"(d[22]), "=f"(d[23]),
                 "=f"(d[24]), "=f"(d[25]), "=f"(d[26]), "=f"(d[27]), "=f"(d[28]), "=f"(d[29]), "=f"(d[30]), "=f"(d[31]),
                 "=f"(d[32]), "=f"(d[33]), "=f"(d[34]), "=f"(d[35]), "=f"(d[36]), "=f"(d[37]), "=f"(d[38]), "=f"(d[39]),
                 "=f"(d[40]), "=f"(d[41]), "=f"(d[42]), "=f"(d[43]), "=f"(d[44]), "=f"(d[45]), "=f"(d[46]), "=f"(d[47]),
                 "=f"(d[48]), "=f"(d[49]), "=f"(d[50]), "=f"(d[51]), "=f"(d[52]), "=f"(d[53]), "=f"(d[54]), "=f"(d[55]),
                 "=f"(d[56]), "=f"(d[57]), "=f"(d[58]), "=f"(d[59]), "=f"(d[60]), "=f"(d[61]), "=f"(d[62]), "=f"(d[63])
               : "l"(a), "l"(b), "n"(TA));
}

constexpr int H_STAGE = 49152, H_NST = 4;
constexpr int H_STG = H_NST * H_STAGE;
constexpr int H_VEC = H_STG + 16384;
constexpr int H_BAR = H_VEC + 6144;
constexpr int H_SMEM = H_BAR + 256;
constexpr int HB_FULL = 0, HB_EMPTY = 32, HB_IFULL = 64, HB_IEMPTY = 80, HB_VFULL = 96, HB_STGF = 112, HB_ITEM = 120, HB_SLOT = 128, HB_Q = 136;
enum { IT_END = 0, IT_MOD = 1, IT_XT = 2, IT_OUT = 3, IT_WS = 4, IT_F1 = 5, IT_F2 = 6, IT_STAT = 7 };
constexpr int N_MOD = 32, N_WS = 28, N_XT = 2, N_STAT = 4;
constexpr int MAX_ITEMS = 1400;
struct HList { uint32_t n; uint32_t it[MAX_ITEMS]; };
#define HT(i)

__device__ __forceinline__ void mbar_arrive_n(uint32_t b, uint32_t n) { asm volatile("mbarrier.arrive.shared::cta.b64 _, [%0], %1;" :: "r"(b), "r"(n) : "memory"); }
__device__ __forceinline__ void bulk_s2g(void* dst, uint32_t src, uint32_t bytes) {
  asm volatile("cp.async.bulk.global.shared::cta.bulk_group [%0], [%1], %2;" :: "l"(dst), "r"(src), "r"(bytes) : "memory");
}
__device__ __forceinline__ void tma2d_add(const CUtensorMap* m, int c0, int c1, uint32_t src) {
  asm volatile("cp.reduce.async.bulk.tensor.2d.global.shared::cta.add.tile.bulk_group [%0, {%2, %3}], [%1];" :: "l"(m), "r"(src), "r"(c0), "r"(c1) : "memory");
}
__device__ __forceinline__ void bulk_commit() { asm volatile("cp.async.bulk.commit_group;" ::: "memory"); }
template <int N> __device__ __forceinline__ void bulk_wait_read() { asm volatile("cp.async.bulk.wait_group.read %0;" :: "n"(N) : "memory"); }
__device__ __forceinline__ void bulk_wait_all() { asm volatile("cp.async.bulk.wait_group 0;" ::: "memory"); }
__device__ __forceinline__ uint32_t hfma2(uint32_t a, uint32_t b, uint32_t c) { uint32_t t; asm("fma.rn.bf16x2 %0, %1, %2, %3;" : "=r"(t) : "r"(a), "r"(b), "r"(c)); return t; }
__device__ __forceinline__ float lds32f(uint32_t a) { return __uint_as_float(lds32(a)); }

template <int BN, int TA>
__device__ __forceinline__ uint32_t h_mainloop(float* acc, uint32_t sb, int nst, uint32_t& st, uint32_t& ph, int wg, bool leader, bool borrow) {
  const uint64_t da0 = TA ? mkdesc(sb + wg * 1024, 2048, 128, 0) : mkdesc(sb + wg * 8192, 16, 1024, 1);
  const uint64_t db0 = mkdesc(sb + 16384, 8192, 1024, 1);
  uint32_t prev = st;
  {
    mbar_wait(sb + H_BAR + HB_FULL + st * 8, ph);
    HT(1);
    const uint64_t da = da0 + st * (H_STAGE >> 4), db = db0 + st * (H_STAGE >> 4);
    WG_FENCE();
    if (BN == 256) wg_ss256_first<TA>(acc, da, db); else wg_ss128_first<TA>(acc, da, db);
#pragma unroll
    for (int k = 1; k < 4; k++) {
      const uint64_t a = da + k * (TA ? 256 : 2), b = db + k * 128;
      if (BN == 256) wg_ss256<TA>(acc, a, b); else wg_ss128<TA>(acc, a, b);
    }
    WG_COMMIT();
    if (++st == H_NST) { st = 0; ph ^= 1; }
  }
#pragma unroll 1
  for (int i = 1; i < nst; i++) {
    mbar_wait(sb + H_BAR + HB_FULL + st * 8, ph);
    const uint64_t da = da0 + st * (H_STAGE >> 4), db = db0 + st * (H_STAGE >> 4);
    WG_FENCE();
#pragma unroll
    for (int k = 0; k < 4; k++) {
      const uint64_t a = da + k * (TA ? 256 : 2), b = db + k * 128;
      if (BN == 256) wg_ss256<TA>(acc, a, b); else wg_ss128<TA>(acc, a, b);
    }
    WG_COMMIT();
    WG_WAIT(1);
    if (leader) mbar_arrive(sb + H_BAR + HB_EMPTY + prev * 8);
    prev = st;
    if (++st == H_NST) { st = 0; ph ^= 1; }
  }
  WG_WAIT(0);
  reg_fence<BN / 2>(acc);
  if (!borrow && leader) mbar_arrive(sb + H_BAR + HB_EMPTY + prev * 8);
  HT(2);
  return prev;
}

template <int BN>
__device__ __forceinline__ void h_gated(const float* acc, uint32_t va, uint32_t stg, uint32_t slot, int warp, int lane) {
  const uint32_t ro = (warp * 16 + (lane & 7)) * 128, x0 = ((lane >> 3) ^ (lane & 7)) << 4;
  va += (lane & 3) * 32;
#pragma unroll
  for (int u = 0; u < BN / 64; u++) {
    if (u == 1) bar_sync<1, 256>();
    const uint32_t base = (u == 0 ? stg : slot + (u - 1) * 16384) + ro;
#pragma unroll
    for (int c2 = 0; c2 < 2; c2++) {
      const int c = 2 * u + c2;
      float g[8];
      lds128f(g, va + c * 128); lds128f(g + 4, va + c * 128 + 16);
#pragma unroll
      for (int h = 0; h < 2; h++) {
        uint32_t y[4];
#pragma unroll
        for (int j = 0; j < 4; j++) { const float* a = acc + c * 16 + j * 4 + h * 2; y[j] = pack2(g[2 * j] * a[0], g[2 * j + 1] * a[1]); }
        stsm4(base + h * 1024 + (x0 ^ (c2 << 6)), y);
      }
    }
  }
}

template <int BN>
__device__ __forceinline__ void h_swiglu(const float* acc, uint32_t va, uint32_t stg, uint32_t slot, int warp, int lane) {
  const uint32_t ro = (warp * 16 + (lane & 7)) * 128, x0 = ((lane >> 3) ^ (lane & 7)) << 4;
  float rs[2], rh[2], nm[2];
#pragma unroll
  for (int h = 0; h < 2; h++) {
    float t[2];
    lds64f(t, va + 2048 + (warp * 16 + h * 8 + (lane >> 2)) * 8);
    rs[h] = t[0]; rh[h] = 0.5f * t[0]; nm[h] = t[1];
  }
  va += (lane & 3) * 32;
#pragma unroll
  for (int c = 0; c < BN / 64; c++) {
    uint32_t y[2][4];
#pragma unroll
    for (int j = 0; j < 4; j++) {
      const float* g = acc + 16 * c + 4 * j; const float* u = g + BN / 4;
      float p[4], q[4], o[4];
      lds128f(p, va + (4 * c + j) * 128); lds128f(q, va + (4 * c + j) * 128 + 16);
#pragma unroll
      for (int e = 0; e < 4; e++) {
        const float g2 = fmaf(rh[e >> 1], g[e], fmaf(nm[e >> 1], p[e & 1], p[2 + (e & 1)]));
        const float h = g2 * fmaf(rs[e >> 1], u[e], fmaf(nm[e >> 1], q[e & 1], q[2 + (e & 1)]));
        float t; asm("tanh.approx.f32 %0, %1;" : "=f"(t) : "f"(g2));
        o[e] = fmaf(h, t, h);
      }
      y[0][j] = pack2(o[0], o[1]); y[1][j] = pack2(o[2], o[3]);
    }
    const uint32_t base = ((c >> 1) == 0 ? stg : slot) + ro + (x0 ^ ((c & 1) << 6));
    stsm4(base, y[0]); stsm4(base + 1024, y[1]);
  }
}

template <bool WS>
__device__ __forceinline__ void h_vecmat(uint32_t sb, int idx, uint32_t& st, uint32_t& ph, int tid, const __nv_bfloat16* cvec, uint8_t* w13s, float* uv,
                                         __nv_bfloat16* mod, float* gate) {
  const uint32_t stg = sb + H_STG, bars = sb + H_BAR;
  const int lane = tid & 31, warp = tid >> 5;
#pragma unroll
  for (int i = 0; i < 4; i++) {
    const int k = tid + 256 * i;
    if (WS) {
      const uint32_t s = __ldcg(reinterpret_cast<const uint16_t*>(mod) + 3 * D_ + k), c = __ldcg(reinterpret_cast<const uint16_t*>(mod) + 4 * D_ + k);
      sts32(stg + k * 4, s << 16); sts32(stg + 4096 + k * 4, c | c << 16);
    } else {
      const float c = __bfloat162float(cvec[k]);
      sts32(stg + k * 4, __float_as_uint(__bfloat162float(__float2bfloat16(c / (1.f + __expf(-c))))));
    }
  }
  bar_sync<1, 256>();
  float v[4][8], u[4][8];
#pragma unroll
  for (int b = 0; b < 4; b++)
#pragma unroll
    for (int e = 0; e < 8; e++) { v[b][e] = 0.f; u[b][e] = 0.f; }
  const int r0 = tid >> 3;
  const uint32_t off = 16384 + r0 * 128 + (((tid & 7) ^ (r0 & 7)) << 4);
  uint32_t prev = 0;
#pragma unroll 1
  for (int i = 0; i < (WS ? 16 : 8); i++) {
    mbar_wait(bars + HB_FULL + st * 8, ph);
    const uint32_t base = sb + st * H_STAGE + off;
#pragma unroll
    for (int ri = 0; ri < 2; ri++) {
      const uint32_t ka = stg + ((WS ? i * 64 : i * 128) + r0 + 32 * ri) * 4;
      const float m0 = lds32f(ka), m1 = WS ? m0 : lds32f(ka + 256);
      const uint32_t c2 = WS ? lds32(ka + 4096) : 0;
#pragma unroll
      for (int b = 0; b < 4; b++) {
        uint32_t w[4];
        lds128(w, base + b * 8192 + ri * 4096);
        const float m = b < 2 ? m0 : m1;
#pragma unroll
        for (int e = 0; e < 4; e++) {
          v[b][2 * e] = fmaf(m, bf_lo(w[e]), v[b][2 * e]); v[b][2 * e + 1] = fmaf(m, bf_hi(w[e]), v[b][2 * e + 1]);
          if (WS) { w[e] = hfma2(w[e], c2, w[e]); u[b][2 * e] += bf_lo(w[e]); u[b][2 * e + 1] += bf_hi(w[e]); }
        }
        if (WS) sts128(base + b * 8192 + ri * 4096, w[0], w[1], w[2], w[3]);
      }
    }
    if (WS) fence_async_smem();
    bar_sync<1, 256>();
    if (tid == 0) {
      if (WS) {
        bulk_s2g(w13s + (size_t)(idx * 16 + i) * 32768, sb + st * H_STAGE + 16384, 32768);
        bulk_commit();
        if (i > 0) { bulk_wait_read<1>(); mbar_arrive_n(bars + HB_EMPTY + prev * 8, 2); }
      } else mbar_arrive_n(bars + HB_EMPTY + st * 8, 2);
    }
    prev = st;
    if (++st == H_NST) { st = 0; ph ^= 1; }
  }
  if (WS && tid == 0) {
    bulk_wait_read<0>(); mbar_arrive_n(bars + HB_EMPTY + prev * 8, 2);
    bulk_wait_all(); fence_async_all(); fence_gpu();
  }
#pragma unroll
  for (int b = 0; b < 4; b++)
#pragma unroll
    for (int e = 0; e < 8; e++) {
      v[b][e] += __shfl_xor_sync(0xffffffffu, v[b][e], 8); v[b][e] += __shfl_xor_sync(0xffffffffu, v[b][e], 16);
      if (WS) { u[b][e] += __shfl_xor_sync(0xffffffffu, u[b][e], 8); u[b][e] += __shfl_xor_sync(0xffffffffu, u[b][e], 16); }
    }
  if (lane < 8) {
#pragma unroll
    for (int b = 0; b < 4; b++) {
      const uint32_t a = stg + warp * 2048 + b * 256 + lane * 32;
      sts128(a, __float_as_uint(v[b][0]), __float_as_uint(v[b][1]), __float_as_uint(v[b][2]), __float_as_uint(v[b][3]));
      sts128(a + 16, __float_as_uint(v[b][4]), __float_as_uint(v[b][5]), __float_as_uint(v[b][6]), __float_as_uint(v[b][7]));
      if (WS) {
        sts128(a + 1024, __float_as_uint(u[b][0]), __float_as_uint(u[b][1]), __float_as_uint(u[b][2]), __float_as_uint(u[b][3]));
        sts128(a + 1040, __float_as_uint(u[b][4]), __float_as_uint(u[b][5]), __float_as_uint(u[b][6]), __float_as_uint(u[b][7]));
      }
    }
  }
  bar_sync<1, 256>();
  float sv = 0.f, su = 0.f;
#pragma unroll
  for (int i = 0; i < 8; i++) {
    sv += lds32f(stg + i * 2048 + tid * 4);
    su += WS ? lds32f(stg + i * 2048 + 1024 + tid * 4) : lds32f(stg + i * 2048 + (tid ^ 128) * 4);
  }
  if (WS) {
    const int n = tid & 127, up = tid >> 7, c = n >> 5, j = (n >> 3) & 3, t = (n >> 1) & 3, e = n & 1;
    float* p = uv + idx * 512 + (c * 4 + j) * 32 + t * 8 + up * 4 + e;
    const float s = up ? 1.f : 0.5f;
    p[0] = s * su; p[2] = s * sv;
  } else if (tid < 128) {
    const int n = idx * 128 + tid, vec = n >> 10, col = n & 1023;
    const __nv_bfloat16 r = __float2bfloat16(sv + su);
    mod[2048 + n] = r;
    if (vec == 0 || vec == 3) gate[(vec ? D_ : 0) + (col & ~31) + ((col >> 1) & 3) * 8 + ((col >> 3) & 3) * 2 + (col & 1)] = __bfloat162float(r);
  }
}

__global__ void __launch_bounds__(384, 1)
kernel_H(const __grid_constant__ CUtensorMap tmo, const __grid_constant__ CUtensorMap tm1, const __grid_constant__ CUtensorMap tm3,
         const __grid_constant__ CUtensorMap tm2, const __grid_constant__ CUtensorMap tmm, const __grid_constant__ CUtensorMap tmx,
         const __nv_bfloat16* __restrict__ x, const __nv_bfloat16* __restrict__ cvec, __nv_bfloat16* out, const __grid_constant__ HList list) {
  extern __shared__ __align__(1024) uint8_t smem[];
  constexpr uint32_t sb = 0x400, bars = sb + H_BAR;
  const int tid = threadIdx.x, lane = tid & 31;
  const int warp = __shfl_sync(0xffffffffu, tid >> 5, 0);
  if (tid == 0) {
    if (smem_u32(smem) != sb) __trap();
    for (int i = 0; i < H_NST; i++) { mbar_init(bars + HB_FULL + i * 8, 1); mbar_init(bars + HB_EMPTY + i * 8, 2); }
    for (int i = 0; i < 2; i++) { mbar_init(bars + HB_IFULL + i * 8, 1); mbar_init(bars + HB_IEMPTY + i * 8, 1); mbar_init(bars + HB_VFULL + i * 8, 1); }
    mbar_init(bars + HB_STGF, 1);
    fence_async_smem();
  }
  __syncthreads();
  if (warp >= 8) {
    asm volatile("setmaxnreg.dec.sync.aligned.u32 40;");
    if (warp == 8) {
      uint32_t st = 0, ph = 1, nv = 0, q = 0;
      if (lane == 0) q = atomicAdd(&g_flags[FL_HEAD], 1);
#pragma unroll 1
      for (uint32_t n = 0;; n++) {
        q = __shfl_sync(0xffffffffu, q, 0);
        const uint32_t it = q < list.n ? list.it[q] : 0;
        const int type = it & 7, mt = (it >> 3) & 15, idx = (it >> 7) & 63, sz = (it >> 13) & 3, kb0 = (it >> 15) & 63, nkb = (it >> 21) & 127;
        {
          int f = FL_GO; uint32_t target = 0;
          if (type == IT_OUT) { f = lane == 0 ? FL_ATT + 8 * mt : lane == 1 ? FL_XT + 8 * mt : FL_MOD; target = lane == 0 ? 64 : lane == 1 ? N_XT : N_MOD; }
          else if (type == IT_F1) { f = lane == 0 ? FL_OUT + 8 * mt : FL_WS; target = lane == 0 ? 1024 : N_WS; }
          else if (type == IT_F2) { f = FL_F1 + 8 * mt; target = 56; }
          else if (type == IT_STAT) { f = FL_OUT + 8 * mt; target = 1024; }
          else if (type == IT_WS) { f = FL_MOD; target = N_MOD; }
          else if (type != IT_END) target = 1;
          if (lane < 3) wait_flag(&g_flags[f], target);
          __syncwarp();
          asm volatile("fence.proxy.async.global;" ::: "memory");
        }
        mbar_wait(bars + HB_IEMPTY + (n & 1) * 8, ((n >> 1) & 1) ^ 1);
        if (elect_one()) {
          sts32(bars + HB_ITEM + (n & 1) * 4, it);
          mbar_arrive(bars + HB_IFULL + (n & 1) * 8);
        }
        if (type == IT_END) break;
        const bool gemm = type == IT_OUT || type == IT_F1 || type == IT_F2;
        const int nst = gemm ? nkb : type == IT_WS ? 16 : type == IT_MOD ? 8 : 0;
        const int bn = 256 >> sz;
        const uint8_t* ap = type == IT_OUT ? g_att + (size_t)mt * 64 * 16384 : g_act + (size_t)mt * 56 * 16384;
        const uint8_t* wp = g_w13s + (size_t)(idx >> sz) * 16 * 32768 + (sz ? (idx & 1) * 8192 : 0);
        const CUtensorMap* tb = type == IT_OUT ? &tmo : type == IT_F2 ? &tm2 : type == IT_WS ? &tm1 : &tmm;
        const CUtensorMap* tc = type == IT_WS ? &tm3 : tb;
        const int c0 = gemm ? idx * bn : type == IT_WS ? idx * 128 : 2048 + idx * 128, dcol = gemm ? 128 : 0, kmul = type == IT_MOD ? 128 : 64, drow = type == IT_MOD ? 64 : 0;
        const uint32_t bytes = gemm ? 16384 + bn * 128 : 32768;
        if (nst < 2 && lane == 0) q = atomicAdd(&g_flags[FL_HEAD], 1);
#pragma unroll 1
        for (int i = 0; i < nst; i++) {
          const int kb = kb0 + i;
          const uint32_t d = sb + st * H_STAGE, fb = bars + HB_FULL + st * 8;
          if (i == nst - 2 && lane == 0) q = atomicAdd(&g_flags[FL_HEAD], 1);
          mbar_wait(bars + HB_EMPTY + st * 8, ph);
          if (elect_one()) {
            mbar_expect(fb, bytes);
            if (type == IT_F1) {
              tma2d(d, &tmx, kb * 64, mt * 128, fb);
              if (sz == 0) bulk_g2s(d + 16384, wp + (size_t)kb * 32768, 32768, fb);
              else { bulk_g2s(d + 16384, wp + (size_t)kb * 32768, 8192, fb); bulk_g2s(d + 24576, wp + (size_t)kb * 32768 + 16384, 8192, fb); }
            } else {
              if (gemm) bulk_g2s(d, ap + (size_t)kb * 16384, 16384, fb);
              tma2d(d + 16384, tb, c0, kb * kmul, fb);
              tma2d(d + 24576, tb, c0 + 64, kb * kmul, fb);
              if (sz == 0) { tma2d(d + 32768, tc, c0 + dcol, kb * kmul + drow, fb); tma2d(d + 40960, tc, c0 + dcol + 64, kb * kmul + drow, fb); }
            }
          }
          if (++st == H_NST) { st = 0; ph ^= 1; }
        }
        if (gemm) {
          if (type == IT_F1) {
            if (lane == 0) wait_flag(&g_flags[FL_STAT + 8 * mt], N_STAT);
            __syncwarp();
            asm volatile("fence.proxy.async.global;" ::: "memory");
          }
          if (elect_one()) {
            const uint32_t v = sb + H_VEC + (nv & 1) * 3072, fb = bars + HB_VFULL + (nv & 1) * 8;
            if (type == IT_F1) {
              mbar_expect(fb, (2048 >> sz) + 1024);
              bulk_g2s(v, g_uv + idx * (512 >> sz), 2048 >> sz, fb);
              bulk_g2s(v + 2048, g_stat + mt * 256, 1024, fb);
            } else {
              mbar_expect(fb, bn * 4);
              bulk_g2s(v, g_gate + (type == IT_F2 ? D_ : 0) + c0, bn * 4, fb);
            }
          }
          nv++;
        }
      }
    } else if (warp == 9) {
#pragma unroll 1
      for (uint32_t n = 0;; n++) {
        mbar_wait(bars + HB_IFULL + (n & 1) * 8, (n >> 1) & 1);
        const uint32_t it = lds32(bars + HB_ITEM + (n & 1) * 4);
        const int type = it & 7, mt = (it >> 3) & 15, idx = (it >> 7) & 63, sz = (it >> 13) & 3, nkb = (it >> 21) & 127;
        if (type == IT_END) break;
        if (n & 1) bar_sync<3, 288>(); else bar_sync<2, 288>();
        if (lane == 0) {
          const bool gated = type == IT_OUT || type == IT_F2, gemm = gated || type == IT_F1;
          if (gemm) {
            const uint32_t slot = lds32(bars + HB_SLOT + (n & 1) * 4);
            const int nu = (gated ? 4 : 2) >> sz;
#pragma unroll 1
            for (int u = 0; u < nu; u++) {
              const uint32_t src = u == 0 ? sb + H_STG : sb + slot * H_STAGE + (u - 1) * 16384;
              if (gated) tma2d_add(&tmx, idx * (256 >> sz) + u * 64, mt * 128, src);
              else bulk_s2g(g_act + (size_t)(mt * 56 + idx * nu + u) * 16384, src, 16384);
            }
            bulk_commit();
            bulk_wait_read<0>();
            if (nu > 1) mbar_arrive_n(bars + HB_EMPTY + slot * 8, 2);
          }
          mbar_arrive(bars + HB_STGF);
          mbar_arrive(bars + HB_IEMPTY + (n & 1) * 8);
          if (gemm) { bulk_wait_all(); fence_async_all(); }
          if (type != IT_F2) {
            const uint32_t inc = type == IT_OUT ? (4 >> sz) * nkb : type == IT_F1 ? 2 >> sz : 1;
            fence_gpu();
            red_add_u32(&g_flags[type == IT_MOD ? FL_MOD : type == IT_WS ? FL_WS :
                                 (type == IT_XT ? FL_XT : type == IT_OUT ? FL_OUT : type == IT_STAT ? FL_STAT : FL_F1) + 8 * mt], inc);
          }
        }
        __syncwarp();
      }
      asm volatile("griddepcontrol.wait;" ::: "memory");
      uint32_t k = 0;
      if (lane == 0) { fence_gpu(); k = atomicAdd(&g_flags[FL_EXIT], 1); }
      k = __shfl_sync(0xffffffffu, k, 0);
      if (k == gridDim.x - 1) {
        fence_gpu();
        for (int i = lane; i < 1024; i += 32) g_flags[i] = 0;
      }
    }
  } else {
    asm volatile("setmaxnreg.inc.sync.aligned.u32 232;");
    const int wg = warp >> 2;
    const bool leader = (tid & 127) == 0;
    uint32_t st = 0, ph = 0, nv = 0;
#pragma unroll 1
    for (uint32_t n = 0;; n++) {
      mbar_wait(bars + HB_IFULL + (n & 1) * 8, (n >> 1) & 1);
      const uint32_t it = __shfl_sync(0xffffffffu, lds32(bars + HB_ITEM + (n & 1) * 4), 0);
      const int type = it & 7, mt = (it >> 3) & 15, idx = (it >> 7) & 63, sz = (it >> 13) & 3, nkb = (it >> 21) & 127;
      if (type == IT_END) break;
      if (type == IT_OUT || type == IT_F1 || type == IT_F2) {
        const uint32_t va = sb + H_VEC + (nv & 1) * 3072, vb = bars + HB_VFULL + (nv & 1) * 8, vp = (nv >> 1) & 1;
        uint32_t last;
        nv++;
        if (sz == 0) {
          float acc[128];
          if (type == IT_OUT) last = h_mainloop<256, 1>(acc, sb, nkb, st, ph, wg, leader, true);
          else last = h_mainloop<256, 0>(acc, sb, nkb, st, ph, wg, leader, true);
          mbar_wait(vb, vp);
          mbar_wait(bars + HB_STGF, (n & 1) ^ 1);
          if (type == IT_F1) h_swiglu<256>(acc, va, sb + H_STG, sb + last * H_STAGE, warp, lane);
          else h_gated<256>(acc, va, sb + H_STG, sb + last * H_STAGE, warp, lane);
        } else {
          float acc[64];
          if (type == IT_OUT) last = h_mainloop<128, 1>(acc, sb, nkb, st, ph, wg, leader, true);
          else last = h_mainloop<128, 0>(acc, sb, nkb, st, ph, wg, leader, type == IT_F2);
          mbar_wait(vb, vp);
          mbar_wait(bars + HB_STGF, (n & 1) ^ 1);
          if (type == IT_F1) h_swiglu<128>(acc, va, sb + H_STG, sb + last * H_STAGE, warp, lane);
          else h_gated<128>(acc, va, sb + H_STG, sb + last * H_STAGE, warp, lane);
        }
        if (tid == 0) sts32(bars + HB_SLOT + (n & 1) * 4, last);
        fence_async_smem();
      } else if (type == IT_XT) {
        const uint4* xp = reinterpret_cast<const uint4*>(x + (size_t)(mt * 128 + idx * 64) * D_) + tid;
        uint4* op = reinterpret_cast<uint4*>(out + (size_t)(mt * 128 + idx * 64) * D_) + tid;
#pragma unroll 1
        for (int b = 0; b < 2; b++) {
          uint4 v[16];
#pragma unroll
          for (int i = 0; i < 16; i++) v[i] = __ldcs(xp + (b * 16 + i) * 256);
#pragma unroll
          for (int i = 0; i < 16; i++) op[(b * 16 + i) * 256] = v[i];
        }
      } else if (type == IT_STAT) {
        const int row0 = mt * 128 + idx * 32 + warp * 4;
        const uint4* xp = reinterpret_cast<const uint4*>(out + (size_t)row0 * D_) + lane;
        uint4 v[16];
#pragma unroll
        for (int i = 0; i < 16; i++) v[i] = __ldcg(xp + (i >> 2) * 128 + (i & 3) * 32);
        float s[4], m[4];
#pragma unroll
        for (int r = 0; r < 4; r++) {
          s[r] = 0.f;
#pragma unroll
          for (int i = 0; i < 4; i++) {
            const uint4 w = v[4 * r + i];
            s[r] += ((bf_lo(w.x) + bf_hi(w.x)) + (bf_lo(w.y) + bf_hi(w.y))) + ((bf_lo(w.z) + bf_hi(w.z)) + (bf_lo(w.w) + bf_hi(w.w)));
          }
        }
#pragma unroll
        for (int o = 1; o < 32; o <<= 1)
#pragma unroll
          for (int r = 0; r < 4; r++) s[r] += __shfl_xor_sync(0xffffffffu, s[r], o);
#pragma unroll
        for (int r = 0; r < 4; r++) {
          m[r] = s[r] * (1.f / D_);
          float a = 0.f, b = 0.f;
#pragma unroll
          for (int i = 0; i < 4; i++) {
            const uint4 w = v[4 * r + i];
            const uint32_t ww[4] = {w.x, w.y, w.z, w.w};
#pragma unroll
            for (int e = 0; e < 4; e++) { const float p = bf_lo(ww[e]) - m[r], t = bf_hi(ww[e]) - m[r]; a = fmaf(p, p, a); b = fmaf(t, t, b); }
          }
          s[r] = a + b;
        }
#pragma unroll
        for (int o = 1; o < 32; o <<= 1)
#pragma unroll
          for (int r = 0; r < 4; r++) s[r] += __shfl_xor_sync(0xffffffffu, s[r], o);
        if (lane < 4) {
          const float sr = lane == 0 ? s[0] : lane == 1 ? s[1] : lane == 2 ? s[2] : s[3], mr = lane == 0 ? m[0] : lane == 1 ? m[1] : lane == 2 ? m[2] : m[3];
          const float rs = rsqrtf(sr * (1.f / D_) + 1e-5f);
          reinterpret_cast<float2*>(g_stat)[row0 + lane] = make_float2(rs, -mr * rs);
        }
      } else {
        mbar_wait(bars + HB_STGF, (n & 1) ^ 1);
        if (type == IT_WS) h_vecmat<true>(sb, idx, st, ph, tid, cvec, g_w13s, g_uv, g_mod, g_gate);
        else h_vecmat<false>(sb, idx, st, ph, tid, cvec, g_w13s, g_uv, g_mod, g_gate);
      }
      HT(3);
      if (n & 1) bar_arrive<3, 288>(); else bar_arrive<2, 288>();
    }
  }
}

uint32_t mk_item(int type, int mt, int idx, int sz, int kb0, int nkb) { return type | mt << 3 | idx << 7 | sz << 13 | kb0 << 15 | nkb << 21; }

void build_list(HList& l) {
  int n = 0;
  for (int i = 0; i < N_MOD; i++) l.it[n++] = mk_item(IT_MOD, 0, i, 0, 0, 0);
  for (int i = 0; i < 16 * N_XT; i++) l.it[n++] = mk_item(IT_XT, i / N_XT, i % N_XT, 0, 0, 0);
  for (int i = 0; i < N_WS; i++) l.it[n++] = mk_item(IT_WS, 0, i, 0, 0, 0);
  for (int mt = 0; mt < 16; mt++) {
    for (int i = 0; i < 8; i++) l.it[n++] = mk_item(IT_OUT, mt, i & 3, 0, (i >> 2) * 32, 32);
    for (int i = 0; i < N_STAT; i++) l.it[n++] = mk_item(IT_STAT, mt, i, 0, 0, 0);
    for (int i = 0; i < 28; i++) l.it[n++] = mk_item(IT_F1, mt, i, 0, 0, 16);
    for (int i = 0; i < 8; i++) l.it[n++] = mk_item(IT_F2, mt, i, 1, 0, 56);
  }
  l.n = n;
}

typedef CUresult (*EncodeFn)(CUtensorMap*, CUtensorMapDataType, cuuint32_t, void*, const cuuint64_t*, const cuuint64_t*,
                             const cuuint32_t*, const cuuint32_t*, CUtensorMapInterleave, CUtensorMapSwizzle,
                             CUtensorMapL2promotion, CUtensorMapFloatOOBfill);

void make_map(EncodeFn fn, CUtensorMap* m, const void* p, uint64_t cols, uint64_t rows, uint32_t bc, uint32_t br, CUtensorMapSwizzle sw) {
  cuuint64_t dims[2] = {cols, rows};
  cuuint64_t strides[1] = {cols * 2};
  cuuint32_t box[2] = {bc, br};
  cuuint32_t es[2] = {1, 1};
  fn(m, CU_TENSOR_MAP_DATA_TYPE_BFLOAT16, 2, const_cast<void*>(p), dims, strides, box, es, CU_TENSOR_MAP_INTERLEAVE_NONE, sw,
     CU_TENSOR_MAP_L2_PROMOTION_L2_128B, CU_TENSOR_MAP_FLOAT_OOB_FILL_NONE);
}

}

extern "C" void kernel_launch(void* const* d_in, const int* in_sizes, int n_in, void* d_out, int out_size) {
  const __nv_bfloat16* x = (const __nv_bfloat16*)d_in[0];
  const __nv_bfloat16* mem0 = (const __nv_bfloat16*)d_in[1];
  const __nv_bfloat16* cvec = (const __nv_bfloat16*)d_in[11];
  static EncodeFn enc = nullptr;
  if (!enc) {
    cudaDriverEntryPointQueryResult qr;
    void* fp = nullptr;
    cudaGetDriverEntryPoint("cuTensorMapEncodeTiled", &fp, cudaEnableDefault, &qr);
    enc = (EncodeFn)fp;
    cudaFuncSetAttribute(kernel_R, cudaFuncAttributeMaxDynamicSharedMemorySize, R_SMEM);
    cudaFuncSetAttribute(kernel_H, cudaFuncAttributeMaxDynamicSharedMemorySize, H_SMEM);
  }
  CUtensorMap tmq, tmk, tmv, tmo, tmm;
  make_map(enc, &tmm, d_in[12], 6144, 1024, 64, 64, CU_TENSOR_MAP_SWIZZLE_NONE);
  make_map(enc, &tmq, d_in[2], 4096, 1024, 64, 64, CU_TENSOR_MAP_SWIZZLE_128B);
  make_map(enc, &tmk, d_in[3], 4096, 1024, 64, 64, CU_TENSOR_MAP_SWIZZLE_128B);
  make_map(enc, &tmv, d_in[4], 4096, 1024, 64, 64, CU_TENSOR_MAP_SWIZZLE_128B);
  make_map(enc, &tmo, d_in[5], 1024, 4096, 16, 128, CU_TENSOR_MAP_SWIZZLE_32B);
  RDesc dsc;
  for (int k = 0; k < 32; k++) {
    dsc.tok[k] = mkdesc(0x400 + (k < 16 ? R_GA : R_GB) + ((k & 15) >> 2) * 4096 + (k & 3) * 256, 128, 1024, 0);
    dsc.tail_a[k] = mkdesc(0x400 + R_TAIL + k * 2048, 1024, 1024, 1);
    if (k < 16) dsc.tail_b[k] = mkdesc(0x400 + R_GA + k * 256, 128, 4096, 0);
  }
  kernel_R<<<96, 256, R_SMEM, cudaStreamPerThread>>>(tmq, tmk, tmv, tmo, tmm, x, mem0, cvec, dsc);

  CUtensorMap ho, h1, h3, h2, hm, hx;
  make_map(enc, &ho, d_in[5], 1024, 4096, 64, 64, CU_TENSOR_MAP_SWIZZLE_128B);
  make_map(enc, &h1, d_in[8], F_, 1024, 64, 64, CU_TENSOR_MAP_SWIZZLE_128B);
  make_map(enc, &h3, d_in[9], F_, 1024, 64, 64, CU_TENSOR_MAP_SWIZZLE_128B);
  make_map(enc, &h2, d_in[10], 1024, F_, 64, 64, CU_TENSOR_MAP_SWIZZLE_128B);
  make_map(enc, &hm, d_in[12], 6144, 1024, 64, 64, CU_TENSOR_MAP_SWIZZLE_128B);
  make_map(enc, &hx, d_out, 1024, S_, 64, 128, CU_TENSOR_MAP_SWIZZLE_128B);
  HList list;
  build_list(list);
  cudaLaunchConfig_t cfg = {};
  cfg.gridDim = dim3(132); cfg.blockDim = dim3(384); cfg.dynamicSmemBytes = H_SMEM; cfg.stream = cudaStreamPerThread;
  cudaLaunchAttribute at[1];
  at[0].id = cudaLaunchAttributeProgrammaticStreamSerialization;
  at[0].val.programmaticStreamSerializationAllowed = 1;
  cfg.attrs = at;
  cfg.numAttrs = 1;
  cudaLaunchKernelEx(&cfg, kernel_H, ho, h1, h3, h2, hm, hx, x, cvec, (__nv_bfloat16*)d_out, list);
}
```

```cpp
#include <cuda_runtime.h>
#include <cuda_bf16.h>
#include <cuda.h>
#include <stdint.h>
#include <type_traits>

namespace {

constexpr int S_ = 2048, D_ = 1024, NSEG = 64, F_ = 3584;

__device__ __align__(1024) uint8_t g_h[S_ * D_ * 2];
__device__ __align__(1024) uint8_t g_att[S_ * 4096 * 2];
__device__ __align__(1024) uint8_t g_act[S_ * F_ * 2];
__device__ __align__(1024) uint8_t g_w13s[28 * 16 * 32768];
__device__ __align__(1024) float g_stat[S_ * 2];
__device__ __align__(1024) float g_uv[F_ * 4];
__device__ __align__(1024) float g_gate[2 * D_];
__device__ __align__(1024) float g_slot[4 * 3 * 8 * 4 * 32 * 4];
__device__ __align__(128) __nv_bfloat16 g_mod[6 * D_];
__device__ __align__(128) float g_modp[3 * 2 * D_];
__device__ __align__(128) uint32_t g_flags[1024];
constexpr int FL_S1 = 0, FL_S2 = 32, FL_MOD = 64, FL_HEAD = 96, FL_EXIT = 128, FL_WS = 160, FL_GO = 192, FL_ATT = 256, FL_XT = 384, FL_OUT = 512, FL_F1 = 640, FL_STAT = 768;

__device__ __forceinline__ uint32_t smem_u32(const void* p) { return (uint32_t)__cvta_generic_to_shared(p); }
__device__ __forceinline__ uint32_t mapa(uint32_t a, uint32_t r) { uint32_t o; asm("mapa.shared::cluster.u32 %0, %1, %2;" : "=r"(o) : "r"(a), "r"(r)); return o; }
__device__ __forceinline__ uint32_t pack2(float a, float b) { uint32_t r; asm("cvt.rn.bf16x2.f32 %0, %1, %2;" : "=r"(r) : "f"(b), "f"(a)); return r; }
__device__ __forceinline__ float bf_lo(uint32_t w) { return __uint_as_float(w << 16); }
__device__ __forceinline__ float bf_hi(uint32_t w) { return __uint_as_float(w & 0xffff0000u); }
__device__ __forceinline__ float ex2(float x) { float y; asm("ex2.approx.ftz.f32 %0, %1;" : "=f"(y) : "f"(x)); return y; }
__device__ __forceinline__ float rcp(float x) { float y; asm("rcp.approx.ftz.f32 %0, %1;" : "=f"(y) : "f"(x)); return y; }
__device__ __forceinline__ uint32_t clk32() { uint64_t c; asm volatile("mov.u64 %0, %%clock64;" : "=l"(c) :: "memory"); return (uint32_t)c; }

__device__ __forceinline__ void mbar_init(uint32_t b, uint32_t n) { asm volatile("mbarrier.init.shared::cta.b64 [%0], %1;" :: "r"(b), "r"(n) : "memory"); }
__device__ __forceinline__ void mbar_arrive(uint32_t b) { asm volatile("mbarrier.arrive.shared::cta.b64 _, [%0];" :: "r"(b) : "memory"); }
__device__ __forceinline__ void mbar_expect(uint32_t b, uint32_t n) { asm volatile("mbarrier.arrive.expect_tx.shared::cta.b64 _, [%0], %1;" :: "r"(b), "r"(n) : "memory"); }
__device__ __forceinline__ uint32_t mbar_try(uint32_t b, uint32_t par) {
  uint32_t ok;
  asm volatile("{\n.reg .pred p;\nmbarrier.try_wait.parity.shared::cta.b64 p, [%1], %2;\nselp.u32 %0, 1, 0, p;\n}" : "=r"(ok) : "r"(b), "r"(par) : "memory");
  return ok;
}
__device__ __forceinline__ void mbar_wait(uint32_t b, uint32_t par) {
  asm volatile("{\n.reg .pred p;\n"
               "LOOP:\n"
               "mbarrier.try_wait.parity.shared::cta.b64 p, [%0], %1;\n"
               "@!p bra.uni LOOP;\n}" :: "r"(b), "r"(par) : "memory");
}
__device__ __forceinline__ void mbar_wait_safe(uint32_t b, uint32_t par) {
  uint32_t c = 0;
  while (!mbar_try(b, par)) { if (++c > 4000000u) __trap(); }
}
__device__ __forceinline__ bool elect_one() {
  uint32_t p;
  asm volatile("{\n.reg .pred p;\nelect.sync _|p, 0xffffffff;\nselp.u32 %0, 1, 0, p;\n}" : "=r"(p));
  return p;
}
__device__ __forceinline__ void sched_fence(uint32_t x, uint32_t y) { asm volatile("{\n.reg .pred p;\nsetp.eq.u32 p, %0, %1;\n@p trap;\n}" :: "r"(x), "r"(y) : "memory"); }
template <class T> __device__ __forceinline__ T opaque32(T x) { asm volatile("" : "+r"(x)); return x; }
template <class T> __device__ __forceinline__ T opaque64(T x) { asm volatile("" : "+l"(x)); return x; }
template <int ID, int N> __device__ __forceinline__ void bar_sync() { asm volatile("bar.sync %0, %1;" :: "n"(ID), "n"(N) : "memory"); }
template <int ID, int N> __device__ __forceinline__ void bar_arrive() { asm volatile("bar.arrive %0, %1;" :: "n"(ID), "n"(N) : "memory"); }
__device__ __forceinline__ void fence_async_smem() { asm volatile("fence.proxy.async.shared::cta;" ::: "memory"); }
__device__ __forceinline__ void fence_async_all() { asm volatile("fence.proxy.async;" ::: "memory"); }
__device__ __forceinline__ void fence_gpu() { asm volatile("fence.acq_rel.gpu;" ::: "memory"); }
__device__ __forceinline__ void red_add_u32(uint32_t* p, uint32_t v) { asm volatile("red.relaxed.gpu.global.add.u32 [%0], %1;" :: "l"(p), "r"(v) : "memory"); }
__device__ __forceinline__ uint32_t ld_acquire(const uint32_t* p) { uint32_t v; asm volatile("ld.acquire.gpu.global.u32 %0, [%1];" : "=r"(v) : "l"(p) : "memory"); return v; }
__device__ __forceinline__ void wait_flag(const uint32_t* p, uint32_t target) {
  uint32_t c = 0;
  while (ld_acquire(p) < target) { if (++c > 20000000u) __trap(); __nanosleep(20); }
}

__device__ __forceinline__ void tma2d(uint32_t dst, const CUtensorMap* m, int c0, int c1, uint32_t bar) {
  asm volatile("cp.async.bulk.tensor.2d.shared::cluster.global.mbarrier::complete_tx::bytes [%0], [%1, {%3, %4}], [%2];"
               :: "r"(dst), "l"(m), "r"(bar), "r"(c0), "r"(c1) : "memory");
}
constexpr uint64_t L2_NORMAL = 0x1000000000000000ull, L2_FIRST = 0x12F0000000000000ull;
__device__ __forceinline__ void tma2d_p(uint32_t dst, const CUtensorMap* m, int c0, int c1, uint32_t bar, uint64_t pol) {
  asm volatile("cp.async.bulk.tensor.2d.shared::cluster.global.mbarrier::complete_tx::bytes.L2::cache_hint [%0], [%1, {%3, %4}], [%2], %5;"
               :: "r"(dst), "l"(m), "r"(bar), "r"(c0), "r"(c1), "l"(pol) : "memory");
}
__device__ __forceinline__ void bulk_g2s_p(uint32_t dst, const void* src, uint32_t bytes, uint32_t bar, uint64_t pol) {
  asm volatile("cp.async.bulk.shared::cluster.global.mbarrier::complete_tx::bytes.L2::cache_hint [%0], [%1], %2, [%3], %4;"
               :: "r"(dst), "l"(src), "r"(bytes), "r"(bar), "l"(pol) : "memory");
}
#define POL_RW L2_FIRST
__device__ __forceinline__ void tma2d_prefetch_p(const CUtensorMap* m, int c0, int c1, uint64_t pol) {
  asm volatile("cp.async.bulk.prefetch.tensor.2d.L2.global.L2::cache_hint [%0, {%1, %2}], %3;" :: "l"(m), "r"(c0), "r"(c1), "l"(pol) : "memory");
}
__device__ __forceinline__ void tma2d_prefetch(const CUtensorMap* m, int c0, int c1) {
  asm volatile("cp.async.bulk.prefetch.tensor.2d.L2.global [%0, {%1, %2}];" :: "l"(m), "r"(c0), "r"(c1) : "memory");
}
__device__ __forceinline__ void bulk_g2s(uint32_t dst, const void* src, uint32_t bytes, uint32_t bar) {
  asm volatile("cp.async.bulk.shared::cluster.global.mbarrier::complete_tx::bytes [%0], [%1], %2, [%3];"
               :: "r"(dst), "l"(src), "r"(bytes), "r"(bar) : "memory");
}
__device__ __forceinline__ void bulk_s2s(uint32_t dst, uint32_t src, uint32_t bytes, uint32_t bar) {
  asm volatile("cp.async.bulk.shared::cluster.shared::cta.mbarrier::complete_tx::bytes [%0], [%1], %2, [%3];"
               :: "r"(dst), "r"(src), "r"(bytes), "r"(bar) : "memory");
}
__device__ __forceinline__ void st_async1(uint32_t dst, uint32_t a, uint32_t bar) {
  asm volatile("st.async.shared::cluster.mbarrier::complete_tx::bytes.b32 [%0], %1, [%2];" :: "r"(dst), "r"(a), "r"(bar) : "memory");
}
__device__ __forceinline__ void st_async2(uint32_t dst, uint32_t a, uint32_t b, uint32_t bar) {
  asm volatile("st.async.shared::cluster.mbarrier::complete_tx::bytes.v2.b32 [%0], {%1, %2}, [%3];" :: "r"(dst), "r"(a), "r"(b), "r"(bar) : "memory");
}
__device__ __forceinline__ void st_async4(uint32_t dst, const uint32_t* r, uint32_t bar) {
  asm volatile("st.async.shared::cluster.mbarrier::complete_tx::bytes.v4.b32 [%0], {%1, %2, %3, %4}, [%5];"
               :: "r"(dst), "r"(r[0]), "r"(r[1]), "r"(r[2]), "r"(r[3]), "r"(bar) : "memory");
}
__device__ __forceinline__ void sts32(uint32_t a, uint32_t v) { asm volatile("st.shared.b32 [%0], %1;" :: "r"(a), "r"(v) : "memory"); }
__device__ __forceinline__ void sts64(uint32_t a, uint32_t x, uint32_t y) { asm volatile("st.shared.v2.b32 [%0], {%1, %2};" :: "r"(a), "r"(x), "r"(y) : "memory"); }
__device__ __forceinline__ void sts128(uint32_t a, uint32_t x, uint32_t y, uint32_t z, uint32_t w) {
  asm volatile("st.shared.v4.b32 [%0], {%1, %2, %3, %4};" :: "r"(a), "r"(x), "r"(y), "r"(z), "r"(w) : "memory");
}
__device__ __forceinline__ void lds128(uint32_t* r, uint32_t a) {
  asm volatile("ld.shared.v4.b32 {%0, %1, %2, %3}, [%4];" : "=r"(r[0]), "=r"(r[1]), "=r"(r[2]), "=r"(r[3]) : "r"(a) : "memory");
}
__device__ __forceinline__ uint32_t lds32(uint32_t a) { uint32_t r; asm volatile("ld.shared.b32 %0, [%1];" : "=r"(r) : "r"(a) : "memory"); return r; }
__device__ __forceinline__ void lds64(uint32_t* r, uint32_t a) {
  asm volatile("ld.shared.v2.b32 {%0, %1}, [%2];" : "=r"(r[0]), "=r"(r[1]) : "r"(a) : "memory");
}
__device__ __forceinline__ void lds128f(float* r, uint32_t a) {
  asm volatile("ld.shared.v4.f32 {%0, %1, %2, %3}, [%4];" : "=f"(r[0]), "=f"(r[1]), "=f"(r[2]), "=f"(r[3]) : "r"(a) : "memory");
}
__device__ __forceinline__ void lds64f(float* r, uint32_t a) {
  asm volatile("ld.shared.v2.f32 {%0, %1}, [%2];" : "=f"(r[0]), "=f"(r[1]) : "r"(a) : "memory");
}
__device__ __forceinline__ void ldsm4(uint32_t* r, uint32_t a) {
  asm volatile("ldmatrix.sync.aligned.m8n8.x4.shared.b16 {%0, %1, %2, %3}, [%4];" : "=r"(r[0]), "=r"(r[1]), "=r"(r[2]), "=r"(r[3]) : "r"(a) : "memory");
}
__device__ __forceinline__ void ldsm4t(uint32_t* r, uint32_t a) {
  asm volatile("ldmatrix.sync.aligned.m8n8.x4.trans.shared.b16 {%0, %1, %2, %3}, [%4];" : "=r"(r[0]), "=r"(r[1]), "=r"(r[2]), "=r"(r[3]) : "r"(a) : "memory");
}
__device__ __forceinline__ void ldsm2(uint32_t* r, uint32_t a) {
  asm volatile("ldmatrix.sync.aligned.m8n8.x2.shared.b16 {%0, %1}, [%2];" : "=r"(r[0]), "=r"(r[1]) : "r"(a) : "memory");
}
__device__ __forceinline__ void stsm4(uint32_t a, const uint32_t* r) {
  asm volatile("stmatrix.sync.aligned.m8n8.x4.shared.b16 [%0], {%1, %2, %3, %4};" :: "r"(a), "r"(r[0]), "r"(r[1]), "r"(r[2]), "r"(r[3]) : "memory");
}
__device__ __forceinline__ uint32_t hadd2(uint32_t a, uint32_t b) { uint32_t t; asm("add.rn.bf16x2 %0, %1, %2;" : "=r"(t) : "r"(a), "r"(b)); return t; }
__device__ __forceinline__ uint32_t hmax2(uint32_t a, uint32_t b) { uint32_t t; asm("max.bf16x2 %0, %1, %2;" : "=r"(t) : "r"(a), "r"(b)); return t; }
__device__ __forceinline__ void ldsm2t(uint32_t* r, uint32_t a) {
  asm volatile("ldmatrix.sync.aligned.m8n8.x2.trans.shared.b16 {%0, %1}, [%2];" : "=r"(r[0]), "=r"(r[1]) : "r"(a) : "memory");
}
__device__ __forceinline__ uint32_t movm(uint32_t x) { uint32_t y; asm volatile("movmatrix.sync.aligned.m8n8.trans.b16 %0, %1;" : "=r"(y) : "r"(x)); return y; }
__device__ __forceinline__ void hmma(float* d, uint32_t a0, uint32_t a1, uint32_t a2, uint32_t a3, uint32_t b0, uint32_t b1) {
  asm volatile("mma.sync.aligned.m16n8k16.row.col.f32.bf16.bf16.f32 {%0,%1,%2,%3}, {%4,%5,%6,%7}, {%8,%9}, {%0,%1,%2,%3};"
               : "+f"(d[0]), "+f"(d[1]), "+f"(d[2]), "+f"(d[3]) : "r"(a0), "r"(a1), "r"(a2), "r"(a3), "r"(b0), "r"(b1));
}
__device__ __forceinline__ void hmma0(float* d, uint32_t a0, uint32_t a1, uint32_t a2, uint32_t a3, uint32_t b0, uint32_t b1) {
  asm volatile("mma.sync.aligned.m16n8k16.row.col.f32.bf16.bf16.f32 {%0,%1,%2,%3}, {%4,%5,%6,%7}, {%8,%9}, {%10,%10,%10,%10};"
               : "=f"(d[0]), "=f"(d[1]), "=f"(d[2]), "=f"(d[3]) : "r"(a0), "r"(a1), "r"(a2), "r"(a3), "r"(b0), "r"(b1), "f"(0.f));
}
__device__ __forceinline__ void hmma_k8(float* d, uint32_t a0, uint32_t a1, uint32_t b0) {
  asm volatile("mma.sync.aligned.m16n8k8.row.col.f32.bf16.bf16.f32 {%0,%1,%2,%3}, {%4,%5}, {%6}, {%0,%1,%2,%3};"
               : "+f"(d[0]), "+f"(d[1]), "+f"(d[2]), "+f"(d[3]) : "r"(a0), "r"(a1), "r"(b0));
}
__host__ __device__ constexpr uint64_t mkdesc(uint32_t addr, uint32_t lbo, uint32_t sbo, uint32_t sw) {
  return (uint64_t)((addr & 0x3FFFF) >> 4) | ((uint64_t)(lbo >> 4) << 16) | ((uint64_t)(sbo >> 4) << 32) | ((uint64_t)sw << 62);
}
#define WG_FENCE() asm volatile("wgmma.fence.sync.aligned;" ::: "memory")
#define WG_COMMIT() asm volatile("wgmma.commit_group.sync.aligned;" ::: "memory")
#define WG_WAIT(n) asm volatile("wgmma.wait_group.sync.aligned " #n ";" ::: "memory")
template <int N> __device__ __forceinline__ void reg_fence(float* d) {
#pragma unroll
  for (int i = 0; i < N; i++) asm volatile("" : "+f"(d[i]) :: "memory");
}
template <int N> __device__ __forceinline__ void zero_regs(float* d) {
#pragma unroll
  for (int i = 0; i < N; i++) asm volatile("mov.b32 %0, 0;" : "=f"(d[i]));
}
template <int SD>
__device__ __forceinline__ void wg_rs32(float* d, uint32_t a0, uint32_t a1, uint32_t a2, uint32_t a3, uint64_t b) {
  asm volatile("wgmma.mma_async.sync.aligned.m64n32k16.f32.bf16.bf16 {%0,%1,%2,%3,%4,%5,%6,%7,%8,%9,%10,%11,%12,%13,%14,%15}, {%16,%17,%18,%19}, %20, %21, 1, 1, 0;"
               : "+f"(d[0]), "+f"(d[1]), "+f"(d[2]), "+f"(d[3]), "+f"(d[4]), "+f"(d[5]), "+f"(d[6]), "+f"(d[7]),
                 "+f"(d[8]), "+f"(d[9]), "+f"(d[10]), "+f"(d[11]), "+f"(d[12]), "+f"(d[13]), "+f"(d[14]), "+f"(d[15])
               : "r"(a0), "r"(a1), "r"(a2), "r"(a3), "l"(b), "n"(SD));
}
template <int TB>
__device__ __forceinline__ void wg_ss40(float* d, uint64_t a, uint64_t b) {
  asm volatile("wgmma.mma_async.sync.aligned.m64n40k16.f32.bf16.bf16 {%0,%1,%2,%3,%4,%5,%6,%7,%8,%9,%10,%11,%12,%13,%14,%15,%16,%17,%18,%19}, %20, %21, 1, 1, 1, 1, %22;"
               : "+f"(d[0]), "+f"(d[1]), "+f"(d[2]), "+f"(d[3]), "+f"(d[4]), "+f"(d[5]), "+f"(d[6]), "+f"(d[7]),
                 "+f"(d[8]), "+f"(d[9]), "+f"(d[10]), "+f"(d[11]), "+f"(d[12]), "+f"(d[13]), "+f"(d[14]), "+f"(d[15]),
                 "+f"(d[16]), "+f"(d[17]), "+f"(d[18]), "+f"(d[19])
               : "l"(a), "l"(b), "n"(TB));
}
template <int T>
__device__ __forceinline__ void wg_ss32(float* d, uint64_t a, uint64_t b) {
  asm volatile("wgmma.mma_async.sync.aligned.m64n32k16.f32.bf16.bf16 {%0,%1,%2,%3,%4,%5,%6,%7,%8,%9,%10,%11,%12,%13,%14,%15}, %16, %17, 1, 1, 1, %18, %18;"
               : "+f"(d[0]), "+f"(d[1]), "+f"(d[2]), "+f"(d[3]), "+f"(d[4]), "+f"(d[5]), "+f"(d[6]), "+f"(d[7]),
                 "+f"(d[8]), "+f"(d[9]), "+f"(d[10]), "+f"(d[11]), "+f"(d[12]), "+f"(d[13]), "+f"(d[14]), "+f"(d[15])
               : "l"(a), "l"(b), "n"(T));
}

constexpr int R_TAIL = 0;
constexpr int R_WO = 65536;
constexpr int R_QK = R_WO + 86016;
constexpr int R_P = R_QK + 10240;
constexpr int R_GA = R_P + 6400;
constexpr int R_M2 = R_GA + 16384;
constexpr int R_M1 = R_M2 + 7168;
constexpr int R_GB = R_M1 + 9216;
constexpr int R_VT = R_GB + 16384;
constexpr int R_VM = R_VT + 8192;
constexpr int R_XS = R_VM + 2048;
constexpr int R_OX = R_XS + 1280;
constexpr int R_BAR = R_OX + 2048;
constexpr int R_TRC = R_BAR + 256;
constexpr int R_SMEM = R_TRC + 1024;
constexpr int B_MB = 0, B_XS = 32, B_VM = 40, B_VT = 48, B_TS = 56, B_FA = 64, B_FB = 72, B_TAIL = 80, B_WO = 88, B_STG = 96, B_WM = 128, B_X = 136;
constexpr int NB_A = 1, NB_B = 2, NB_X = 3, NB_C = 4, NB_D = 5, NB_E = 6, NB_F = 7, NB_G = 8, NB_H = 9, NB_S = 10, NB_E2 = 11, NB_P = 12, NB_W0 = 13;

#define POLL_DELAY 750
#define POLL_DELAY1 700
#define POLL_STAG 150
#define POLL_K0 20
#define ZS 2
#define HPF 4
#define PF1 2
#define PF2 2
#define PF3 2
#define PF4 0
#define RF_FIRST 0
#define BX_I 5
#define NCH 4
#define TOP2 0
#define CX_I 13
#define ATT_LATE 0
#define V_FENCE 1
#define SELF_STAS 1
#define Q_FENCE 1
#define ND_K 3
#define TRACE(i)
#define TS(i)

__device__ __forceinline__ int rot_chunk(int c, int rank) {
  int G = c;
  if (c < 9) { G = c + 3 * rank; if (G >= 9) G -= 9; }
  return G;
}
__device__ __forceinline__ int wo_tile(int i, int rank) {
  if (i < 12) return 12 * rank + i;
  const int r = i - 12 + 9 * rank;
  return r < 16 ? 48 + r : 20 + r;
}
__device__ __forceinline__ void load_chunk(uint32_t dst, int seg, int G, uint32_t bar) {
  mbar_expect(bar, 4096);
  bulk_g2s(dst, g_h + (size_t)(seg * 16 + G) * 4096, 4096, bar);
}
__device__ __forceinline__ void load_red(uint32_t* v, const float* p) {
#pragma unroll
  for (int j = 0; j < 2; j++)
    asm volatile("ld.relaxed.gpu.global.v4.u32 {%0, %1, %2, %3}, [%4];"
                 : "=r"(v[4 * j]), "=r"(v[4 * j + 1]), "=r"(v[4 * j + 2]), "=r"(v[4 * j + 3]) : "l"(p + j * 256) : "memory");
}
__device__ __forceinline__ bool red_done(const uint32_t* v) { return __all_sync(0xffffffffu, (v[3] & v[7]) == 0x42000000u); }
__device__ __forceinline__ uint32_t finish_red(uint32_t* v, const float* p) {
  uint32_t tries = 0;
  if (__builtin_expect(!red_done(v), 0)) {
    do { if (++tries > 20000000u) __trap(); load_red(v, p); } while (!red_done(v));
  }
  return tries;
}
__device__ __forceinline__ void exp10(float* sv, const uint32_t* x) {
  constexpr float SC = 0.08838834764831845f * 1.4426950408889634f;
  uint32_t m2 = hmax2(hmax2(hmax2(x[0], x[1]), hmax2(x[2], x[3])), x[4]);
  m2 = hmax2(m2, __shfl_xor_sync(0xffffffffu, m2, 1));
  m2 = hmax2(m2, __shfl_xor_sync(0xffffffffu, m2, 2));
  const float nm = -fmaxf(bf_lo(m2), bf_hi(m2)) * SC;
#pragma unroll
  for (int j = 0; j < 5; j++) { sv[2 * j] = ex2(fmaf(bf_lo(x[j]), SC, nm)); sv[2 * j + 1] = ex2(fmaf(bf_hi(x[j]), SC, nm)); }
}

__device__ __forceinline__ uint32_t arm_size(int w, bool isC) {
  return w == 0 ? (isC ? 1280 : 640) : w == 1 ? (isC ? 0 : 2048) : w == 2 ? (isC ? 0 : 8192) : (isC ? 0 : 1792);
}
struct RDesc { uint64_t tok[32], tail_b[16], tail_a[32]; };

template <int WG>
__device__ __forceinline__ void r_main(const uint32_t (&W)[48][4], const RDesc& dsc, int head, uint32_t rank, int lane_, int w) {
  const uint32_t sb = (rank << 24) + 0x400, bars = sb + R_BAR;
  const uint32_t to1 = rank == 0 ? 2u << 24 : 0u - (1u << 24), to2 = rank == 2 ? 0u - (2u << 24) : 1u << 24;
  const bool isC = rank == 2;
  const int lane = opaque32(lane_), warp = WG * 4 + w;
  const int gl = rot_chunk(4 * (lane & 3) + w, rank);
  const int g0 = __shfl_sync(0xffffffffu, gl, 0), g1 = __shfl_sync(0xffffffffu, gl, 1), g2 = __shfl_sync(0xffffffffu, gl, 2);
  const uint32_t arm_bytes = arm_size(w, isC);

#define L16 opaque32(sb + opaque32(lane) * 16)
#define L8 opaque32(sb + opaque32(lane) * 8)
#define L4 opaque32(sb + opaque32(lane) * 4)
#define LV opaque32(sb + R_VT + ((opaque32(lane) >> 3) & 1) * 512 + (opaque32(lane) >> 4) * 128 + (opaque32(lane) & 7) * 16)
#define SLOT(st) opaque64(slot0 + ((st) & 3) * 12288 + ((st) & 4) * 32)
  float* const slot0 = opaque64(g_slot + (rank * 1024 + warp * 128 + lane) * 4);
  const uint32_t woa = opaque32(sb + R_WO + warp * 12288 + ((lane >> 4) * 8 + (lane & 7)) * 32 + ((((lane >> 3) ^ (lane >> 2)) & 1) << 4));
  const bool has_wo = WG == 0 || isC || w < 3;
  float acc[20];
  uint32_t pk[8] = {0u, 0u, 0u, 0u, 0u, 0u, 0u, 0u};

  auto forward = [&](auto rd, const uint32_t* v, int st, uint32_t tries) {
    constexpr int RD = decltype(rd)::value;
    uint32_t u[6];
#pragma unroll
    for (int j = 0; j < 6; j++) u[j] = movm(v[4 * (j / 3) + j % 3]);
    const bool all3 = RD == 0 || w < 3;
    if (RD == 0) {
      const uint32_t a = L16 + R_M1 + w * 768, a2 = L8 + R_M1 + 512 + w * 768;
      st_async4(a + to1 + 3072, u, bars + to1 + B_MB + 8); st_async2(a2 + to1 + 3072, u[4], u[5], bars + to1 + B_MB + 8);
      sts128(a, u[0], u[1], u[2], u[3]); sts64(a2, u[4], u[5]);
      __syncwarp();
      if (elect_one()) mbar_arrive(bars + B_MB);
      st_async4(a + to2 + 6144, u, bars + to2 + B_MB + 16); st_async2(a2 + to2 + 6144, u[4], u[5], bars + to2 + B_MB + 16);
    } else {
      const uint32_t a = L4 + R_M2 + rank * 2304 + w * 768;
#pragma unroll
      for (int j = 0; j < 6; j++) if (j < 2 || all3) st_async1(a + to1 + j * 128, u[j], bars + to1 + B_MB + 24);
#pragma unroll
      for (int j = 0; j < 6; j++) if (j < 2 || all3) st_async1(a + to2 + j * 128, u[j], bars + to2 + B_MB + 24);
      if (SELF_STAS) {
#pragma unroll
        for (int j = 0; j < 6; j++) if (j < 2 || all3) st_async1(a + j * 128, u[j], bars + B_MB + 24);
      } else {
#pragma unroll
        for (int j = 0; j < 6; j++) if (j < 2 || all3) sts32(a + j * 128, u[j]);
        __syncwarp();
        if (elect_one()) mbar_arrive(bars + B_MB + 24);
      }
    }
  };

  auto send_vt = [&]() {
    if (elect_one()) {
      const uint32_t src = sb + R_VT + warp * 1024;
      bulk_s2s(src + to1, src, 1024, bars + to1 + B_VT);
      bulk_s2s(src + to2, src, 1024, bars + to2 + B_VT);
    }
  };
  auto store_att = [&](int sg) {
    uint32_t* op = reinterpret_cast<uint32_t*>(g_att + (size_t)((sg >> 2) * 64 + head * 2 + rank) * 16384 + (2 * w * 16 + (sg & 3) * 4) * 128) + opaque32(lane);
#pragma unroll
    for (int j = 0; j < 8; j++) op[(j & 1) * 512 + (j >> 1) * 32] = pk[j];
  };

  if (WG == 0) bar_arrive<NB_G, 256>();
#pragma unroll 1
  for (int s = -1; s < NSEG; s++) {
    const uint32_t par = (s + 1) & 1;
    const uint32_t last = s == NSEG - 1;
    TRACE(0);
    {
      float c[NCH][4];
      uint32_t b[3][6];
      const uint32_t ma = L16, m8 = L8;
#pragma unroll
      for (int i = 0; i < 18; i++) {
        if (i < 16) {
          if (i % 4 == 0 && !(i == 4 && TOP2)) mbar_wait(bars + B_MB + (i / 4) * 8, par ^ 1);
          if (i == 0 && TOP2) mbar_wait(bars + B_MB + 8, par ^ 1);
          if (i % 4 == 0) TRACE(1 + i / 4);
          if (i < 12) { lds128(b[i % 3], ma + R_M1 + i * 768); lds64(b[i % 3] + 4, m8 + R_M1 + 512 + i * 768); }
          else { ldsm4(b[i % 3], ma + R_M2 + 4096 + (i - 12) * 768); ldsm2(b[i % 3] + 4, ma + R_M2 + 4096 + 512 + (i - 12) * 768); }
          if (WG == 1 && i == BX_I) {
            bar_sync<NB_G, 256>();
            if (!last && elect_one()) load_chunk(sb + R_GB + w * 4096, s + 1, g0, bars + B_FB);
          }
          if (i == CX_I) {
            if (isC && s >= 0) send_vt();
            if (WG == 1 && ATT_LATE && !isC && s > 0) store_att(s - 1);
          }
          __syncwarp();
        }
        if (i >= 2) {
          const int j = i - 2;
#pragma unroll
          for (int q = 0; q < 3; q++) {
            const uint32_t* f = W[3 * j + q];
            if (3 * j + q < NCH) hmma0(c[3 * j + q], f[0], f[1], f[2], f[3], b[j % 3][2 * q], b[j % 3][2 * q + 1]);
            else hmma(c[(3 * j + q) % NCH], f[0], f[1], f[2], f[3], b[j % 3][2 * q], b[j % 3][2 * q + 1]);
          }
        }
        if (i == 14) zero_regs<16>(acc);
        if (i == 16) mbar_wait(bars + B_FA, last);
      }
#pragma unroll
      for (int j = 0; j < 4; j++) acc[16 + j] = NCH == 3 ? (c[0][j] + c[1][j]) + c[2][j] : (c[0][j] + c[1][j]) + (c[2][j] + c[NCH - 1][j]);
    }
    TRACE(5);
    bar_sync<NB_H, 256>();
    WG_FENCE();
#pragma unroll
    for (int k = 0; k < 16; k++) wg_ss40<0>(acc, dsc.tail_a[WG * 16 + k], dsc.tail_b[k]);
    WG_COMMIT();
    uint32_t vt[4][4];
    {
      const uint32_t a = opaque32(L4 + w * 256 + (isC ? WG * 1024 + R_VM : R_QK + 4096 + WG * 5120));
      const uint32_t qa = L16 + R_QK, xa = opaque32(LV + w * 2048 + (WG == 0 ? 0 : (opaque32(lane) & 8) * 64 + R_QK + 5120 - R_VT));
      const uint32_t d = opaque32(L4 + R_XS + rank * 640 + w * 256);
      if (s == 0) {
        mbar_wait_safe(bars + B_WO, 0);
        TS(10);
        if (WG == 1 && head == 0 && rank == 0 && w == 0 && elect_one()) red_add_u32(&g_flags[FL_GO], 1);
      }
      mbar_wait(bars + B_FB, last);
      if (WG == 0) mbar_wait(bars + B_VT, par);
      WG_WAIT(0);
      reg_fence<20>(acc);
      TRACE(6);
      const uint32_t p0 = pack2(acc[16], acc[17]), p1 = pack2(acc[18], acc[19]);
      sts32(a, p0); sts32(a + 128, p1);
      if (isC) {
        st_async1(a + to1, p0, bars + B_VM + to1); st_async1(a + to1 + 128, p1, bars + B_VM + to1);
        st_async1(a + to2, p0, bars + B_VM + to2); st_async1(a + to2 + 128, p1, bars + B_VM + to2);
      }
      if (WG == 0) {
        bar_arrive<NB_A, 256>();
        if (Q_FENCE && !isC) fence_async_smem();
#pragma unroll
        for (int i = 0; i < 4; i++) ldsm4(vt[i], xa + (i >> 1) * 1024 + (i & 1) * 256);
        bar_sync<NB_S, 256>();
      } else {
        bar_sync<NB_A, 256>();
        if (!isC) {
          if (w < 3) {
            uint32_t q[8], k[4][4];
            ldsm4t(q, qa + 4096); ldsm4t(k[0], xa); ldsm4t(k[1], xa + 256);
            ldsm4t(q + 4, qa + 4096 + 512); ldsm4t(k[2], xa + 512); ldsm4t(k[3], xa + 768);
            float x[4], y[4];
            hmma0(x, k[0][0], k[0][1], k[0][2], k[0][3], q[0], q[1]); hmma0(y, k[1][0], k[1][1], k[1][2], k[1][3], q[2], q[3]);
            hmma(x, k[2][0], k[2][1], k[2][2], k[2][3], q[4], q[5]); hmma(y, k[3][0], k[3][1], k[3][2], k[3][3], q[6], q[7]);
            const uint32_t s0 = pack2(x[0] + y[0], x[1] + y[1]), s1 = pack2(x[2] + y[2], x[3] + y[3]);
            st_async1(d + to1, s0, bars + B_XS + to1);
            st_async1(d + to2, s0, bars + B_XS + to2);
            if (w < 2) { st_async1(d + to1 + 128, s1, bars + B_XS + to1); st_async1(d + to2 + 128, s1, bars + B_XS + to2); sts32(d + 128, s1); }
            sts32(d, s0);
          }
        }
        bar_arrive<NB_S, 256>();
      }
    }
    if (WG == 1) {
      if (!last && elect_one()) load_chunk(sb + R_GA + w * 4096, s + 1, g1, bars + B_FA);
      {
        if (w > 0 && elect_one()) mbar_expect(bars + B_MB + 8 * w, w < 3 ? 3072 : SELF_STAS ? 28 * 256 : isC ? 18 * 256 : 19 * 256);
      }
      fence_async_smem();
      bar_sync<NB_B, 256>();
    }
    TRACE(7);
    WG_FENCE();
#pragma unroll
    for (int k = 0; k < 16; k++) wg_rs32<1>(acc, W[k][0], W[k][1], W[k][2], W[k][3], dsc.tok[16 + k]);
    WG_COMMIT();
    uint32_t wa[3][4];
    const uint32_t oxa = L16 + R_OX;
    if (WG == 0) {
      const uint32_t vma = oxa - (R_OX - R_VM) + w * 512, oa = opaque32(L4 + w * 512 + R_OX);
      TRACE(8);
      mbar_wait(bars + B_XS, par);
      TRACE(9);
      float sv[10];
      {
        uint32_t x[10];
        ldsm4t(x, oxa - (R_OX - R_XS)); ldsm4t(x + 4, oxa - (R_OX - R_XS) + 512); ldsm2t(x + 8, oxa - (R_OX - R_XS) + 1024);
        bar_arrive<NB_B, 256>();
#pragma unroll
        for (int j = 0; j < 5; j++) x[j] = hadd2(x[j], x[j + 5]);
        exp10(sv, x);
      }
      WG_WAIT(0);
      bar_arrive<NB_X, 256>();
      mbar_wait(bars + B_VM, par);
      uint32_t vm[4];
      ldsm4(vm, vma);
      uint32_t pb[5];
#pragma unroll
      for (int j = 0; j < 5; j++) pb[j] = pack2(sv[2 * j], sv[2 * j + 1]);
      TRACE(10);
      float o0[4], o1[4], sm[4];
      const uint32_t ONE = 0x3f803f80u;
      hmma0(o0, vt[0][0], vt[0][1], vt[0][2], vt[0][3], pb[0], pb[1]);
      hmma0(o1, vt[2][0], vt[2][1], vt[2][2], vt[2][3], pb[0], pb[1]);
      hmma0(sm, ONE, ONE, ONE, ONE, pb[0], pb[1]);
      hmma(sm, ONE, ONE, ONE, ONE, pb[2], pb[3]);
      hmma(o0, vt[1][0], vt[1][1], vt[1][2], vt[1][3], pb[2], pb[3]);
      hmma(o1, vt[3][0], vt[3][1], vt[3][2], vt[3][3], pb[2], pb[3]);
      hmma_k8(sm, ONE, ONE, pb[4]);
      hmma_k8(o0, vm[0], vm[1], pb[4]);
      hmma_k8(o1, vm[2], vm[3], pb[4]);
#pragma unroll
      for (int i = 0; i < 3; i++) ldsm4t(wa[i], woa + i * 4096);
      __syncwarp();
      const float i0 = rcp(sm[0]), i1 = rcp(sm[1]);
      sts32(oa, pack2(o0[0] * i0, o0[1] * i1)); sts32(oa + 128, pack2(o0[2] * i0, o0[3] * i1));
      sts32(oa + 256, pack2(o1[0] * i0, o1[1] * i1)); sts32(oa + 384, pack2(o1[2] * i0, o1[3] * i1));
      TRACE(11);
      bar_sync<NB_C, 128>();
    } else {
      if (!isC) {
        constexpr uint64_t dQ = mkdesc(0x400 + R_QK, 128, 1024, 0), dK = mkdesc(0x400 + R_QK + 5120, 128, 1024, 0);
        float sc[16];
        zero_regs<16>(sc);
        WG_FENCE();
#pragma unroll
        for (int k = 0; k < 4; k++) wg_ss32<1>(sc, dK + k * 16, dQ + k * 16);
        WG_COMMIT();
        const uint32_t top = rank == 0 ? to2 : to1, e = L4 + R_P + w * 256;
        WG_WAIT(0);
        bar_sync<NB_X, 256>();
        if (!last && elect_one()) load_chunk(sb + R_GB + w * 4096, s + 1, g2, bars + B_FB);
        reg_fence<16>(sc);
        if (w < 3) {
#pragma unroll
          for (int j = 0; j < 8; j++) {
            if ((j & 1) ? (j > 1 && (w == 0 || (w == 1 && j == 7))) : (j >= 4 || w != 1)) {
              const uint32_t t = pack2(sc[2 * j], sc[2 * j + 1]), o = (j >> 1) * 768 + (j & 1) * 128;
              st_async1(e + top + 3072 + o, t, bars + top + B_TS);
              sts32(e + o, t);
            }
          }
          __syncwarp();
          if (elect_one()) mbar_arrive(bars + B_TS);
        }
      } else {
        WG_WAIT(0);
        bar_sync<NB_X, 256>();
        if (!last && elect_one()) load_chunk(sb + R_GB + w * 4096, s + 1, g2, bars + B_FB);
      }
      TRACE(8);
      mbar_wait(bars + B_FA, 1);
      TRACE(11);
    }
    if (has_wo) {
      float* rslot = SLOT(s);
      uint32_t ob[4][4];
      float c[3][4];
      if (WG == 1) {
#pragma unroll
        for (int i = 0; i < 3; i++) ldsm4t(wa[i], woa + i * 4096);
        bar_sync<NB_D, 256>();
      }
      ldsm4t(ob[0], oxa);
      __syncwarp();
#pragma unroll
      for (int k = 0; k < 8; k++) {
        uint32_t nx[3][4];
        if ((k & 1) == 0 && k < 6) { ldsm4t(ob[(k >> 1) + 1], oxa + ((k >> 1) + 1) * 512); __syncwarp(); }
#pragma unroll
        for (int i = 0; i < 3; i++) {
          const uint32_t* o = ob[k >> 1] + (k & 1) * 2;
          if (k < 7) { ldsm4t(nx[i], woa + i * 4096 + (k + 1) * 512); if (i == 2) __syncwarp(); }
          if (k == 0) hmma0(c[i], wa[i][0], wa[i][1], wa[i][2], wa[i][3], o[0], o[1]);
          else hmma(c[i], wa[i][0], wa[i][1], wa[i][2], wa[i][3], o[0], o[1]);
#pragma unroll
          for (int q = 0; q < 4; q++) if (k < 7) wa[i][q] = nx[i][q];
        }
        if (k == ND_K && WG == 0) bar_arrive<NB_D, 256>();
      }
      const float* cv = &c[0][0];
      uint32_t r[6];
#pragma unroll
      for (int j = 0; j < 6; j++) r[j] = pack2(cv[2 * j], cv[2 * j + 1]);
      asm volatile("{\n.reg .pred p;\nsetp.lt.s32 p, %8, 0;\n@p bra.uni SKIP;\n"
                   "red.relaxed.gpu.global.add.noftz.v4.bf16x2 [%0], {%1, %2, %3, %7};\n"
                   "red.relaxed.gpu.global.add.noftz.v4.bf16x2 [%0+1024], {%4, %5, %6, %7};\nSKIP:\n}"
                   :: "l"(rslot), "r"(r[0]), "r"(r[1]), "r"(r[2]), "r"(r[3]), "r"(r[4]), "r"(r[5]), "r"(0x3f800000), "r"(s) : "memory");
    } else {
      bar_arrive<NB_D, 256>();
      if ((s & 3) == 0) {
        fence_gpu();
        if (s > 0 && elect_one()) red_add_u32(&g_flags[FL_ATT + 2 * (s - 4)], 1);
      }
      if (rank == 0 || head < 16)
        reinterpret_cast<uint4*>(g_slot)[((s + ZS) & 3) * 3072 + ((s + ZS) & 4) * 8 + rank * 2048 + head * 64 + opaque32(lane)] = make_uint4(0, 0, 0, 0);
      if (HPF && head < 16 && rank == 0 && s + HPF < NSEG && elect_one())
        asm volatile("cp.async.bulk.prefetch.L2.global [%0], 4096;" :: "l"(g_h + (size_t)((s + HPF) * 16 + head) * 4096) : "memory");
    }
    const uint32_t t_red = clk32();
    uint32_t v[8];
    const float* slot = SLOT(s);
    TRACE(13);
    if (WG == 0) {
      if (!isC) {
        const int ln = opaque32(lane), kg = w - (ln >> 3);
        const uint32_t r16 = sb + R_P + w * 768 + (ln & 7) * 16;
        const uint32_t ta = r16 + (kg >= 0 ? kg * 128 : 640);
        const int dg = (ln >> 2) - 2 * (ln & 3);
        const uint32_t keep = dg > 0 ? 0xffffffffu : dg == 0 ? 0x0000ffffu : 0u;
        mbar_wait(bars + B_TS, par);
        uint32_t x[6], y[4];
        ldsm4t(x, ta); ldsm4t(y, ta + 3072); ldsm2t(x + 4, r16 + 512 + ((ln >> 3) & 1) * 3072);
#pragma unroll
        for (int j = 0; j < 5; j++) x[j] = hadd2(x[j], j < 4 ? y[j] : x[5]);
        x[0] = (x[0] & keep) | (0xff80ff80u & ~keep);
        float sv[10];
        exp10(sv, x);
        float sum = (((sv[0] + sv[1]) + (sv[2] + sv[3])) + ((sv[4] + sv[5]) + (sv[6] + sv[7]))) + (sv[8] + sv[9]);
        sum += __shfl_xor_sync(0xffffffffu, sum, 1);
        sum += __shfl_xor_sync(0xffffffffu, sum, 2);
        const float inv = rcp(sum);
#pragma unroll
        for (int j = 0; j < 5; j++) x[j] = pack2(sv[2 * j] * inv, sv[2 * j + 1] * inv);
        stsm4(r16 + (kg & 3) * 128, x);
        sts32(sb + ln * 4 + w * 768 + R_P + 512, x[4]);
        fence_async_smem();
        bar_arrive<NB_P, 256>();
      }
      while (clk32() - t_red < POLL_DELAY) {}
      load_red(v, slot);
      bar_sync<NB_E, 256>();
    } else {
      mbar_wait(bars + B_FB, 1);
    }
    TRACE(14);
    float ao[16];
    if (WG == 1) zero_regs<16>(ao);
    WG_FENCE();
#pragma unroll
    for (int k = 0; k < 32; k++) {
      if (WG == 0 && k == 16) WG_COMMIT();
      wg_rs32<1>(acc, W[16 + k][0], W[16 + k][1], W[16 + k][2], W[16 + k][3], dsc.tok[k]);
    }
    WG_COMMIT();
    TRACE(12);
    if (WG == 1) {
      if (!isC) {
        constexpr uint64_t dP = mkdesc(0x400 + R_P, 128, 768, 0);
        const uint64_t dV = mkdesc(0x400 + R_VT, 128, 512, 0) + rank * 256, dM = mkdesc(0x400 + R_VM, 0, 128, 0) + rank * 64;
        bar_sync<NB_P, 256>();
        WG_FENCE();
        wg_ss32<0>(ao, dV, dP); wg_ss32<0>(ao, dV + 16, dP + 16); wg_ss32<0>(ao, dM, dP + 32);
        WG_COMMIT();
      }
      bar_arrive<NB_E, 256>();
      if (elect_one()) mbar_expect(bars + B_XS + 8 * w, arm_bytes);
      while (clk32() - t_red < POLL_DELAY1) {}
      load_red(v, slot);
      bar_arrive<NB_W0, 128>();
    } else {
      WG_WAIT(1);
      bar_arrive<NB_F, 256>();
      sched_fence(head, 100);
      v[3] = opaque32(v[3]);
      const uint32_t tries = finish_red(v, slot);
      forward(std::integral_constant<int, 0>(), v, s, tries);
      TRACE(16);
    }
    WG_WAIT(0);
    reg_fence<16>(acc);
    if (WG == 0) bar_arrive<NB_G, 256>();
    TRACE(15);
    {
      uint32_t pq[8];
#pragma unroll
      for (int j = 0; j < 8; j++) pq[j] = pack2(acc[2 * j], acc[2 * j + 1]);
      if (WG == 1) {
        reg_fence<16>(ao);
#pragma unroll
        for (int j = 0; j < 8; j++) pk[j] = pack2(ao[2 * j], ao[2 * j + 1]);
      }
      if (!isC) {
        const uint32_t q = L4 + w * 256 + R_QK + WG * 5120;
#pragma unroll
        for (int j = 0; j < 8; j++) sts32(q + (j >> 1) * 1024 + (j & 1) * 128, pq[j]);
        if (WG == 1 && !ATT_LATE && s >= 0) store_att(s);
      } else {
        const uint32_t a = LV + warp * 1024;
        stsm4(a, pq); stsm4(a + 256, pq + 4);
      }
    }
    TRACE(17);
    if (WG == 1) {
      auto refill = [&]() {
        bar_sync<NB_F, 256>();
        if (s < NSEG - 2 && elect_one()) load_chunk(sb + R_GA + w * 4096, s + 2, 12 + w, bars + B_FA);
      };
      if (RF_FIRST) refill();
      if (has_wo) { v[3] = opaque32(v[3]); const uint32_t tries = finish_red(v, slot); forward(std::integral_constant<int, 1>(), v, s, tries); }
      if (!RF_FIRST) refill();
      TRACE(16);
    }
    if (isC && V_FENCE) { fence_async_smem(); __syncwarp(); }
    TRACE(18);
  }
  if (WG == 1 && ATT_LATE && !isC) store_att(NSEG - 1);
  if (WG == 1) bar_sync<NB_G, 256>();
  mbar_wait_safe(bars + B_MB + 8, 0); mbar_wait_safe(bars + B_MB + 16, 0); mbar_wait_safe(bars + B_MB + 24, 0);
#undef L16
#undef L8
#undef L4
#undef SLOT
#undef LV
}

__global__ void __cluster_dims__(3, 1, 1) __launch_bounds__(256, 1)
kernel_R(const __grid_constant__ CUtensorMap tmq, const __grid_constant__ CUtensorMap tmk, const __grid_constant__ CUtensorMap tmv,
         const __grid_constant__ CUtensorMap tmo, const __grid_constant__ CUtensorMap tmm, const __nv_bfloat16* __restrict__ x,
         const __nv_bfloat16* __restrict__ mem0, const __nv_bfloat16* __restrict__ cvec, const __grid_constant__ RDesc dsc) {
  extern __shared__ __align__(1024) uint8_t smem[];
  const uint32_t sb = smem_u32(smem);
  uint32_t rank; asm("mov.u32 %0, %%cluster_ctarank;" : "=r"(rank));
  rank = __shfl_sync(0xffffffffu, rank, 0);
  const int cta = blockIdx.x, head = __shfl_sync(0xffffffffu, cta / 3, 0);
  const int tid = threadIdx.x, lane = tid & 31;
  const int warp = __shfl_sync(0xffffffffu, tid >> 5, 0);
  const int wg = warp >> 2, w = warp & 3;
  const uint32_t bars = sb + R_BAR;
  const CUtensorMap* tmw = rank == 2 ? &tmv : (wg == 0 ? &tmq : &tmk);
  const int fcol = head * 128 + (rank == 2 ? wg * 64 : (int)rank * 64);

  asm volatile("griddepcontrol.launch_dependents;");
  uint32_t W[48][4];
  {
    if (sb != (rank << 24) + 0x400) __trap();
    if (tid == 0) {
      sts64(bars + 248, rank, head);
      mbar_init(bars + B_MB, 4); mbar_init(bars + B_MB + 8, 1); mbar_init(bars + B_MB + 16, 1); mbar_init(bars + B_MB + 24, SELF_STAS ? 1 : rank == 2 ? 5 : 4);
      for (int i = B_XS; i <= B_X; i += 8) mbar_init(bars + i, i == B_FA || i == B_FB || (i == B_TS && rank < 2) ? 4 : 1);
      asm volatile("fence.mbarrier_init.release.cluster;" ::: "memory");
      fence_async_smem();
    }
    __syncthreads();
    asm volatile("barrier.cluster.arrive.relaxed.aligned;" ::: "memory");
    TS(0);
    const int nwm = rank == 0 ? 6 : 5, wm0 = rank == 0 ? 0 : 5 * rank + 1, nrg = cta < 64 ? 3 : 2;
    if (elect_one()) {
      if (warp == 0) { mbar_expect(bars + B_WM, nwm * 8192); mbar_expect(bars + B_X, nrg * 16384); }
      if (warp < nwm) tma2d_p(sb + R_GA + warp * 8192, &tmm, head * 64, (wm0 + warp) * 64, bars + B_WM, POL_RW);
#pragma unroll 1
      for (int r = 0; r < nrg; r++) bulk_g2s(sb + R_TAIL + (r * 8 + warp) * 2064, x + (size_t)((cta + 96 * r) * 8 + warp) * D_, 2048, bars + B_X);
      if (w == 0) mbar_expect(bars + B_STG + wg * 16, 49152);
      if (w < 2) tma2d_p(sb + R_WO + wg * 49152 + w * 8192, tmw, fcol, rot_chunk(w, rank) * 64, bars + B_STG + wg * 16, POL_RW);
    }
    float* scr = reinterpret_cast<float*>(smem + R_VT);
#pragma unroll 1
    for (int i = tid; i < nwm * 64; i += 256) {
      const float c = __bfloat162float(cvec[wm0 * 64 + i]);
      scr[i] = __bfloat162float(__float2bfloat16(c / (1.f + __expf(-c))));
    }
    if (tid < 128) {
      uint32_t e[4] = {0u, 0u, 0u, 0u};
      if (cta >= 72 && (tid & 32)) {
        const uint16_t* mp = reinterpret_cast<const uint16_t*>(mem0) + 2 * (lane & 3) * D_ + (lane >> 2);
#pragma unroll
        for (int q = 0; q < 3; q++) {
          const int n = 3 * (tid >> 6) + q, col = wo_tile(3 * (cta & 7) + (n >> 1), (cta - 72) >> 3) * 16 + 8 * (n & 1);
          e[q] = mp[col] | (uint32_t)mp[col + D_] << 16;
        }
        e[3] = 0x42000000u;
      }
      reinterpret_cast<uint4*>(g_slot)[cta * 128 + tid] = make_uint4(e[0], e[1], e[2], e[3]);
    }
    __syncthreads();
    TS(1);
    mbar_wait_safe(bars + B_WM, 0);
    if (elect_one()) tma2d_p(sb + R_WO + wg * 49152 + (2 + w) * 8192, tmw, fcol, rot_chunk(2 + w, rank) * 64, bars + B_STG + wg * 16, POL_RW);
    {
      float a[8];
#pragma unroll
      for (int j = 0; j < 8; j++) a[j] = 0.f;
#pragma unroll 2
      for (int i = 0; i < 2 * nwm; i++) {
        uint32_t u[4];
        lds128(u, sb + R_GA + i * 4096 + tid * 16);
        const float sc = scr[i * 32 + (tid >> 3)];
#pragma unroll
        for (int j = 0; j < 4; j++) { a[2 * j] += sc * bf_lo(u[j]); a[2 * j + 1] += sc * bf_hi(u[j]); }
      }
#pragma unroll
      for (int j = 0; j < 8; j++) { a[j] += __shfl_xor_sync(0xffffffffu, a[j], 8); a[j] += __shfl_xor_sync(0xffffffffu, a[j], 16); }
      if (lane < 8) {
        sts128(sb + R_VT + 1536 + warp * 256 + lane * 32, __float_as_uint(a[0]), __float_as_uint(a[1]), __float_as_uint(a[2]), __float_as_uint(a[3]));
        sts128(sb + R_VT + 1552 + warp * 256 + lane * 32, __float_as_uint(a[4]), __float_as_uint(a[5]), __float_as_uint(a[6]), __float_as_uint(a[7]));
      }
    }
    __syncthreads();
    TS(2);
    if (warp == 7) {
      float t0 = 0.f, t1 = 0.f;
#pragma unroll
      for (int i = 0; i < 8; i++) { float t[2]; lds64f(t, sb + R_VT + 1536 + i * 256 + lane * 8); t0 += t[0]; t1 += t[1]; }
      reinterpret_cast<float2*>(g_modp + rank * 2048 + head * 64)[lane] = make_float2(t0, t1);
      fence_gpu();
      __syncwarp();
      if (lane == 0) red_add_u32(&g_flags[FL_S1], 1);
      __syncwarp();
    }
    mbar_wait_safe(bars + B_X, 0);
#pragma unroll 1
    for (int r = 0; r < nrg; r++) {
      float f[32];
#pragma unroll
      for (int i = 0; i < 4; i++) {
        uint32_t u[4];
        lds128(u, sb + R_TAIL + (r * 8 + warp) * 2064 + i * 512 + lane * 16);
#pragma unroll
        for (int j = 0; j < 4; j++) { f[8 * i + 2 * j] = bf_lo(u[j]); f[8 * i + 2 * j + 1] = bf_hi(u[j]); }
      }
      float t = 0.f;
#pragma unroll
      for (int i = 0; i < 32; i++) t += f[i];
#pragma unroll
      for (int o = 1; o < 32; o <<= 1) t += __shfl_xor_sync(0xffffffffu, t, o);
      const float mean = t * (1.f / D_);
      t = 0.f;
#pragma unroll
      for (int i = 0; i < 32; i++) t = fmaf(f[i] - mean, f[i] - mean, t);
#pragma unroll
      for (int o = 1; o < 32; o <<= 1) t += __shfl_xor_sync(0xffffffffu, t, o);
      const float rstd = rsqrtf(t * (1.f / D_) + 1e-5f);
      if (lane == 0) sts64(sb + R_VT + 3584 + (r * 8 + warp) * 8, __float_as_uint(rstd), __float_as_uint(-mean * rstd));
    }
    TS(3);
    if (w < PF1 && elect_one()) tma2d_prefetch_p(tmw, fcol, rot_chunk(6 + w, rank) * 64, POL_RW);
    if (tid == 0) wait_flag(&g_flags[FL_S1], 96);
    __syncthreads();
    TS(4);
    {
      float4 p[6];
#pragma unroll
      for (int i = 0; i < 6; i++) p[i] = __ldcg(reinterpret_cast<const float4*>(g_modp + (i >> 1) * 2048) + 2 * tid + (i & 1));
      if (w < PF2 && elect_one()) tma2d_prefetch_p(tmw, fcol, (9 + w) * 64, POL_RW);
      sts128(sb + R_VT + 5120 + tid * 16, pack2(p[0].x + p[2].x + p[4].x, p[0].y + p[2].y + p[4].y), pack2(p[0].z + p[2].z + p[4].z, p[0].w + p[2].w + p[4].w),
             pack2(p[1].x + p[3].x + p[5].x, p[1].y + p[3].y + p[5].y), pack2(p[1].z + p[3].z + p[5].z, p[1].w + p[3].w + p[5].w));
    }
    __syncthreads();
#pragma unroll 2
    for (int it = 0; it < 4 * nrg; it++) {
      const int r = it >> 2, rg = cta + 96 * r, c = 16 * warp + (lane >> 3) + 4 * (it & 3);
      uint32_t a[4], b[4], u[4], o[4];
      float t[2];
      lds128(u, sb + R_TAIL + (r * 8 + (lane & 7)) * 2064 + c * 16);
      lds128(a, sb + R_VT + 5120 + c * 16); lds128(b, sb + R_VT + 7168 + c * 16);
      lds64f(t, sb + R_VT + 3584 + (r * 8 + (lane & 7)) * 8);
#pragma unroll
      for (int j = 0; j < 4; j++)
        o[j] = pack2(fmaf(fmaf(bf_lo(u[j]), t[0], t[1]), 1.f + bf_lo(b[j]), bf_lo(a[j])), fmaf(fmaf(bf_hi(u[j]), t[0], t[1]), 1.f + bf_hi(b[j]), bf_hi(a[j])));
      *reinterpret_cast<uint4*>(g_h + (size_t)(rg >> 2) * 65536 + (lane & 7) * 16 + (c & 7) * 128 +
                                (c < 96 ? (c >> 3) * 4096 + (rg & 3) * 1024 : 49152 + (rg & 3) * 4096 + ((c >> 3) - 12) * 1024)) =
          make_uint4(o[0], o[1], o[2], o[3]);
    }
    TS(5);
    __syncthreads();
    TS(6);
    if (w < PF3 && elect_one()) tma2d_p(sb + R_TAIL + warp * 8192, tmw, fcol, 768 + w * 64, bars + B_TAIL, POL_RW);
    if (warp == 3 && lane == 0) { fence_gpu(); red_add_u32(&g_flags[FL_S2], 1); }
    __syncwarp();

    const uint32_t a0 = opaque32(sb + R_WO + wg * 49152 + ((lane >> 4) * 8 + (lane & 7)) * 128 + (((2 * w + ((lane >> 3) & 1)) ^ (lane & 7)) << 4));
    mbar_wait_safe(bars + B_STG + wg * 16, 0);
    TS(7);
#pragma unroll
    for (int i = 0; i < 24; i++) ldsm4t(W[i], a0 + i * 2048);
    if (tid == 0) wait_flag(&g_flags[FL_S2], 96);
    __syncthreads();
    asm volatile("fence.proxy.async.global;" ::: "memory");
    if (elect_one()) {
      if (wg == 0) load_chunk(sb + R_GA + w * 4096, 0, 12 + w, bars + B_FA);
      if (w == 0) mbar_expect(bars + B_STG + wg * 16 + 8, 49152);
#pragma unroll 1
      for (int c = w; c < 6; c += 4) tma2d_p(sb + R_WO + wg * 49152 + c * 8192, tmw, fcol, rot_chunk(6 + c, rank) * 64, bars + B_STG + wg * 16 + 8, POL_RW);
      if (warp == 0) mbar_expect(bars + B_TAIL, 65536);
      if (w >= PF3) tma2d_p(sb + R_TAIL + warp * 8192, tmw, fcol, 768 + w * 64, bars + B_TAIL, POL_RW);
      if (wg == 1) mbar_expect(bars + B_XS + 8 * w, w == 2 ? 0 : arm_size(w, rank == 2));
#pragma unroll 1
      for (int i = warp; i < PF4; i += 8) tma2d_prefetch(&tmo, 16 * wo_tile(i, rank), head * 128);
    }
    TS(8);
    mbar_wait_safe(bars + B_STG + wg * 16 + 8, 0);
    TS(9);
#pragma unroll
    for (int i = 0; i < 24; i++) ldsm4t(W[24 + i], a0 + i * 2048);
    __syncthreads();
    if (elect_one()) {
      const int n = rank == 2 ? 22 : 21;
      if (warp == 0) mbar_expect(bars + B_WO, n * 4096);
#pragma unroll 1
      for (int i = warp; i < n; i += 8) tma2d(sb + R_WO + i * 4096, &tmo, 16 * wo_tile(i, rank), head * 128, bars + B_WO);
    }
    sts32(sb + R_P + warp * 768 + 640 + lane * 4, wg == 0 ? 0u : 0xff80ff80u);
    mbar_wait_safe(bars + B_TAIL, 0);
    asm volatile("barrier.cluster.wait.aligned;\nbarrier.cluster.arrive.relaxed.aligned;\nbarrier.cluster.wait.aligned;" ::: "memory");
  }
  uint32_t rh[2];
  lds64(rh, bars + 248);
  rh[0] = __shfl_sync(0xffffffffu, rh[0], 0); rh[1] = __shfl_sync(0xffffffffu, rh[1], 0);
  if (wg == 0) r_main<0>(W, dsc, rh[1], rh[0], lane, w);
  else r_main<1>(W, dsc, rh[1], rh[0], lane, w);
  __syncthreads();
  if (rank < 2 && threadIdx.x == 0) { fence_gpu(); red_add_u32(&g_flags[FL_ATT + 8 * 15], 1); }
  asm volatile("barrier.cluster.arrive.release.aligned;\nbarrier.cluster.wait.acquire.aligned;" ::: "memory");
}

template <int TA> __device__ __forceinline__ void wg_ss256(float* d, uint64_t a, uint64_t b) {
  asm volatile("wgmma.mma_async.sync.aligned.m64n256k16.f32.bf16.bf16 {%0,%1,%2,%3,%4,%5,%6,%7,%8,%9,%10,%11,%12,%13,%14,%15,%16,%17,%18,%19,%20,%21,%22,%23,%24,%25,%26,%27,%28,%29,%30,%31,%32,%33,%34,%35,%36,%37,%38,%39,%40,%41,%42,%43,%44,%45,%46,%47,%48,%49,%50,%51,%52,%53,%54,%55,%56,%57,%58,%59,%60,%61,%62,%63,%64,%65,%66,%67,%68,%69,%70,%71,%72,%73,%74,%75,%76,%77,%78,%79,%80,%81,%82,%83,%84,%85,%86,%87,%88,%89,%90,%91,%92,%93,%94,%95,%96,%97,%98,%99,%100,%101,%102,%103,%104,%105,%106,%107,%108,%109,%110,%111,%112,%113,%114,%115,%116,%117,%118,%119,%120,%121,%122,%123,%124,%125,%126,%127}, %128, %129, 1, 1, 1, %130, 1;"
               : "+f"(d[0]), "+f"(d[1]), "+f"(d[2]), "+f"(d[3]), "+f"(d[4]), "+f"(d[5]), "+f"(d[6]), "+f"(d[7]),
                 "+f"(d[8]), "+f"(d[9]), "+f"(d[10]), "+f"(d[11]), "+f"(d[12]), "+f"(d[13]), "+f"(d[14]), "+f"(d[15]),
                 "+f"(d[16]), "+f"(d[17]), "+f"(d[18]), "+f"(d[19]), "+f"(d[20]), "+f"(d[21]), "+f"(d[22]), "+f"(d[23]),
                 "+f"(d[24]), "+f"(d[25]), "+f"(d[26]), "+f"(d[27]), "+f"(d[28]), "+f"(d[29]), "+f"(d[30]), "+f"(d[31]),
                 "+f"(d[32]), "+f"(d[33]), "+f"(d[34]), "+f"(d[35]), "+f"(d[36]), "+f"(d[37]), "+f"(d[38]), "+f"(d[39]),
                 "+f"(d[40]), "+f"(d[41]), "+f"(d[42]), "+f"(d[43]), "+f"(d[44]), "+f"(d[45]), "+f"(d[46]), "+f"(d[47]),
                 "+f"(d[48]), "+f"(d[49]), "+f"(d[50]), "+f"(d[51]), "+f"(d[52]), "+f"(d[53]), "+f"(d[54]), "+f"(d[55]),
                 "+f"(d[56]), "+f"(d[57]), "+f"(d[58]), "+f"(d[59]), "+f"(d[60]), "+f"(d[61]), "+f"(d[62]), "+f"(d[63]),
                 "+f"(d[64]), "+f"(d[65]), "+f"(d[66]), "+f"(d[67]), "+f"(d[68]), "+f"(d[69]), "+f"(d[70]), "+f"(d[71]),
                 "+f"(d[72]), "+f"(d[73]), "+f"(d[74]), "+f"(d[75]), "+f"(d[76]), "+f"(d[77]), "+f"(d[78]), "+f"(d[79]),
                 "+f"(d[80]), "+f"(d[81]), "+f"(d[82]), "+f"(d[83]), "+f"(d[84]), "+f"(d[85]), "+f"(d[86]), "+f"(d[87]),
                 "+f"(d[88]), "+f"(d[89]), "+f"(d[90]), "+f"(d[91]), "+f"(d[92]), "+f"(d[93]), "+f"(d[94]), "+f"(d[95]),
                 "+f"(d[96]), "+f"(d[97]), "+f"(d[98]), "+f"(d[99]), "+f"(d[100]), "+f"(d[101]), "+f"(d[102]), "+f"(d[103]),
                 "+f"(d[104]), "+f"(d[105]), "+f"(d[106]), "+f"(d[107]), "+f"(d[108]), "+f"(d[109]), "+f"(d[110]), "+f"(d[111]),
                 "+f"(d[112]), "+f"(d[113]), "+f"(d[114]), "+f"(d[115]), "+f"(d[116]), "+f"(d[117]), "+f"(d[118]), "+f"(d[119]),
                 "+f"(d[120]), "+f"(d[121]), "+f"(d[122]), "+f"(d[123]), "+f"(d[124]), "+f"(d[125]), "+f"(d[126]), "+f"(d[127])
               : "l"(a), "l"(b), "n"(TA));
}
template <int TA> __device__ __forceinline__ void wg_ss128(float* d, uint64_t a, uint64_t b) {
  asm volatile("wgmma.mma_async.sync.aligned.m64n128k16.f32.bf16.bf16 {%0,%1,%2,%3,%4,%5,%6,%7,%8,%9,%10,%11,%12,%13,%14,%15,%16,%17,%18,%19,%20,%21,%22,%23,%24,%25,%26,%27,%28,%29,%30,%31,%32,%33,%34,%35,%36,%37,%38,%39,%40,%41,%42,%43,%44,%45,%46,%47,%48,%49,%50,%51,%52,%53,%54,%55,%56,%57,%58,%59,%60,%61,%62,%63}, %64, %65, 1, 1, 1, %66, 1;"
               : "+f"(d[0]), "+f"(d[1]), "+f"(d[2]), "+f"(d[3]), "+f"(d[4]), "+f"(d[5]), "+f"(d[6]), "+f"(d[7]),
                 "+f"(d[8]), "+f"(d[9]), "+f"(d[10]), "+f"(d[11]), "+f"(d[12]), "+f"(d[13]), "+f"(d[14]), "+f"(d[15]),
                 "+f"(d[16]), "+f"(d[17]), "+f"(d[18]), "+f"(d[19]), "+f"(d[20]), "+f"(d[21]), "+f"(d[22]), "+f"(d[23]),
                 "+f"(d[24]), "+f"(d[25]), "+f"(d[26]), "+f"(d[27]), "+f"(d[28]), "+f"(d[29]), "+f"(d[30]), "+f"(d[31]),
                 "+f"(d[32]), "+f"(d[33]), "+f"(d[34]), "+f"(d[35]), "+f"(d[36]), "+f"(d[37]), "+f"(d[38]), "+f"(d[39]),
                 "+f"(d[40]), "+f"(d[41]), "+f"(d[42]), "+f"(d[43]), "+f"(d[44]), "+f"(d[45]), "+f"(d[46]), "+f"(d[47]),
                 "+f"(d[48]), "+f"(d[49]), "+f"(d[50]), "+f"(d[51]), "+f"(d[52]), "+f"(d[53]), "+f"(d[54]), "+f"(d[55]),
                 "+f"(d[56]), "+f"(d[57]), "+f"(d[58]), "+f"(d[59]), "+f"(d[60]), "+f"(d[61]), "+f"(d[62]), "+f"(d[63])
               : "l"(a), "l"(b), "n"(TA));
}
template <int TA> __device__ __forceinline__ void wg_ss256_first(float* d, uint64_t a, uint64_t b) {
  asm volatile("wgmma.mma_async.sync.aligned.m64n256k16.f32.bf16.bf16 {%0,%1,%2,%3,%4,%5,%6,%7,%8,%9,%10,%11,%12,%13,%14,%15,%16,%17,%18,%19,%20,%21,%22,%23,%24,%25,%26,%27,%28,%29,%30,%31,%32,%33,%34,%35,%36,%37,%38,%39,%40,%41,%42,%43,%44,%45,%46,%47,%48,%49,%50,%51,%52,%53,%54,%55,%56,%57,%58,%59,%60,%61,%62,%63,%64,%65,%66,%67,%68,%69,%70,%71,%72,%73,%74,%75,%76,%77,%78,%79,%80,%81,%82,%83,%84,%85,%86,%87,%88,%89,%90,%91,%92,%93,%94,%95,%96,%97,%98,%99,%100,%101,%102,%103,%104,%105,%106,%107,%108,%109,%110,%111,%112,%113,%114,%115,%116,%117,%118,%119,%120,%121,%122,%123,%124,%125,%126,%127}, %128, %129, 0, 1, 1, %130, 1;"
               : "=f"(d[0]), "=f"(d[1]), "=f"(d[2]), "=f"(d[3]), "=f"(d[4]), "=f"(d[5]), "=f"(d[6]), "=f"(d[7]),
                 "=f"(d[8]), "=f"(d[9]), "=f"(d[10]), "=f"(d[11]), "=f"(d[12]), "=f"(d[13]), "=f"(d[14]), "=f"(d[15]),
                 "=f"(d[16]), "=f"(d[17]), "=f"(d[18]), "=f"(d[19]), "=f"(d[20]), "=f"(d[21]), "=f"(d[22]), "=f"(d[23]),
                 "=f"(d[24]), "=f"(d[25]), "=f"(d[26]), "=f"(d[27]), "=f"(d[28]), "=f"(d[29]), "=f"(d[30]), "=f"(d[31]),
                 "=f"(d[32]), "=f"(d[33]), "=f"(d[34]), "=f"(d[35]), "=f"(d[36]), "=f"(d[37]), "=f"(d[38]), "=f"(d[39]),
                 "=f"(d[40]), "=f"(d[41]), "=f"(d[42]), "=f"(d[43]), "=f"(d[44]), "=f"(d[45]), "=f"(d[46]), "=f"(d[47]),
                 "=f"(d[48]), "=f"(d[49]), "=f"(d[50]), "=f"(d[51]), "=f"(d[52]), "=f"(d[53]), "=f"(d[54]), "=f"(d[55]),
                 "=f"(d[56]), "=f"(d[57]), "=f"(d[58]), "=f"(d[59]), "=f"(d[60]), "=f"(d[61]), "=f"(d[62]), "=f"(d[63]),
                 "=f"(d[64]), "=f"(d[65]), "=f"(d[66]), "=f"(d[67]), "=f"(d[68]), "=f"(d[69]), "=f"(d[70]), "=f"(d[71]),
                 "=f"(d[72]), "=f"(d[73]), "=f"(d[74]), "=f"(d[75]), "=f"(d[76]), "=f"(d[77]), "=f"(d[78]), "=f"(d[79]),
                 "=f"(d[80]), "=f"(d[81]), "=f"(d[82]), "=f"(d[83]), "=f"(d[84]), "=f"(d[85]), "=f"(d[86]), "=f"(d[87]),
                 "=f"(d[88]), "=f"(d[89]), "=f"(d[90]), "=f"(d[91]), "=f"(d[92]), "=f"(d[93]), "=f"(d[94]), "=f"(d[95]),
                 "=f"(d[96]), "=f"(d[97]), "=f"(d[98]), "=f"(d[99]), "=f"(d[100]), "=f"(d[101]), "=f"(d[102]), "=f"(d[103]),
                 "=f"(d[104]), "=f"(d[105]), "=f"(d[106]), "=f"(d[107]), "=f"(d[108]), "=f"(d[109]), "=f"(d[110]), "=f"(d[111]),
                 "=f"(d[112]), "=f"(d[113]), "=f"(d[114]), "=f"(d[115]), "=f"(d[116]), "=f"(d[117]), "=f"(d[118]), "=f"(d[119]),
                 "=f"(d[120]), "=f"(d[121]), "=f"(d[122]), "=f"(d[123]), "=f"(d[124]), "=f"(d[125]), "=f"(d[126]), "=f"(d[127])
               : "l"(a), "l"(b), "n"(TA));
}
template <int TA> __device__ __forceinline__ void wg_ss128_first(float* d, uint64_t a, uint64_t b) {
  asm volatile("wgmma.mma_async.sync.aligned.m64n128k16.f32.bf16.bf16 {%0,%1,%2,%3,%4,%5,%6,%7,%8,%9,%10,%11,%12,%13,%14,%15,%16,%17,%18,%19,%20,%21,%22,%23,%24,%25,%26,%27,%28,%29,%30,%31,%32,%33,%34,%35,%36,%37,%38,%39,%40,%41,%42,%43,%44,%45,%46,%47,%48,%49,%50,%51,%52,%53,%54,%55,%56,%57,%58,%59,%60,%61,%62,%63}, %64, %65, 0, 1, 1, %66, 1;"
               : "=f"(d[0]), "=f"(d[1]), "=f"(d[2]), "=f"(d[3]), "=f"(d[4]), "=f"(d[5]), "=f"(d[6]), "=f"(d[7]),
                 "=f"(d[8]), "=f"(d[9]), "=f"(d[10]), "=f"(d[11]), "=f"(d[12]), "=f"(d[13]), "=f"(d[14]), "=f"(d[15]),
                 "=f"(d[16]), "=f"(d[17]), "=f"(d[18]), "=f"(d[19]), "=f"(d[20]), "=f"(d[21]), "=f"(d[22]), "=f"(d[23]),
                 "=f"(d[24]), "=f"(d[25]), "=f"(d[26]), "=f"(d[27]), "=f"(d[28]), "=f"(d[29]), "=f"(d[30]), "=f"(d[31]),
                 "=f"(d[32]), "=f"(d[33]), "=f"(d[34]), "=f"(d[35]), "=f"(d[36]), "=f"(d[37]), "=f"(d[38]), "=f"(d[39]),
                 "=f"(d[40]), "=f"(d[41]), "=f"(d[42]), "=f"(d[43]), "=f"(d[44]), "=f"(d[45]), "=f"(d[46]), "=f"(d[47]),
                 "=f"(d[48]), "=f"(d[49]), "=f"(d[50]), "=f"(d[51]), "=f"(d[52]), "=f"(d[53]), "=f"(d[54]), "=f"(d[55]),
                 "=f"(d[56]), "=f"(d[57]), "=f"(d[58]), "=f"(d[59]), "=f"(d[60]), "=f"(d[61]), "=f"(d[62]), "=f"(d[63])
               : "l"(a), "l"(b), "n"(TA));
}

constexpr int H_STAGE = 49152, H_NST = 4;
constexpr int H_STG = H_NST * H_STAGE;
constexpr int H_VEC = H_STG + 16384;
constexpr int H_BAR = H_VEC + 6144;
constexpr int H_SMEM = H_BAR + 256;
constexpr int HB_FULL = 0, HB_EMPTY = 32, HB_IFULL = 64, HB_IEMPTY = 80, HB_VFULL = 96, HB_STGF = 112, HB_ITEM = 120, HB_SLOT = 128, HB_Q = 136;
enum { IT_END = 0, IT_MOD = 1, IT_XT = 2, IT_OUT = 3, IT_WS = 4, IT_F1 = 5, IT_F2 = 6, IT_STAT = 7 };
constexpr int N_MOD = 32, N_WS = 28, N_XT = 2, N_STAT = 4;
constexpr int MAX_ITEMS = 1400;
struct HList { uint32_t n; uint32_t it[MAX_ITEMS]; };
#define HT(i)

#define POL_WO L2_NORMAL
#define POL_W2 L2_NORMAL
#define POL_ATT L2_FIRST
#define POL_ACT L2_FIRST
#define POL_PRE L2_FIRST
__device__ __forceinline__ void mbar_arrive_n(uint32_t b, uint32_t n) { asm volatile("mbarrier.arrive.shared::cta.b64 _, [%0], %1;" :: "r"(b), "r"(n) : "memory"); }
__device__ __forceinline__ void bulk_s2g(void* dst, uint32_t src, uint32_t bytes) {
  asm volatile("cp.async.bulk.global.shared::cta.bulk_group [%0], [%1], %2;" :: "l"(dst), "r"(src), "r"(bytes) : "memory");
}
__device__ __forceinline__ void tma2d_add(const CUtensorMap* m, int c0, int c1, uint32_t src) {
  asm volatile("cp.reduce.async.bulk.tensor.2d.global.shared::cta.add.tile.bulk_group [%0, {%2, %3}], [%1];" :: "l"(m), "r"(src), "r"(c0), "r"(c1) : "memory");
}
__device__ __forceinline__ void bulk_commit() { asm volatile("cp.async.bulk.commit_group;" ::: "memory"); }
template <int N> __device__ __forceinline__ void bulk_wait_read() { asm volatile("cp.async.bulk.wait_group.read %0;" :: "n"(N) : "memory"); }
__device__ __forceinline__ void bulk_wait_all() { asm volatile("cp.async.bulk.wait_group 0;" ::: "memory"); }
__device__ __forceinline__ uint32_t hfma2(uint32_t a, uint32_t b, uint32_t c) { uint32_t t; asm("fma.rn.bf16x2 %0, %1, %2, %3;" : "=r"(t) : "r"(a), "r"(b), "r"(c)); return t; }
__device__ __forceinline__ float lds32f(uint32_t a) { return __uint_as_float(lds32(a)); }

template <int BN, int TA>
__device__ __forceinline__ uint32_t h_mainloop(float* acc, uint32_t sb, int nst, uint32_t& st, uint32_t& ph, int wg, bool leader, bool borrow) {
  const uint64_t da0 = TA ? mkdesc(sb + wg * 1024, 2048, 128, 0) : mkdesc(sb + wg * 8192, 16, 1024, 1);
  const uint64_t db0 = mkdesc(sb + 16384, 8192, 1024, 1);
  uint32_t prev = st;
  {
    mbar_wait(sb + H_BAR + HB_FULL + st * 8, ph);
    HT(1);
    const uint64_t da = da0 + st * (H_STAGE >> 4), db = db0 + st * (H_STAGE >> 4);
    WG_FENCE();
    if (BN == 256) wg_ss256_first<TA>(acc, da, db); else wg_ss128_first<TA>(acc, da, db);
#pragma unroll
    for (int k = 1; k < 4; k++) {
      const uint64_t a = da + k * (TA ? 256 : 2), b = db + k * 128;
      if (BN == 256) wg_ss256<TA>(acc, a, b); else wg_ss128<TA>(acc, a, b);
    }
    WG_COMMIT();
    if (++st == H_NST) { st = 0; ph ^= 1; }
  }
#pragma unroll 1
  for (int i = 1; i < nst; i++) {
    mbar_wait(sb + H_BAR + HB_FULL + st * 8, ph);
    const uint64_t da = da0 + st * (H_STAGE >> 4), db = db0 + st * (H_STAGE >> 4);
    WG_FENCE();
#pragma unroll
    for (int k = 0; k < 4; k++) {
      const uint64_t a = da + k * (TA ? 256 : 2), b = db + k * 128;
      if (BN == 256) wg_ss256<TA>(acc, a, b); else wg_ss128<TA>(acc, a, b);
    }
    WG_COMMIT();
    WG_WAIT(1);
    if (leader) mbar_arrive(sb + H_BAR + HB_EMPTY + prev * 8);
    prev = st;
    if (++st == H_NST) { st = 0; ph ^= 1; }
  }
  WG_WAIT(0);
  reg_fence<BN / 2>(acc);
  if (!borrow && leader) mbar_arrive(sb + H_BAR + HB_EMPTY + prev * 8);
  HT(2);
  return prev;
}

template <int BN>
__device__ __forceinline__ void h_gated(const float* acc, uint32_t va, uint32_t stg, uint32_t slot, int warp, int lane) {
  const uint32_t ro = (warp * 16 + (lane & 7)) * 128, x0 = ((lane >> 3) ^ (lane & 7)) << 4;
  va += (lane & 3) * 32;
#pragma unroll
  for (int u = 0; u < BN / 64; u++) {
    if (u == 1) bar_sync<1, 256>();
    const uint32_t base = (u == 0 ? stg : slot + (u - 1) * 16384) + ro;
#pragma unroll
    for (int c2 = 0; c2 < 2; c2++) {
      const int c = 2 * u + c2;
      float g[8];
      lds128f(g, va + c * 128); lds128f(g + 4, va + c * 128 + 16);
#pragma unroll
      for (int h = 0; h < 2; h++) {
        uint32_t y[4];
#pragma unroll
        for (int j = 0; j < 4; j++) { const float* a = acc + c * 16 + j * 4 + h * 2; y[j] = pack2(g[2 * j] * a[0], g[2 * j + 1] * a[1]); }
        stsm4(base + h * 1024 + (x0 ^ (c2 << 6)), y);
      }
    }
  }
}

template <int BN>
__device__ __forceinline__ void h_swiglu(const float* acc, uint32_t va, uint32_t stg, uint32_t slot, int warp, int lane) {
  const uint32_t ro = (warp * 16 + (lane & 7)) * 128, x0 = ((lane >> 3) ^ (lane & 7)) << 4;
  float rs[2], rh[2], nm[2];
#pragma unroll
  for (int h = 0; h < 2; h++) {
    float t[2];
    lds64f(t, va + 2048 + (warp * 16 + h * 8 + (lane >> 2)) * 8);
    rs[h] = t[0]; rh[h] = 0.5f * t[0]; nm[h] = t[1];
  }
  va += (lane & 3) * 32;
#pragma unroll
  for (int c = 0; c < BN / 64; c++) {
    uint32_t y[2][4];
#pragma unroll
    for (int j = 0; j < 4; j++) {
      const float* g = acc + 16 * c + 4 * j; const float* u = g + BN / 4;
      float p[4], q[4], o[4];
      lds128f(p, va + (4 * c + j) * 128); lds128f(q, va + (4 * c + j) * 128 + 16);
#pragma unroll
      for (int e = 0; e < 4; e++) {
        const float g2 = fmaf(rh[e >> 1], g[e], fmaf(nm[e >> 1], p[e & 1], p[2 + (e & 1)]));
        const float h = g2 * fmaf(rs[e >> 1], u[e], fmaf(nm[e >> 1], q[e & 1], q[2 + (e & 1)]));
        float t; asm("tanh.approx.f32 %0, %1;" : "=f"(t) : "f"(g2));
        o[e] = fmaf(h, t, h);
      }
      y[0][j] = pack2(o[0], o[1]); y[1][j] = pack2(o[2], o[3]);
    }
    const uint32_t base = ((c >> 1) == 0 ? stg : slot) + ro + (x0 ^ ((c & 1) << 6));
    stsm4(base, y[0]); stsm4(base + 1024, y[1]);
  }
}

template <bool WS>
__device__ __forceinline__ void h_vecmat(uint32_t sb, int idx, uint32_t& st, uint32_t& ph, int tid, const __nv_bfloat16* cvec, uint8_t* w13s, float* uv,
                                         __nv_bfloat16* mod, float* gate) {
  const uint32_t stg = sb + H_STG, bars = sb + H_BAR;
  const int lane = tid & 31, warp = tid >> 5;
#pragma unroll
  for (int i = 0; i < 4; i++) {
    const int k = tid + 256 * i;
    if (WS) {
      const uint32_t s = __ldcg(reinterpret_cast<const uint16_t*>(mod) + 3 * D_ + k), c = __ldcg(reinterpret_cast<const uint16_t*>(mod) + 4 * D_ + k);
      sts32(stg + k * 4, s << 16); sts32(stg + 4096 + k * 4, c | c << 16);
    } else {
      const float c = __bfloat162float(cvec[k]);
      sts32(stg + k * 4, __float_as_uint(__bfloat162float(__float2bfloat16(c / (1.f + __expf(-c))))));
    }
  }
  bar_sync<1, 256>();
  float v[4][8], u[4][8];
#pragma unroll
  for (int b = 0; b < 4; b++)
#pragma unroll
    for (int e = 0; e < 8; e++) { v[b][e] = 0.f; u[b][e] = 0.f; }
  const int r0 = tid >> 3;
  const uint32_t off = 16384 + r0 * 128 + (((tid & 7) ^ (r0 & 7)) << 4);
  uint32_t prev = 0;
#pragma unroll 1
  for (int i = 0; i < (WS ? 16 : 8); i++) {
    mbar_wait(bars + HB_FULL + st * 8, ph);
    const uint32_t base = sb + st * H_STAGE + off;
#pragma unroll
    for (int ri = 0; ri < 2; ri++) {
      const uint32_t ka = stg + ((WS ? i * 64 : i * 128) + r0 + 32 * ri) * 4;
      const float m0 = lds32f(ka), m1 = WS ? m0 : lds32f(ka + 256);
      const uint32_t c2 = WS ? lds32(ka + 4096) : 0;
#pragma unroll
      for (int b = 0; b < 4; b++) {
        uint32_t w[4];
        lds128(w, base + b * 8192 + ri * 4096);
        const float m = b < 2 ? m0 : m1;
#pragma unroll
        for (int e = 0; e < 4; e++) {
          v[b][2 * e] = fmaf(m, bf_lo(w[e]), v[b][2 * e]); v[b][2 * e + 1] = fmaf(m, bf_hi(w[e]), v[b][2 * e + 1]);
          if (WS) { w[e] = hfma2(w[e], c2, w[e]); u[b][2 * e] += bf_lo(w[e]); u[b][2 * e + 1] += bf_hi(w[e]); }
        }
        if (WS) sts128(base + b * 8192 + ri * 4096, w[0], w[1], w[2], w[3]);
      }
    }
    if (WS) fence_async_smem();
    bar_sync<1, 256>();
    if (tid == 0) {
      if (WS) {
        bulk_s2g(w13s + (size_t)(idx * 16 + i) * 32768, sb + st * H_STAGE + 16384, 32768);
        bulk_commit();
        if (i > 0) { bulk_wait_read<1>(); mbar_arrive_n(bars + HB_EMPTY + prev * 8, 2); }
      } else mbar_arrive_n(bars + HB_EMPTY + st * 8, 2);
    }
    prev = st;
    if (++st == H_NST) { st = 0; ph ^= 1; }
  }
  if (WS && tid == 0) {
    bulk_wait_read<0>(); mbar_arrive_n(bars + HB_EMPTY + prev * 8, 2);
    bulk_wait_all(); fence_async_all(); fence_gpu();
  }
#pragma unroll
  for (int b = 0; b < 4; b++)
#pragma unroll
    for (int e = 0; e < 8; e++) {
      v[b][e] += __shfl_xor_sync(0xffffffffu, v[b][e], 8); v[b][e] += __shfl_xor_sync(0xffffffffu, v[b][e], 16);
      if (WS) { u[b][e] += __shfl_xor_sync(0xffffffffu, u[b][e], 8); u[b][e] += __shfl_xor_sync(0xffffffffu, u[b][e], 16); }
    }
  if (lane < 8) {
#pragma unroll
    for (int b = 0; b < 4; b++) {
      const uint32_t a = stg + warp * 2048 + b * 256 + lane * 32;
      sts128(a, __float_as_uint(v[b][0]), __float_as_uint(v[b][1]), __float_as_uint(v[b][2]), __float_as_uint(v[b][3]));
      sts128(a + 16, __float_as_uint(v[b][4]), __float_as_uint(v[b][5]), __float_as_uint(v[b][6]), __float_as_uint(v[b][7]));
      if (WS) {
        sts128(a + 1024, __float_as_uint(u[b][0]), __float_as_uint(u[b][1]), __float_as_uint(u[b][2]), __float_as_uint(u[b][3]));
        sts128(a + 1040, __float_as_uint(u[b][4]), __float_as_uint(u[b][5]), __float_as_uint(u[b][6]), __float_as_uint(u[b][7]));
      }
    }
  }
  bar_sync<1, 256>();
  float sv = 0.f, su = 0.f;
#pragma unroll
  for (int i = 0; i < 8; i++) {
    sv += lds32f(stg + i * 2048 + tid * 4);
    su += WS ? lds32f(stg + i * 2048 + 1024 + tid * 4) : lds32f(stg + i * 2048 + (tid ^ 128) * 4);
  }
  if (WS) {
    const int n = tid & 127, up = tid >> 7, c = n >> 5, j = (n >> 3) & 3, t = (n >> 1) & 3, e = n & 1;
    float* p = uv + idx * 512 + (c * 4 + j) * 32 + t * 8 + up * 4 + e;
    const float s = up ? 1.f : 0.5f;
    p[0] = s * su; p[2] = s * sv;
  } else if (tid < 128) {
    const int n = idx * 128 + tid, vec = n >> 10, col = n & 1023;
    const __nv_bfloat16 r = __float2bfloat16(sv + su);
    mod[2048 + n] = r;
    if (vec == 0 || vec == 3) gate[(vec ? D_ : 0) + (col & ~31) + ((col >> 1) & 3) * 8 + ((col >> 3) & 3) * 2 + (col & 1)] = __bfloat162float(r);
  }
}

__global__ void __launch_bounds__(384, 1)
kernel_H(const __grid_constant__ CUtensorMap tmo, const __grid_constant__ CUtensorMap tm1, const __grid_constant__ CUtensorMap tm3,
         const __grid_constant__ CUtensorMap tm2, const __grid_constant__ CUtensorMap tmm, const __grid_constant__ CUtensorMap tmx,
         const __nv_bfloat16* __restrict__ x, const __nv_bfloat16* __restrict__ cvec, __nv_bfloat16* out, const __grid_constant__ HList list) {
  extern __shared__ __align__(1024) uint8_t smem[];
  constexpr uint32_t sb = 0x400, bars = sb + H_BAR;
  const int tid = threadIdx.x, lane = tid & 31;
  const int warp = __shfl_sync(0xffffffffu, tid >> 5, 0);
  if (tid == 0) {
    if (smem_u32(smem) != sb) __trap();
    for (int i = 0; i < H_NST; i++) { mbar_init(bars + HB_FULL + i * 8, 1); mbar_init(bars + HB_EMPTY + i * 8, 2); }
    for (int i = 0; i < 2; i++) { mbar_init(bars + HB_IFULL + i * 8, 1); mbar_init(bars + HB_IEMPTY + i * 8, 1); mbar_init(bars + HB_VFULL + i * 8, 1); }
    mbar_init(bars + HB_STGF, 1);
    fence_async_smem();
  }
  __syncthreads();
  if (warp >= 8) {
    asm volatile("setmaxnreg.dec.sync.aligned.u32 40;");
    if (warp == 8) {
      uint32_t st = 0, ph = 1, nv = 0, q = 0;
      if (lane == 0) q = atomicAdd(&g_flags[FL_HEAD], 1);
#pragma unroll 1
      for (uint32_t n = 0;; n++) {
        q = __shfl_sync(0xffffffffu, q, 0);
        const uint32_t it = q < list.n ? list.it[q] : 0;
        const int type = it & 7, mt = (it >> 3) & 15, idx = (it >> 7) & 63, sz = (it >> 13) & 3, kb0 = (it >> 15) & 63, nkb = (it >> 21) & 127;
        {
          int f = FL_GO; uint32_t target = 0;
          if (type == IT_OUT) { f = lane == 0 ? FL_ATT + 8 * mt : lane == 1 ? FL_XT + 8 * mt : FL_MOD; target = lane == 0 ? 64 : lane == 1 ? N_XT : N_MOD; }
          else if (type == IT_F1) { f = lane == 0 ? FL_OUT + 8 * mt : FL_WS; target = lane == 0 ? 1024 : N_WS; }
          else if (type == IT_F2) { f = FL_F1 + 8 * mt; target = 56; }
          else if (type == IT_STAT) { f = FL_OUT + 8 * mt; target = 1024; }
          else if (type == IT_WS) { f = FL_MOD; target = N_MOD; }
          else if (type != IT_END) target = 1;
          if (lane < 3) wait_flag(&g_flags[f], target);
          __syncwarp();
          asm volatile("fence.proxy.async.global;" ::: "memory");
        }
        mbar_wait(bars + HB_IEMPTY + (n & 1) * 8, ((n >> 1) & 1) ^ 1);
        if (elect_one()) {
          sts32(bars + HB_ITEM + (n & 1) * 4, it);
          mbar_arrive(bars + HB_IFULL + (n & 1) * 8);
        }
        if (type == IT_END) break;
        const bool gemm = type == IT_OUT || type == IT_F1 || type == IT_F2;
        const int nst = gemm ? nkb : type == IT_WS ? 16 : type == IT_MOD ? 8 : 0;
        const int bn = 256 >> sz;
        const uint8_t* ap = type == IT_OUT ? g_att + (size_t)mt * 64 * 16384 : g_act + (size_t)mt * 56 * 16384;
        const uint8_t* wp = g_w13s + (size_t)(idx >> sz) * 16 * 32768 + (sz ? (idx & 1) * 8192 : 0);
        const CUtensorMap* tb = type == IT_OUT ? &tmo : type == IT_F2 ? &tm2 : type == IT_WS ? &tm1 : &tmm;
        const CUtensorMap* tc = type == IT_WS ? &tm3 : tb;
        const int c0 = gemm ? idx * bn : type == IT_WS ? idx * 128 : 2048 + idx * 128, dcol = gemm ? 128 : 0, kmul = type == IT_MOD ? 128 : 64, drow = type == IT_MOD ? 64 : 0;
        const uint32_t bytes = gemm ? 16384 + bn * 128 : 32768;
        const uint64_t pa = type == IT_OUT ? POL_ATT : POL_ACT, pb = type == IT_OUT ? POL_WO : type == IT_F2 ? POL_W2 : POL_PRE;
        if (nst < 2 && lane == 0) q = atomicAdd(&g_flags[FL_HEAD], 1);
#pragma unroll 1
        for (int i = 0; i < nst; i++) {
          const int kb = kb0 + i;
          const uint32_t d = sb + st * H_STAGE, fb = bars + HB_FULL + st * 8;
          if (i == nst - 2 && lane == 0) q = atomicAdd(&g_flags[FL_HEAD], 1);
          mbar_wait(bars + HB_EMPTY + st * 8, ph);
          if (elect_one()) {
            mbar_expect(fb, bytes);
            if (type == IT_F1) {
              tma2d(d, &tmx, kb * 64, mt * 128, fb);
              if (sz == 0) bulk_g2s(d + 16384, wp + (size_t)kb * 32768, 32768, fb);
              else { bulk_g2s(d + 16384, wp + (size_t)kb * 32768, 8192, fb); bulk_g2s(d + 24576, wp + (size_t)kb * 32768 + 16384, 8192, fb); }
            } else {
              if (gemm) bulk_g2s_p(d, ap + (size_t)kb * 16384, 16384, fb, pa);
              tma2d_p(d + 16384, tb, c0, kb * kmul, fb, pb);
              tma2d_p(d + 24576, tb, c0 + 64, kb * kmul, fb, pb);
              if (sz == 0) { tma2d_p(d + 32768, tc, c0 + dcol, kb * kmul + drow, fb, pb); tma2d_p(d + 40960, tc, c0 + dcol + 64, kb * kmul + drow, fb, pb); }
            }
          }
          if (++st == H_NST) { st = 0; ph ^= 1; }
        }
        if (gemm) {
          if (type == IT_F1) {
            if (lane == 0) wait_flag(&g_flags[FL_STAT + 8 * mt], N_STAT);
            __syncwarp();
            asm volatile("fence.proxy.async.global;" ::: "memory");
          }
          if (elect_one()) {
            const uint32_t v = sb + H_VEC + (nv & 1) * 3072, fb = bars + HB_VFULL + (nv & 1) * 8;
            if (type == IT_F1) {
              mbar_expect(fb, (2048 >> sz) + 1024);
              bulk_g2s(v, g_uv + idx * (512 >> sz), 2048 >> sz, fb);
              bulk_g2s(v + 2048, g_stat + mt * 256, 1024, fb);
            } else {
              mbar_expect(fb, bn * 4);
              bulk_g2s(v, g_gate + (type == IT_F2 ? D_ : 0) + c0, bn * 4, fb);
            }
          }
          nv++;
        }
      }
    } else if (warp == 9) {
#pragma unroll 1
      for (uint32_t n = 0;; n++) {
        mbar_wait(bars + HB_IFULL + (n & 1) * 8, (n >> 1) & 1);
        const uint32_t it = lds32(bars + HB_ITEM + (n & 1) * 4);
        const int type = it & 7, mt = (it >> 3) & 15, idx = (it >> 7) & 63, sz = (it >> 13) & 3, nkb = (it >> 21) & 127;
        if (type == IT_END) break;
        if (n & 1) bar_sync<3, 288>(); else bar_sync<2, 288>();
        if (lane == 0) {
          const bool gated = type == IT_OUT || type == IT_F2, gemm = gated || type == IT_F1;
          if (gemm) {
            const uint32_t slot = lds32(bars + HB_SLOT + (n & 1) * 4);
            const int nu = (gated ? 4 : 2) >> sz;
#pragma unroll 1
            for (int u = 0; u < nu; u++) {
              const uint32_t src = u == 0 ? sb + H_STG : sb + slot * H_STAGE + (u - 1) * 16384;
              if (gated) tma2d_add(&tmx, idx * (256 >> sz) + u * 64, mt * 128, src);
              else bulk_s2g(g_act + (size_t)(mt * 56 + idx * nu + u) * 16384, src, 16384);
            }
            bulk_commit();
            bulk_wait_read<0>();
            if (nu > 1) mbar_arrive_n(bars + HB_EMPTY + slot * 8, 2);
          }
          mbar_arrive(bars + HB_STGF);
          mbar_arrive(bars + HB_IEMPTY + (n & 1) * 8);
          if (gemm) { bulk_wait_all(); fence_async_all(); }
          if (type != IT_F2) {
            const uint32_t inc = type == IT_OUT ? (4 >> sz) * nkb : type == IT_F1 ? 2 >> sz : 1;
            fence_gpu();
            red_add_u32(&g_flags[type == IT_MOD ? FL_MOD : type == IT_WS ? FL_WS :
                                 (type == IT_XT ? FL_XT : type == IT_OUT ? FL_OUT : type == IT_STAT ? FL_STAT : FL_F1) + 8 * mt], inc);
          }
        }
        __syncwarp();
      }
      asm volatile("griddepcontrol.wait;" ::: "memory");
      uint32_t k = 0;
      if (lane == 0) { fence_gpu(); k = atomicAdd(&g_flags[FL_EXIT], 1); }
      k = __shfl_sync(0xffffffffu, k, 0);
      if (k == gridDim.x - 1) {
        fence_gpu();
        for (int i = lane; i < 1024; i += 32) g_flags[i] = 0;
      }
    }
  } else {
    asm volatile("setmaxnreg.inc.sync.aligned.u32 232;");
    const int wg = warp >> 2;
    const bool leader = (tid & 127) == 0;
    uint32_t st = 0, ph = 0, nv = 0;
#pragma unroll 1
    for (uint32_t n = 0;; n++) {
      mbar_wait(bars + HB_IFULL + (n & 1) * 8, (n >> 1) & 1);
      const uint32_t it = __shfl_sync(0xffffffffu, lds32(bars + HB_ITEM + (n & 1) * 4), 0);
      const int type = it & 7, mt = (it >> 3) & 15, idx = (it >> 7) & 63, sz = (it >> 13) & 3, nkb = (it >> 21) & 127;
      if (type == IT_END) break;
      if (type == IT_OUT || type == IT_F1 || type == IT_F2) {
        const uint32_t va = sb + H_VEC + (nv & 1) * 3072, vb = bars + HB_VFULL + (nv & 1) * 8, vp = (nv >> 1) & 1;
        uint32_t last;
        nv++;
        if (sz == 0) {
          float acc[128];
          if (type == IT_OUT) last = h_mainloop<256, 1>(acc, sb, nkb, st, ph, wg, leader, true);
          else last = h_mainloop<256, 0>(acc, sb, nkb, st, ph, wg, leader, true);
          mbar_wait(vb, vp);
          mbar_wait(bars + HB_STGF, (n & 1) ^ 1);
          if (type == IT_F1) h_swiglu<256>(acc, va, sb + H_STG, sb + last * H_STAGE, warp, lane);
          else h_gated<256>(acc, va, sb + H_STG, sb + last * H_STAGE, warp, lane);
        } else {
          float acc[64];
          if (type == IT_OUT) last = h_mainloop<128, 1>(acc, sb, nkb, st, ph, wg, leader, true);
          else last = h_mainloop<128, 0>(acc, sb, nkb, st, ph, wg, leader, type == IT_F2);
          mbar_wait(vb, vp);
          mbar_wait(bars + HB_STGF, (n & 1) ^ 1);
          if (type == IT_F1) h_swiglu<128>(acc, va, sb + H_STG, sb + last * H_STAGE, warp, lane);
          else h_gated<128>(acc, va, sb + H_STG, sb + last * H_STAGE, warp, lane);
        }
        if (tid == 0) sts32(bars + HB_SLOT + (n & 1) * 4, last);
        fence_async_smem();
      } else if (type == IT_XT) {
        const uint4* xp = reinterpret_cast<const uint4*>(x + (size_t)(mt * 128 + idx * 64) * D_) + tid;
        uint4* op = reinterpret_cast<uint4*>(out + (size_t)(mt * 128 + idx * 64) * D_) + tid;
#pragma unroll 1
        for (int b = 0; b < 2; b++) {
          uint4 v[16];
#pragma unroll
          for (int i = 0; i < 16; i++) v[i] = __ldcs(xp + (b * 16 + i) * 256);
#pragma unroll
          for (int i = 0; i < 16; i++) op[(b * 16 + i) * 256] = v[i];
        }
      } else if (type == IT_STAT) {
        const int row0 = mt * 128 + idx * 32 + warp * 4;
        const uint4* xp = reinterpret_cast<const uint4*>(out + (size_t)row0 * D_) + lane;
        uint4 v[16];
#pragma unroll
        for (int i = 0; i < 16; i++) v[i] = __ldcg(xp + (i >> 2) * 128 + (i & 3) * 32);
        float s[4], m[4];
#pragma unroll
        for (int r = 0; r < 4; r++) {
          s[r] = 0.f;
#pragma unroll
          for (int i = 0; i < 4; i++) {
            const uint4 w = v[4 * r + i];
            s[r] += ((bf_lo(w.x) + bf_hi(w.x)) + (bf_lo(w.y) + bf_hi(w.y))) + ((bf_lo(w.z) + bf_hi(w.z)) + (bf_lo(w.w) + bf_hi(w.w)));
          }
        }
#pragma unroll
        for (int o = 1; o < 32; o <<= 1)
#pragma unroll
          for (int r = 0; r < 4; r++) s[r] += __shfl_xor_sync(0xffffffffu, s[r], o);
#pragma unroll
        for (int r = 0; r < 4; r++) {
          m[r] = s[r] * (1.f / D_);
          float a = 0.f, b = 0.f;
#pragma unroll
          for (int i = 0; i < 4; i++) {
            const uint4 w = v[4 * r + i];
            const uint32_t ww[4] = {w.x, w.y, w.z, w.w};
#pragma unroll
            for (int e = 0; e < 4; e++) { const float p = bf_lo(ww[e]) - m[r], t = bf_hi(ww[e]) - m[r]; a = fmaf(p, p, a); b = fmaf(t, t, b); }
          }
          s[r] = a + b;
        }
#pragma unroll
        for (int o = 1; o < 32; o <<= 1)
#pragma unroll
          for (int r = 0; r < 4; r++) s[r] += __shfl_xor_sync(0xffffffffu, s[r], o);
        if (lane < 4) {
          const float sr = lane == 0 ? s[0] : lane == 1 ? s[1] : lane == 2 ? s[2] : s[3], mr = lane == 0 ? m[0] : lane == 1 ? m[1] : lane == 2 ? m[2] : m[3];
          const float rs = rsqrtf(sr * (1.f / D_) + 1e-5f);
          reinterpret_cast<float2*>(g_stat)[row0 + lane] = make_float2(rs, -mr * rs);
        }
      } else {
        mbar_wait(bars + HB_STGF, (n & 1) ^ 1);
        if (type == IT_WS) h_vecmat<true>(sb, idx, st, ph, tid, cvec, g_w13s, g_uv, g_mod, g_gate);
        else h_vecmat<false>(sb, idx, st, ph, tid, cvec, g_w13s, g_uv, g_mod, g_gate);
      }
      HT(3);
      if (n & 1) bar_arrive<3, 288>(); else bar_arrive<2, 288>();
    }
  }
}

const uint32_t h_items[] = {
  0x1, 0x81, 0x101, 0x181, 0x201, 0x281, 0x301, 0x381, 0x401, 0x481, 0x501, 0x581, 0x601, 0x681,
  0x701, 0x781, 0x801, 0x881, 0x901, 0x981, 0xa01, 0xa81, 0xb01, 0xb81, 0xc01, 0xc81, 0xd01, 0xd81,
  0xe01, 0xe81, 0xf01, 0xf81, 0x2, 0x82, 0xa, 0x8a, 0x12, 0x92, 0x1a, 0x9a, 0x22, 0xa2,
  0x2a, 0xaa, 0x32, 0xb2, 0x3a, 0xba, 0x4, 0x84, 0x104, 0x184, 0x42, 0xc2, 0x4a, 0xca,
  0x52, 0xd2, 0x5a, 0xda, 0x62, 0xe2, 0x6a, 0xea, 0x72, 0xf2, 0x7a, 0xfa, 0x204, 0x284,
  0x304, 0x384, 0x404, 0x484, 0x504, 0x584, 0x604, 0x684, 0x704, 0x784, 0x804, 0x884, 0x904, 0x984,
  0xa04, 0xa84, 0xb04, 0xb84, 0xc04, 0xc84, 0xd04, 0xd84, 0x1000003, 0x1000083, 0x1000103, 0x1000183, 0x1040003, 0x1040083,
  0x1040103, 0x1040183, 0x1080003, 0x1080083, 0x1080103, 0x1080183, 0x10c0003, 0x10c0083, 0x10c0103, 0x10c0183, 0x1100003, 0x1100083, 0x1100103, 0x1100183,
  0x1140003, 0x1140083, 0x1140103, 0x1140183, 0x1180003, 0x1180083, 0x1180103, 0x1180183, 0x11c0003, 0x11c0083, 0x11c0103, 0x11c0183, 0x400000b, 0x400008b,
  0x400010b, 0x400018b, 0x410000b, 0x410008b, 0x410010b, 0x410018b, 0x7, 0x87, 0x107, 0x187, 0x2000005, 0x2000085, 0x2000105, 0x2000185,
  0x2000205, 0x2000285, 0x2000305, 0x2000385, 0x2000405, 0x2000485, 0x2000505, 0x2000585, 0x2000605, 0x2000685, 0x2000705, 0x2000785, 0x2000805, 0x2000885,
  0x2000905, 0x2000985, 0x2000a05, 0x2000a85, 0x2000b05, 0x2000b85, 0x2000c05, 0x2000c85, 0x2000d05, 0x2000d85, 0x4000013, 0x4000093, 0x4000113, 0x4000193,
  0x4100013, 0x4100093, 0x4100113, 0x4100193, 0x3800006, 0x3800086, 0x3800106, 0x3800186, 0x38e0006, 0x38e0086, 0x38e0106, 0x38e0186, 0xf, 0x8f,
  0x10f, 0x18f, 0x200000d, 0x200008d, 0x200010d, 0x200018d, 0x200020d, 0x200028d, 0x200030d, 0x200038d, 0x200040d, 0x200048d, 0x200050d, 0x200058d,
  0x200060d, 0x200068d, 0x200070d, 0x200078d, 0x200080d, 0x200088d, 0x200090d, 0x200098d, 0x400001b, 0x400009b, 0x400011b, 0x400019b, 0x410001b, 0x410009b,
  0x410011b, 0x410019b, 0x2000a0d, 0x2000a8d, 0x2000b0d, 0x2000b8d, 0x2000c0d, 0x2000c8d, 0x2000d0d, 0x2000d8d, 0x17, 0x97, 0x117, 0x197,
  0x2000015, 0x2000095, 0x2000115, 0x2000195, 0x2000215, 0x2000295, 0x2000315, 0x2000395, 0x2000415, 0x2000495, 0x2000515, 0x2000595, 0x2000615, 0x2000695,
  0x2000715, 0x2000795, 0x2000815, 0x2000895, 0x2000915, 0x2000995, 0x4000023, 0x40000a3, 0x4000123, 0x40001a3, 0x4100023, 0x41000a3, 0x4100123, 0x41001a3,
  0x2000a15, 0x2000a95, 0x2000b15, 0x2000b95, 0x2000c15, 0x2000c95, 0x2000d15, 0x2000d95, 0x380000e, 0x380008e, 0x380010e, 0x380018e, 0x38e000e, 0x38e008e,
  0x38e010e, 0x38e018e, 0x400002b, 0x40000ab, 0x400012b, 0x40001ab, 0x410002b, 0x41000ab, 0x410012b, 0x41001ab, 0x1f, 0x9f, 0x11f, 0x19f,
  0x200001d, 0x200009d, 0x200011d, 0x200019d, 0x200021d, 0x200029d, 0x200031d, 0x200039d, 0x200041d, 0x200049d, 0x200051d, 0x200059d, 0x200061d, 0x200069d,
  0x200071d, 0x200079d, 0x200081d, 0x200089d, 0x200091d, 0x200099d, 0x2000a1d, 0x2000a9d, 0x2000b1d, 0x2000b9d, 0x2000c1d, 0x2000c9d, 0x2000d1d, 0x2000d9d,
  0x27, 0xa7, 0x127, 0x1a7, 0x4000033, 0x40000b3, 0x4000133, 0x40001b3, 0x4100033, 0x41000b3, 0x4100133, 0x41001b3, 0x2000025, 0x20000a5,
  0x2000125, 0x20001a5, 0x2000225, 0x20002a5, 0x2000325, 0x20003a5, 0x2000425, 0x20004a5, 0x2000525, 0x20005a5, 0x2000625, 0x20006a5, 0x2000725, 0x20007a5,
  0x2000825, 0x20008a5, 0x2000925, 0x20009a5, 0x2000a25, 0x2000aa5, 0x2000b25, 0x2000ba5, 0x2000c25, 0x2000ca5, 0x2000d25, 0x2000da5, 0x2f, 0xaf,
  0x12f, 0x1af, 0x400003b, 0x40000bb, 0x400013b, 0x40001bb, 0x410003b, 0x41000bb, 0x410013b, 0x41001bb, 0x200002d, 0x20000ad, 0x200012d, 0x20001ad,
  0x200022d, 0x20002ad, 0x200032d, 0x20003ad, 0x200042d, 0x20004ad, 0x200052d, 0x20005ad, 0x200062d, 0x20006ad, 0x200072d, 0x20007ad, 0x200082d, 0x20008ad,
  0x200092d, 0x20009ad, 0x2000a2d, 0x2000aad, 0x2000b2d, 0x2000bad, 0x2000c2d, 0x2000cad, 0x2000d2d, 0x2000dad, 0x37, 0xb7, 0x137, 0x1b7,
  0x4000043, 0x40000c3, 0x4000143, 0x40001c3, 0x2000035, 0x20000b5, 0x2000135, 0x20001b5, 0x2000235, 0x20002b5, 0x2000335, 0x20003b5, 0x4100043, 0x41000c3,
  0x4100143, 0x41001c3, 0x2000435, 0x20004b5, 0x2000535, 0x20005b5, 0x2000635, 0x20006b5, 0x2000735, 0x20007b5, 0x2000835, 0x20008b5, 0x2000935, 0x20009b5,
  0x2000a35, 0x2000ab5, 0x2000b35, 0x2000bb5, 0x2000c35, 0x2000cb5, 0x2000d35, 0x2000db5, 0x3800016, 0x3800096, 0x3800116, 0x3800196, 0x38e0016, 0x38e0096,
  0x38e0116, 0x38e0196, 0x3f, 0xbf, 0x13f, 0x1bf, 0x200003d, 0x20000bd, 0x200013d, 0x20001bd, 0x200023d, 0x20002bd, 0x200033d, 0x20003bd,
  0x200043d, 0x20004bd, 0x200053d, 0x20005bd, 0x400004b, 0x40000cb, 0x400014b, 0x40001cb, 0x410004b, 0x41000cb, 0x410014b, 0x41001cb, 0x200063d, 0x20006bd,
  0x200073d, 0x20007bd, 0x200083d, 0x20008bd, 0x200093d, 0x20009bd, 0x47, 0xc7, 0x147, 0x1c7, 0x2000a3d, 0x2000abd, 0x2000b3d, 0x2000bbd,
  0x2000c3d, 0x2000cbd, 0x2000d3d, 0x2000dbd, 0x2000045, 0x20000c5, 0x2000145, 0x20001c5, 0x2000245, 0x20002c5, 0x2000345, 0x20003c5, 0x2000445, 0x20004c5,
  0x2000545, 0x20005c5, 0x4000053, 0x40000d3, 0x4000153, 0x40001d3, 0x4100053, 0x41000d3, 0x4100153, 0x41001d3, 0x2000645, 0x20006c5, 0x2000745, 0x20007c5,
  0x2000845, 0x20008c5, 0x2000945, 0x20009c5, 0x2000a45, 0x2000ac5, 0x2000b45, 0x2000bc5, 0x2000c45, 0x2000cc5, 0x2000d45, 0x2000dc5, 0x380001e, 0x380009e,
  0x380011e, 0x380019e, 0x38e001e, 0x38e009e, 0x38e011e, 0x38e019e, 0x3800026, 0x38000a6, 0x3800126, 0x38001a6, 0x4f, 0xcf, 0x14f, 0x1cf,
  0x400005b, 0x40000db, 0x400015b, 0x40001db, 0x410005b, 0x41000db, 0x410015b, 0x41001db, 0x200004d, 0x20000cd, 0x200014d, 0x20001cd, 0x200024d, 0x20002cd,
  0x200034d, 0x20003cd, 0x200044d, 0x20004cd, 0x200054d, 0x20005cd, 0x200064d, 0x20006cd, 0x200074d, 0x20007cd, 0x57, 0xd7, 0x157, 0x1d7,
  0x200084d, 0x20008cd, 0x200094d, 0x20009cd, 0x2000a4d, 0x2000acd, 0x2000b4d, 0x2000bcd, 0x4000063, 0x40000e3, 0x4000163, 0x40001e3, 0x4100063, 0x41000e3,
  0x4100163, 0x41001e3, 0x2000c4d, 0x2000ccd, 0x2000d4d, 0x2000dcd, 0x2000055, 0x20000d5, 0x2000155, 0x20001d5, 0x2000255, 0x20002d5, 0x2000355, 0x20003d5,
  0x2000455, 0x20004d5, 0x2000555, 0x20005d5, 0x2000655, 0x20006d5, 0x2000755, 0x20007d5, 0x2000855, 0x20008d5, 0x2000955, 0x20009d5, 0x2000a55, 0x2000ad5,
  0x2000b55, 0x2000bd5, 0x2000c55, 0x2000cd5, 0x2000d55, 0x2000dd5, 0x5f, 0xdf, 0x15f, 0x1df, 0x200006b, 0x20000eb, 0x200016b, 0x20001eb,
  0x208006b, 0x20800eb, 0x208016b, 0x20801eb, 0x210006b, 0x21000eb, 0x210016b, 0x21001eb, 0x218006b, 0x21800eb, 0x218016b, 0x21801eb, 0x200005d, 0x20000dd,
  0x200015d, 0x20001dd, 0x200025d, 0x20002dd, 0x200035d, 0x20003dd, 0x200045d, 0x20004dd, 0x200055d, 0x20005dd, 0x200065d, 0x20006dd, 0x200075d, 0x20007dd,
  0x200085d, 0x20008dd, 0x200095d, 0x20009dd, 0x67, 0xe7, 0x167, 0x1e7, 0x2000073, 0x20000f3, 0x2000173, 0x20001f3, 0x2080073, 0x20800f3,
  0x2080173, 0x20801f3, 0x2100073, 0x21000f3, 0x2100173, 0x21001f3, 0x2180073, 0x21800f3, 0x2180173, 0x21801f3, 0x2000a5d, 0x2000add, 0x2000b5d, 0x2000bdd,
  0x2000c5d, 0x2000cdd, 0x2000d5d, 0x2000ddd, 0x2000065, 0x20000e5, 0x2000165, 0x20001e5, 0x2000265, 0x20002e5, 0x2000365, 0x20003e5, 0x6f, 0xef,
  0x16f, 0x1ef, 0x2000465, 0x20004e5, 0x2000565, 0x20005e5, 0x2000665, 0x20006e5, 0x2000765, 0x20007e5, 0x2000865, 0x20008e5, 0x2000965, 0x20009e5,
  0x2000a65, 0x2000ae5, 0x2000b65, 0x2000be5, 0x100207b, 0x10020fb, 0x100217b, 0x10021fb, 0x100227b, 0x10022fb, 0x100237b, 0x10023fb, 0x104207b, 0x10420fb,
  0x104217b, 0x10421fb, 0x104227b, 0x10422fb, 0x104237b, 0x10423fb, 0x108207b, 0x10820fb, 0x108217b, 0x10821fb, 0x108227b, 0x10822fb, 0x108237b, 0x10823fb,
  0x10c207b, 0x10c20fb, 0x10c217b, 0x10c21fb, 0x10c227b, 0x10c22fb, 0x10c237b, 0x10c23fb, 0x110207b, 0x11020fb, 0x110217b, 0x11021fb, 0x110227b, 0x11022fb,
  0x110237b, 0x11023fb, 0x114207b, 0x11420fb, 0x114217b, 0x11421fb, 0x114227b, 0x11422fb, 0x114237b, 0x11423fb, 0x118207b, 0x11820fb, 0x118217b, 0x11821fb,
  0x77, 0xf7, 0x177, 0x1f7, 0x118227b, 0x11822fb, 0x118237b, 0x11823fb, 0x11c207b, 0x11c20fb, 0x11c217b, 0x11c21fb, 0x11c227b, 0x11c22fb,
  0x11c237b, 0x11c23fb, 0x2000c65, 0x2000ce5, 0x2000d65, 0x2000de5, 0x200006d, 0x20000ed, 0x200016d, 0x20001ed, 0x200026d, 0x20002ed, 0x200036d, 0x20003ed,
  0x200046d, 0x20004ed, 0x200056d, 0x20005ed, 0x200066d, 0x20006ed, 0x200076d, 0x20007ed, 0x200086d, 0x20008ed, 0x200096d, 0x20009ed, 0x2000a6d, 0x2000aed,
  0x2000b6d, 0x2000bed, 0x2000c6d, 0x2000ced, 0x2000d6d, 0x2000ded, 0x1ce0026, 0x1ce00a6, 0x1ce0126, 0x1ce01a6, 0x1d50026, 0x1d500a6, 0x1d50126, 0x1d501a6,
  0x2000075, 0x20000f5, 0x2000175, 0x20001f5, 0x1c0002e, 0x1c000ae, 0x1c0012e, 0x1c001ae, 0x2000275, 0x20002f5, 0x2000375, 0x20003f5, 0x1c7002e, 0x1c700ae,
  0x2000475, 0x20004f5, 0x2000575, 0x20005f5, 0x2000675, 0x20006f5, 0x2000775, 0x20007f5, 0x2000875, 0x20008f5, 0x2000975, 0x20009f5, 0x2000a75, 0x2000af5,
  0x2000b75, 0x2000bf5, 0x2000c75, 0x2000cf5, 0x2000d75, 0x2000df5, 0x1c7012e, 0x1c701ae, 0x1ce002e, 0x1ce00ae, 0x1ce012e, 0x1ce01ae, 0x1d5002e, 0x1d500ae,
  0x1d5012e, 0x1d501ae, 0x1c00036, 0x1c000b6, 0x1c00136, 0x1c001b6, 0x1c70036, 0x1c700b6, 0x1c70136, 0x1c701b6, 0x1ce0036, 0x1ce00b6, 0x1ce0136, 0x1ce01b6,
  0x1d50036, 0x1d500b6, 0x1d50136, 0x1d501b6, 0x1c0003e, 0x1c000be, 0x1c0013e, 0x1c001be, 0x1c7003e, 0x1c700be, 0x1c7013e, 0x1c701be, 0x1ce003e, 0x1ce00be,
  0x1ce013e, 0x1ce01be, 0x1d5003e, 0x1d500be, 0x1d5013e, 0x1d501be, 0x1c00046, 0x1c000c6, 0x1c00146, 0x1c001c6, 0x7f, 0xff, 0x17f, 0x1ff,
  0x200207d, 0x20020fd, 0x200217d, 0x20021fd, 0x200227d, 0x20022fd, 0x200237d, 0x20023fd, 0x200247d, 0x20024fd, 0x200257d, 0x20025fd, 0x200267d, 0x20026fd,
  0x200277d, 0x20027fd, 0x200287d, 0x20028fd, 0x200297d, 0x20029fd, 0x2002a7d, 0x2002afd, 0x2002b7d, 0x2002bfd, 0x2002c7d, 0x2002cfd, 0x2002d7d, 0x2002dfd,
  0x2002e7d, 0x2002efd, 0x2002f7d, 0x2002ffd, 0x200307d, 0x20030fd, 0x200317d, 0x20031fd, 0x200327d, 0x20032fd, 0x200337d, 0x20033fd, 0x200347d, 0x20034fd,
  0x200357d, 0x20035fd, 0x200367d, 0x20036fd, 0x200377d, 0x20037fd, 0x200387d, 0x20038fd, 0x200397d, 0x20039fd, 0x2003a7d, 0x2003afd, 0x2003b7d, 0x2003bfd,
  0x1c70046, 0x1c700c6, 0x1c70146, 0x1c701c6, 0x1ce0046, 0x1ce00c6, 0x1ce0146, 0x1ce01c6, 0x1d50046, 0x1d500c6, 0x1d50146, 0x1d501c6, 0x1c0004e, 0x1c000ce,
  0x1c0014e, 0x1c001ce, 0x1c7004e, 0x1c700ce, 0x1c7014e, 0x1c701ce, 0x1ce004e, 0x1ce00ce, 0x1ce014e, 0x1ce01ce, 0x1d5004e, 0x1d500ce, 0x1d5014e, 0x1d501ce,
  0x1c00056, 0x1c000d6, 0x1c00156, 0x1c001d6, 0x1c70056, 0x1c700d6, 0x1c70156, 0x1c701d6, 0x1ce0056, 0x1ce00d6, 0x1ce0156, 0x1ce01d6, 0x1d50056, 0x1d500d6,
  0x1d50156, 0x1d501d6, 0x1c0005e, 0x1c000de, 0x1c0015e, 0x1c001de, 0x1c7005e, 0x1c700de, 0x1c7015e, 0x1c701de, 0x1ce005e, 0x1ce00de, 0x1ce015e, 0x1ce01de,
  0x1d5005e, 0x1d500de, 0x1d5015e, 0x1d501de, 0x1c00066, 0x1c000e6, 0x1c00166, 0x1c001e6, 0x1c70066, 0x1c700e6, 0x1c70166, 0x1c701e6, 0x1ce0066, 0x1ce00e6,
  0x1ce0166, 0x1ce01e6, 0x1d50066, 0x1d500e6, 0x1d50166, 0x1d501e6, 0x1c0006e, 0x1c000ee, 0x1c0016e, 0x1c001ee, 0x1c7006e, 0x1c700ee, 0x1c7016e, 0x1c701ee,
  0x1ce006e, 0x1ce00ee, 0x1ce016e, 0x1ce01ee, 0x1d5006e, 0x1d500ee, 0x1d5016e, 0x1d501ee, 0x1c00076, 0x1c000f6, 0x1c00176, 0x1c001f6, 0x1c70076, 0x1c700f6,
  0x1c70176, 0x1c701f6, 0x1ce0076, 0x1ce00f6, 0x1ce0176, 0x1ce01f6, 0x1d50076, 0x1d500f6, 0x1d50176, 0x1d501f6, 0xe0207e, 0xe020fe, 0xe0217e, 0xe021fe,
  0xe0227e, 0xe022fe, 0xe0237e, 0xe023fe, 0xe3a07e, 0xe3a0fe, 0xe3a17e, 0xe3a1fe, 0xe3a27e, 0xe3a2fe, 0xe3a37e, 0xe3a3fe, 0xe7207e, 0xe720fe,
  0xe7217e, 0xe721fe, 0xe7227e, 0xe722fe, 0xe7237e, 0xe723fe, 0xeaa07e, 0xeaa0fe, 0xeaa17e, 0xeaa1fe, 0xeaa27e, 0xeaa2fe, 0xeaa37e, 0xeaa3fe,
  0xee207e, 0xee20fe, 0xee217e, 0xee21fe, 0xee227e, 0xee22fe, 0xee237e, 0xee23fe, 0xf1a07e, 0xf1a0fe, 0xf1a17e, 0xf1a1fe, 0xf1a27e, 0xf1a2fe,
  0xf1a37e, 0xf1a3fe, 0xf5207e, 0xf520fe, 0xf5217e, 0xf521fe, 0xf5227e, 0xf522fe, 0xf5237e, 0xf523fe, 0xf8a07e, 0xf8a0fe, 0xf8a17e, 0xf8a1fe,
  0xf8a27e, 0xf8a2fe, 0xf8a37e, 0xf8a3fe,
};

void build_list(HList& l) {
  int n = 0;
  n = sizeof(h_items) / sizeof(h_items[0]);
  for (int i = 0; i < n; i++) l.it[i] = h_items[i];
  l.n = n;
}

typedef CUresult (*EncodeFn)(CUtensorMap*, CUtensorMapDataType, cuuint32_t, void*, const cuuint64_t*, const cuuint64_t*,
                             const cuuint32_t*, const cuuint32_t*, CUtensorMapInterleave, CUtensorMapSwizzle,
                             CUtensorMapL2promotion, CUtensorMapFloatOOBfill);

void make_map(EncodeFn fn, CUtensorMap* m, const void* p, uint64_t cols, uint64_t rows, uint32_t bc, uint32_t br, CUtensorMapSwizzle sw) {
  cuuint64_t dims[2] = {cols, rows};
  cuuint64_t strides[1] = {cols * 2};
  cuuint32_t box[2] = {bc, br};
  cuuint32_t es[2] = {1, 1};
  fn(m, CU_TENSOR_MAP_DATA_TYPE_BFLOAT16, 2, const_cast<void*>(p), dims, strides, box, es, CU_TENSOR_MAP_INTERLEAVE_NONE, sw,
     CU_TENSOR_MAP_L2_PROMOTION_L2_128B, CU_TENSOR_MAP_FLOAT_OOB_FILL_NONE);
}

}

extern "C" void kernel_launch(void* const* d_in, const int* in_sizes, int n_in, void* d_out, int out_size) {
  const __nv_bfloat16* x = (const __nv_bfloat16*)d_in[0];
  const __nv_bfloat16* mem0 = (const __nv_bfloat16*)d_in[1];
  const __nv_bfloat16* cvec = (const __nv_bfloat16*)d_in[11];
  static EncodeFn enc = nullptr;
  if (!enc) {
    cudaDriverEntryPointQueryResult qr;
    void* fp = nullptr;
    cudaGetDriverEntryPoint("cuTensorMapEncodeTiled", &fp, cudaEnableDefault, &qr);
    enc = (EncodeFn)fp;
    cudaFuncSetAttribute(kernel_R, cudaFuncAttributeMaxDynamicSharedMemorySize, R_SMEM);
    cudaFuncSetAttribute(kernel_H, cudaFuncAttributeMaxDynamicSharedMemorySize, H_SMEM);
  }
  CUtensorMap tmq, tmk, tmv, tmo, tmm;
  make_map(enc, &tmm, d_in[12], 6144, 1024, 64, 64, CU_TENSOR_MAP_SWIZZLE_NONE);
  make_map(enc, &tmq, d_in[2], 4096, 1024, 64, 64, CU_TENSOR_MAP_SWIZZLE_128B);
  make_map(enc, &tmk, d_in[3], 4096, 1024, 64, 64, CU_TENSOR_MAP_SWIZZLE_128B);
  make_map(enc, &tmv, d_in[4], 4096, 1024, 64, 64, CU_TENSOR_MAP_SWIZZLE_128B);
  make_map(enc, &tmo, d_in[5], 1024, 4096, 16, 128, CU_TENSOR_MAP_SWIZZLE_32B);
  RDesc dsc;
  for (int k = 0; k < 32; k++) {
    dsc.tok[k] = mkdesc(0x400 + (k < 16 ? R_GA : R_GB) + ((k & 15) >> 2) * 4096 + (k & 3) * 256, 128, 1024, 0);
    dsc.tail_a[k] = mkdesc(0x400 + R_TAIL + k * 2048, 1024, 1024, 1);
    if (k < 16) dsc.tail_b[k] = mkdesc(0x400 + R_GA + k * 256, 128, 4096, 0);
  }
  kernel_R<<<96, 256, R_SMEM, cudaStreamPerThread>>>(tmq, tmk, tmv, tmo, tmm, x, mem0, cvec, dsc);

  CUtensorMap ho, h1, h3, h2, hm, hx;
  make_map(enc, &ho, d_in[5], 1024, 4096, 64, 64, CU_TENSOR_MAP_SWIZZLE_128B);
  make_map(enc, &h1, d_in[8], F_, 1024, 64, 64, CU_TENSOR_MAP_SWIZZLE_128B);
  make_map(enc, &h3, d_in[9], F_, 1024, 64, 64, CU_TENSOR_MAP_SWIZZLE_128B);
  make_map(enc, &h2, d_in[10], 1024, F_, 64, 64, CU_TENSOR_MAP_SWIZZLE_128B);
  make_map(enc, &hm, d_in[12], 6144, 1024, 64, 64, CU_TENSOR_MAP_SWIZZLE_128B);
  make_map(enc, &hx, d_out, 1024, S_, 64, 128, CU_TENSOR_MAP_SWIZZLE_128B);
  HList list;
  build_list(list);
  cudaLaunchConfig_t cfg = {};
  cfg.gridDim = dim3(132); cfg.blockDim = dim3(384); cfg.dynamicSmemBytes = H_SMEM; cfg.stream = cudaStreamPerThread;
  cudaLaunchAttribute at[1];
  at[0].id = cudaLaunchAttributeProgrammaticStreamSerialization;
  at[0].val.programmaticStreamSerializationAllowed = 1;
  cfg.attrs = at;
  cfg.numAttrs = 1;
  cudaLaunchKernelEx(&cfg, kernel_H, ho, h1, h3, h2, hm, hx, x, cvec, (__nv_bfloat16*)d_out, list);
}
```

```cpp
#include <cuda_runtime.h>
#include <cuda_bf16.h>
#include <cuda.h>
#include <stdint.h>
#include <type_traits>

namespace {

constexpr int S_ = 2048, D_ = 1024, NSEG = 64, F_ = 3584;

__device__ __align__(1024) uint8_t g_h[S_ * D_ * 2];
__device__ __align__(1024) uint8_t g_att[S_ * 4096 * 2];
__device__ __align__(1024) uint8_t g_act[S_ * F_ * 2];
__device__ __align__(1024) uint8_t g_w13s[28 * 16 * 32768];
__device__ __align__(1024) uint8_t g_ext[16 * 2560];
__device__ __align__(1024) uint8_t g_bext[28 * 4096];
__device__ __align__(1024) __nv_bfloat16 g_gate[2 * D_];
__device__ __align__(1024) float g_slot[4 * 3 * 8 * 4 * 32 * 4];
__device__ __align__(128) __nv_bfloat16 g_mod[6 * D_];
__device__ __align__(128) float g_modp[3 * 2 * D_];
__device__ __align__(128) uint32_t g_flags[1024];
constexpr int FL_S1 = 0, FL_S2 = 32, FL_MOD = 64, FL_HEAD = 96, FL_EXIT = 128, FL_WS = 160, FL_GO = 192, FL_ATT = 256, FL_XT = 384, FL_OUT = 512, FL_F1 = 640, FL_STAT = 768;

__device__ __forceinline__ uint32_t smem_u32(const void* p) { return (uint32_t)__cvta_generic_to_shared(p); }
__device__ __forceinline__ uint32_t mapa(uint32_t a, uint32_t r) { uint32_t o; asm("mapa.shared::cluster.u32 %0, %1, %2;" : "=r"(o) : "r"(a), "r"(r)); return o; }
__device__ __forceinline__ uint32_t pack2(float a, float b) { uint32_t r; asm("cvt.rn.bf16x2.f32 %0, %1, %2;" : "=r"(r) : "f"(b), "f"(a)); return r; }
__device__ __forceinline__ float bf_lo(uint32_t w) { return __uint_as_float(w << 16); }
__device__ __forceinline__ float bf_hi(uint32_t w) { return __uint_as_float(w & 0xffff0000u); }
__device__ __forceinline__ float ex2(float x) { float y; asm("ex2.approx.ftz.f32 %0, %1;" : "=f"(y) : "f"(x)); return y; }
__device__ __forceinline__ float rcp(float x) { float y; asm("rcp.approx.ftz.f32 %0, %1;" : "=f"(y) : "f"(x)); return y; }
__device__ __forceinline__ uint32_t clk32() { uint64_t c; asm volatile("mov.u64 %0, %%clock64;" : "=l"(c) :: "memory"); return (uint32_t)c; }

__device__ __forceinline__ void mbar_init(uint32_t b, uint32_t n) { asm volatile("mbarrier.init.shared::cta.b64 [%0], %1;" :: "r"(b), "r"(n) : "memory"); }
__device__ __forceinline__ void mbar_arrive(uint32_t b) { asm volatile("mbarrier.arrive.shared::cta.b64 _, [%0];" :: "r"(b) : "memory"); }
__device__ __forceinline__ void mbar_expect(uint32_t b, uint32_t n) { asm volatile("mbarrier.arrive.expect_tx.shared::cta.b64 _, [%0], %1;" :: "r"(b), "r"(n) : "memory"); }
__device__ __forceinline__ uint32_t mbar_try(uint32_t b, uint32_t par) {
  uint32_t ok;
  asm volatile("{\n.reg .pred p;\nmbarrier.try_wait.parity.shared::cta.b64 p, [%1], %2;\nselp.u32 %0, 1, 0, p;\n}" : "=r"(ok) : "r"(b), "r"(par) : "memory");
  return ok;
}
__device__ __forceinline__ void mbar_wait(uint32_t b, uint32_t par) {
  asm volatile("{\n.reg .pred p;\n"
               "LOOP:\n"
               "mbarrier.try_wait.parity.shared::cta.b64 p, [%0], %1;\n"
               "@!p bra.uni LOOP;\n}" :: "r"(b), "r"(par) : "memory");
}
__device__ __forceinline__ void mbar_wait_safe(uint32_t b, uint32_t par) {
  uint32_t c = 0;
  while (!mbar_try(b, par)) { if (++c > 4000000u) __trap(); }
}
__device__ __forceinline__ bool elect_one() {
  uint32_t p;
  asm volatile("{\n.reg .pred p;\nelect.sync _|p, 0xffffffff;\nselp.u32 %0, 1, 0, p;\n}" : "=r"(p));
  return p;
}
__device__ __forceinline__ void sched_fence(uint32_t x, uint32_t y) { asm volatile("{\n.reg .pred p;\nsetp.eq.u32 p, %0, %1;\n@p trap;\n}" :: "r"(x), "r"(y) : "memory"); }
template <class T> __device__ __forceinline__ T opaque32(T x) { asm volatile("" : "+r"(x)); return x; }
template <class T> __device__ __forceinline__ T opaque64(T x) { asm volatile("" : "+l"(x)); return x; }
template <int ID, int N> __device__ __forceinline__ void bar_sync() { asm volatile("bar.sync %0, %1;" :: "n"(ID), "n"(N) : "memory"); }
template <int ID, int N> __device__ __forceinline__ void bar_arrive() { asm volatile("bar.arrive %0, %1;" :: "n"(ID), "n"(N) : "memory"); }
__device__ __forceinline__ void fence_async_smem() { asm volatile("fence.proxy.async.shared::cta;" ::: "memory"); }
__device__ __forceinline__ void fence_async_all() { asm volatile("fence.proxy.async;" ::: "memory"); }
__device__ __forceinline__ void fence_gpu() { asm volatile("fence.acq_rel.gpu;" ::: "memory"); }
__device__ __forceinline__ void red_add_u32(uint32_t* p, uint32_t v) { asm volatile("red.relaxed.gpu.global.add.u32 [%0], %1;" :: "l"(p), "r"(v) : "memory"); }
__device__ __forceinline__ uint32_t ld_acquire(const uint32_t* p) { uint32_t v; asm volatile("ld.acquire.gpu.global.u32 %0, [%1];" : "=r"(v) : "l"(p) : "memory"); return v; }
__device__ __forceinline__ void wait_flag(const uint32_t* p, uint32_t target) {
  uint32_t c = 0;
  while (ld_acquire(p) < target) { if (++c > 20000000u) __trap(); __nanosleep(20); }
}

__device__ __forceinline__ void tma2d(uint32_t dst, const CUtensorMap* m, int c0, int c1, uint32_t bar) {
  asm volatile("cp.async.bulk.tensor.2d.shared::cluster.global.mbarrier::complete_tx::bytes [%0], [%1, {%3, %4}], [%2];"
               :: "r"(dst), "l"(m), "r"(bar), "r"(c0), "r"(c1) : "memory");
}
constexpr uint64_t L2_NORMAL = 0x1000000000000000ull, L2_FIRST = 0x12F0000000000000ull;
__device__ __forceinline__ void tma2d_p(uint32_t dst, const CUtensorMap* m, int c0, int c1, uint32_t bar, uint64_t pol) {
  asm volatile("cp.async.bulk.tensor.2d.shared::cluster.global.mbarrier::complete_tx::bytes.L2::cache_hint [%0], [%1, {%3, %4}], [%2], %5;"
               :: "r"(dst), "l"(m), "r"(bar), "r"(c0), "r"(c1), "l"(pol) : "memory");
}
__device__ __forceinline__ void bulk_g2s_p(uint32_t dst, const void* src, uint32_t bytes, uint32_t bar, uint64_t pol) {
  asm volatile("cp.async.bulk.shared::cluster.global.mbarrier::complete_tx::bytes.L2::cache_hint [%0], [%1], %2, [%3], %4;"
               :: "r"(dst), "l"(src), "r"(bytes), "r"(bar), "l"(pol) : "memory");
}
#define POL_RW L2_FIRST
__device__ __forceinline__ void tma2d_prefetch_p(const CUtensorMap* m, int c0, int c1, uint64_t pol) {
  asm volatile("cp.async.bulk.prefetch.tensor.2d.L2.global.L2::cache_hint [%0, {%1, %2}], %3;" :: "l"(m), "r"(c0), "r"(c1), "l"(pol) : "memory");
}
__device__ __forceinline__ void tma2d_prefetch(const CUtensorMap* m, int c0, int c1) {
  asm volatile("cp.async.bulk.prefetch.tensor.2d.L2.global [%0, {%1, %2}];" :: "l"(m), "r"(c0), "r"(c1) : "memory");
}
__device__ __forceinline__ void bulk_g2s(uint32_t dst, const void* src, uint32_t bytes, uint32_t bar) {
  asm volatile("cp.async.bulk.shared::cluster.global.mbarrier::complete_tx::bytes [%0], [%1], %2, [%3];"
               :: "r"(dst), "l"(src), "r"(bytes), "r"(bar) : "memory");
}
__device__ __forceinline__ void bulk_s2s(uint32_t dst, uint32_t src, uint32_t bytes, uint32_t bar) {
  asm volatile("cp.async.bulk.shared::cluster.shared::cta.mbarrier::complete_tx::bytes [%0], [%1], %2, [%3];"
               :: "r"(dst), "r"(src), "r"(bytes), "r"(bar) : "memory");
}
__device__ __forceinline__ void st_async1(uint32_t dst, uint32_t a, uint32_t bar) {
  asm volatile("st.async.shared::cluster.mbarrier::complete_tx::bytes.b32 [%0], %1, [%2];" :: "r"(dst), "r"(a), "r"(bar) : "memory");
}
__device__ __forceinline__ void st_async2(uint32_t dst, uint32_t a, uint32_t b, uint32_t bar) {
  asm volatile("st.async.shared::cluster.mbarrier::complete_tx::bytes.v2.b32 [%0], {%1, %2}, [%3];" :: "r"(dst), "r"(a), "r"(b), "r"(bar) : "memory");
}
__device__ __forceinline__ void st_async4(uint32_t dst, const uint32_t* r, uint32_t bar) {
  asm volatile("st.async.shared::cluster.mbarrier::complete_tx::bytes.v4.b32 [%0], {%1, %2, %3, %4}, [%5];"
               :: "r"(dst), "r"(r[0]), "r"(r[1]), "r"(r[2]), "r"(r[3]), "r"(bar) : "memory");
}
__device__ __forceinline__ void sts32(uint32_t a, uint32_t v) { asm volatile("st.shared.b32 [%0], %1;" :: "r"(a), "r"(v) : "memory"); }
__device__ __forceinline__ void sts64(uint32_t a, uint32_t x, uint32_t y) { asm volatile("st.shared.v2.b32 [%0], {%1, %2};" :: "r"(a), "r"(x), "r"(y) : "memory"); }
__device__ __forceinline__ void sts128(uint32_t a, uint32_t x, uint32_t y, uint32_t z, uint32_t w) {
  asm volatile("st.shared.v4.b32 [%0], {%1, %2, %3, %4};" :: "r"(a), "r"(x), "r"(y), "r"(z), "r"(w) : "memory");
}
__device__ __forceinline__ void lds128(uint32_t* r, uint32_t a) {
  asm volatile("ld.shared.v4.b32 {%0, %1, %2, %3}, [%4];" : "=r"(r[0]), "=r"(r[1]), "=r"(r[2]), "=r"(r[3]) : "r"(a) : "memory");
}
__device__ __forceinline__ uint32_t lds32(uint32_t a) { uint32_t r; asm volatile("ld.shared.b32 %0, [%1];" : "=r"(r) : "r"(a) : "memory"); return r; }
__device__ __forceinline__ void lds64(uint32_t* r, uint32_t a) {
  asm volatile("ld.shared.v2.b32 {%0, %1}, [%2];" : "=r"(r[0]), "=r"(r[1]) : "r"(a) : "memory");
}
__device__ __forceinline__ void lds128f(float* r, uint32_t a) {
  asm volatile("ld.shared.v4.f32 {%0, %1, %2, %3}, [%4];" : "=f"(r[0]), "=f"(r[1]), "=f"(r[2]), "=f"(r[3]) : "r"(a) : "memory");
}
__device__ __forceinline__ void lds64f(float* r, uint32_t a) {
  asm volatile("ld.shared.v2.f32 {%0, %1}, [%2];" : "=f"(r[0]), "=f"(r[1]) : "r"(a) : "memory");
}
__device__ __forceinline__ void ldsm4(uint32_t* r, uint32_t a) {
  asm volatile("ldmatrix.sync.aligned.m8n8.x4.shared.b16 {%0, %1, %2, %3}, [%4];" : "=r"(r[0]), "=r"(r[1]), "=r"(r[2]), "=r"(r[3]) : "r"(a) : "memory");
}
__device__ __forceinline__ void ldsm4t(uint32_t* r, uint32_t a) {
  asm volatile("ldmatrix.sync.aligned.m8n8.x4.trans.shared.b16 {%0, %1, %2, %3}, [%4];" : "=r"(r[0]), "=r"(r[1]), "=r"(r[2]), "=r"(r[3]) : "r"(a) : "memory");
}
__device__ __forceinline__ void ldsm2(uint32_t* r, uint32_t a) {
  asm volatile("ldmatrix.sync.aligned.m8n8.x2.shared.b16 {%0, %1}, [%2];" : "=r"(r[0]), "=r"(r[1]) : "r"(a) : "memory");
}
__device__ __forceinline__ void stsm4(uint32_t a, const uint32_t* r) {
  asm volatile("stmatrix.sync.aligned.m8n8.x4.shared.b16 [%0], {%1, %2, %3, %4};" :: "r"(a), "r"(r[0]), "r"(r[1]), "r"(r[2]), "r"(r[3]) : "memory");
}
__device__ __forceinline__ uint32_t hadd2(uint32_t a, uint32_t b) { uint32_t t; asm("add.rn.bf16x2 %0, %1, %2;" : "=r"(t) : "r"(a), "r"(b)); return t; }
__device__ __forceinline__ uint32_t hmax2(uint32_t a, uint32_t b) { uint32_t t; asm("max.bf16x2 %0, %1, %2;" : "=r"(t) : "r"(a), "r"(b)); return t; }
__device__ __forceinline__ void ldsm2t(uint32_t* r, uint32_t a) {
  asm volatile("ldmatrix.sync.aligned.m8n8.x2.trans.shared.b16 {%0, %1}, [%2];" : "=r"(r[0]), "=r"(r[1]) : "r"(a) : "memory");
}
__device__ __forceinline__ uint32_t movm(uint32_t x) { uint32_t y; asm volatile("movmatrix.sync.aligned.m8n8.trans.b16 %0, %1;" : "=r"(y) : "r"(x)); return y; }
__device__ __forceinline__ void hmma(float* d, uint32_t a0, uint32_t a1, uint32_t a2, uint32_t a3, uint32_t b0, uint32_t b1) {
  asm volatile("mma.sync.aligned.m16n8k16.row.col.f32.bf16.bf16.f32 {%0,%1,%2,%3}, {%4,%5,%6,%7}, {%8,%9}, {%0,%1,%2,%3};"
               : "+f"(d[0]), "+f"(d[1]), "+f"(d[2]), "+f"(d[3]) : "r"(a0), "r"(a1), "r"(a2), "r"(a3), "r"(b0), "r"(b1));
}
__device__ __forceinline__ void hmma0(float* d, uint32_t a0, uint32_t a1, uint32_t a2, uint32_t a3, uint32_t b0, uint32_t b1) {
  asm volatile("mma.sync.aligned.m16n8k16.row.col.f32.bf16.bf16.f32 {%0,%1,%2,%3}, {%4,%5,%6,%7}, {%8,%9}, {%10,%10,%10,%10};"
               : "=f"(d[0]), "=f"(d[1]), "=f"(d[2]), "=f"(d[3]) : "r"(a0), "r"(a1), "r"(a2), "r"(a3), "r"(b0), "r"(b1), "f"(0.f));
}
__device__ __forceinline__ void hmma_k8(float* d, uint32_t a0, uint32_t a1, uint32_t b0) {
  asm volatile("mma.sync.aligned.m16n8k8.row.col.f32.bf16.bf16.f32 {%0,%1,%2,%3}, {%4,%5}, {%6}, {%0,%1,%2,%3};"
               : "+f"(d[0]), "+f"(d[1]), "+f"(d[2]), "+f"(d[3]) : "r"(a0), "r"(a1), "r"(b0));
}
__host__ __device__ constexpr uint64_t mkdesc(uint32_t addr, uint32_t lbo, uint32_t sbo, uint32_t sw) {
  return (uint64_t)((addr & 0x3FFFF) >> 4) | ((uint64_t)(lbo >> 4) << 16) | ((uint64_t)(sbo >> 4) << 32) | ((uint64_t)sw << 62);
}
#define WG_FENCE() asm volatile("wgmma.fence.sync.aligned;" ::: "memory")
#define WG_COMMIT() asm volatile("wgmma.commit_group.sync.aligned;" ::: "memory")
#define WG_WAIT(n) asm volatile("wgmma.wait_group.sync.aligned " #n ";" ::: "memory")
template <int N> __device__ __forceinline__ void reg_fence(float* d) {
#pragma unroll
  for (int i = 0; i < N; i++) asm volatile("" : "+f"(d[i]) :: "memory");
}
template <int N> __device__ __forceinline__ void zero_regs(float* d) {
#pragma unroll
  for (int i = 0; i < N; i++) asm volatile("mov.b32 %0, 0;" : "=f"(d[i]));
}
template <int SD>
__device__ __forceinline__ void wg_rs32(float* d, uint32_t a0, uint32_t a1, uint32_t a2, uint32_t a3, uint64_t b) {
  asm volatile("wgmma.mma_async.sync.aligned.m64n32k16.f32.bf16.bf16 {%0,%1,%2,%3,%4,%5,%6,%7,%8,%9,%10,%11,%12,%13,%14,%15}, {%16,%17,%18,%19}, %20, %21, 1, 1, 0;"
               : "+f"(d[0]), "+f"(d[1]), "+f"(d[2]), "+f"(d[3]), "+f"(d[4]), "+f"(d[5]), "+f"(d[6]), "+f"(d[7]),
                 "+f"(d[8]), "+f"(d[9]), "+f"(d[10]), "+f"(d[11]), "+f"(d[12]), "+f"(d[13]), "+f"(d[14]), "+f"(d[15])
               : "r"(a0), "r"(a1), "r"(a2), "r"(a3), "l"(b), "n"(SD));
}
template <int TB>
__device__ __forceinline__ void wg_ss40(float* d, uint64_t a, uint64_t b) {
  asm volatile("wgmma.mma_async.sync.aligned.m64n40k16.f32.bf16.bf16 {%0,%1,%2,%3,%4,%5,%6,%7,%8,%9,%10,%11,%12,%13,%14,%15,%16,%17,%18,%19}, %20, %21, 1, 1, 1, 1, %22;"
               : "+f"(d[0]), "+f"(d[1]), "+f"(d[2]), "+f"(d[3]), "+f"(d[4]), "+f"(d[5]), "+f"(d[6]), "+f"(d[7]),
                 "+f"(d[8]), "+f"(d[9]), "+f"(d[10]), "+f"(d[11]), "+f"(d[12]), "+f"(d[13]), "+f"(d[14]), "+f"(d[15]),
                 "+f"(d[16]), "+f"(d[17]), "+f"(d[18]), "+f"(d[19])
               : "l"(a), "l"(b), "n"(TB));
}
template <int T>
__device__ __forceinline__ void wg_ss32(float* d, uint64_t a, uint64_t b) {
  asm volatile("wgmma.mma_async.sync.aligned.m64n32k16.f32.bf16.bf16 {%0,%1,%2,%3,%4,%5,%6,%7,%8,%9,%10,%11,%12,%13,%14,%15}, %16, %17, 1, 1, 1, %18, %18;"
               : "+f"(d[0]), "+f"(d[1]), "+f"(d[2]), "+f"(d[3]), "+f"(d[4]), "+f"(d[5]), "+f"(d[6]), "+f"(d[7]),
                 "+f"(d[8]), "+f"(d[9]), "+f"(d[10]), "+f"(d[11]), "+f"(d[12]), "+f"(d[13]), "+f"(d[14]), "+f"(d[15])
               : "l"(a), "l"(b), "n"(T));
}

constexpr int R_TAIL = 0;
constexpr int R_WO = 65536;
constexpr int R_QK = R_WO + 86016;
constexpr int R_P = R_QK + 10240;
constexpr int R_GA = R_P + 6400;
constexpr int R_M2 = R_GA + 16384;
constexpr int R_M1 = R_M2 + 7168;
constexpr int R_GB = R_M1 + 9216;
constexpr int R_VT = R_GB + 16384;
constexpr int R_VM = R_VT + 8192;
constexpr int R_XS = R_VM + 2048;
constexpr int R_OX = R_XS + 1280;
constexpr int R_BAR = R_OX + 2048;
constexpr int R_TRC = R_BAR + 256;
constexpr int R_SMEM = R_TRC + 1024;
constexpr int B_MB = 0, B_XS = 32, B_VM = 40, B_VT = 48, B_TS = 56, B_FA = 64, B_FB = 72, B_TAIL = 80, B_WO = 88, B_STG = 96, B_WM = 128, B_X = 136;
constexpr int NB_A = 1, NB_B = 2, NB_X = 3, NB_C = 4, NB_D = 5, NB_E = 6, NB_F = 7, NB_G = 8, NB_H = 9, NB_S = 10, NB_E2 = 11, NB_P = 12, NB_W0 = 13;

#define POLL_DELAY 750
#define POLL_DELAY1 700
#define POLL_STAG 150
#define POLL_K0 20
#define ZS 2
#define HPF 4
#define PF1 2
#define PF2 2
#define PF3 2
#define PF4 0
#define RF_FIRST 0
#define BX_I 5
#define NCH 4
#define TOP2 0
#define CX_I 13
#define ATT_LATE 0
#define V_FENCE 1
#define SELF_STAS 1
#define Q_FENCE 1
#define ND_K 3
#define TRACE(i)
#define TS(i)

__device__ __forceinline__ int rot_chunk(int c, int rank) {
  int G = c;
  if (c < 9) { G = c + 3 * rank; if (G >= 9) G -= 9; }
  return G;
}
__device__ __forceinline__ int wo_tile(int i, int rank) {
  if (i < 12) return 12 * rank + i;
  const int r = i - 12 + 9 * rank;
  return r < 16 ? 48 + r : 20 + r;
}
__device__ __forceinline__ void load_chunk(uint32_t dst, int seg, int G, uint32_t bar) {
  mbar_expect(bar, 4096);
  bulk_g2s(dst, g_h + (size_t)(seg * 16 + G) * 4096, 4096, bar);
}
__device__ __forceinline__ void load_red(uint32_t* v, const float* p) {
#pragma unroll
  for (int j = 0; j < 2; j++)
    asm volatile("ld.relaxed.gpu.global.v4.u32 {%0, %1, %2, %3}, [%4];"
                 : "=r"(v[4 * j]), "=r"(v[4 * j + 1]), "=r"(v[4 * j + 2]), "=r"(v[4 * j + 3]) : "l"(p + j * 256) : "memory");
}
__device__ __forceinline__ bool red_done(const uint32_t* v) { return __all_sync(0xffffffffu, (v[3] & v[7]) == 0x42000000u); }
__device__ __forceinline__ uint32_t finish_red(uint32_t* v, const float* p) {
  uint32_t tries = 0;
  if (__builtin_expect(!red_done(v), 0)) {
    do { if (++tries > 20000000u) __trap(); load_red(v, p); } while (!red_done(v));
  }
  return tries;
}
__device__ __forceinline__ void exp10(float* sv, const uint32_t* x) {
  constexpr float SC = 0.08838834764831845f * 1.4426950408889634f;
  uint32_t m2 = hmax2(hmax2(hmax2(x[0], x[1]), hmax2(x[2], x[3])), x[4]);
  m2 = hmax2(m2, __shfl_xor_sync(0xffffffffu, m2, 1));
  m2 = hmax2(m2, __shfl_xor_sync(0xffffffffu, m2, 2));
  const float nm = -fmaxf(bf_lo(m2), bf_hi(m2)) * SC;
#pragma unroll
  for (int j = 0; j < 5; j++) { sv[2 * j] = ex2(fmaf(bf_lo(x[j]), SC, nm)); sv[2 * j + 1] = ex2(fmaf(bf_hi(x[j]), SC, nm)); }
}

__device__ __forceinline__ uint32_t arm_size(int w, bool isC) {
  return w == 0 ? (isC ? 1280 : 640) : w == 1 ? (isC ? 0 : 2048) : w == 2 ? (isC ? 0 : 8192) : (isC ? 0 : 1792);
}
struct RDesc { uint64_t tok[32], tail_b[16], tail_a[32]; };

template <int WG>
__device__ __forceinline__ void r_main(const uint32_t (&W)[48][4], const RDesc& dsc, int head, uint32_t rank, int lane_, int w) {
  const uint32_t sb = (rank << 24) + 0x400, bars = sb + R_BAR;
  const uint32_t to1 = rank == 0 ? 2u << 24 : 0u - (1u << 24), to2 = rank == 2 ? 0u - (2u << 24) : 1u << 24;
  const bool isC = rank == 2;
  const int lane = opaque32(lane_), warp = WG * 4 + w;
  const int gl = rot_chunk(4 * (lane & 3) + w, rank);
  const int g0 = __shfl_sync(0xffffffffu, gl, 0), g1 = __shfl_sync(0xffffffffu, gl, 1), g2 = __shfl_sync(0xffffffffu, gl, 2);
  const uint32_t arm_bytes = arm_size(w, isC);

#define L16 opaque32(sb + opaque32(lane) * 16)
#define L8 opaque32(sb + opaque32(lane) * 8)
#define L4 opaque32(sb + opaque32(lane) * 4)
#define LV opaque32(sb + R_VT + ((opaque32(lane) >> 3) & 1) * 512 + (opaque32(lane) >> 4) * 128 + (opaque32(lane) & 7) * 16)
#define SLOT(st) opaque64(slot0 + ((st) & 3) * 12288 + ((st) & 4) * 32)
  float* const slot0 = opaque64(g_slot + (rank * 1024 + warp * 128 + lane) * 4);
  const uint32_t woa = opaque32(sb + R_WO + warp * 12288 + ((lane >> 4) * 8 + (lane & 7)) * 32 + ((((lane >> 3) ^ (lane >> 2)) & 1) << 4));
  const bool has_wo = WG == 0 || isC || w < 3;
  float acc[20];
  uint32_t pk[8] = {0u, 0u, 0u, 0u, 0u, 0u, 0u, 0u};

  auto forward = [&](auto rd, const uint32_t* v, int st, uint32_t tries) {
    constexpr int RD = decltype(rd)::value;
    uint32_t u[6];
#pragma unroll
    for (int j = 0; j < 6; j++) u[j] = movm(v[4 * (j / 3) + j % 3]);
    const bool all3 = RD == 0 || w < 3;
    if (RD == 0) {
      const uint32_t a = L16 + R_M1 + w * 768, a2 = L8 + R_M1 + 512 + w * 768;
      st_async4(a + to1 + 3072, u, bars + to1 + B_MB + 8); st_async2(a2 + to1 + 3072, u[4], u[5], bars + to1 + B_MB + 8);
      sts128(a, u[0], u[1], u[2], u[3]); sts64(a2, u[4], u[5]);
      __syncwarp();
      if (elect_one()) mbar_arrive(bars + B_MB);
      st_async4(a + to2 + 6144, u, bars + to2 + B_MB + 16); st_async2(a2 + to2 + 6144, u[4], u[5], bars + to2 + B_MB + 16);
    } else {
      const uint32_t a = L4 + R_M2 + rank * 2304 + w * 768;
#pragma unroll
      for (int j = 0; j < 6; j++) if (j < 2 || all3) st_async1(a + to1 + j * 128, u[j], bars + to1 + B_MB + 24);
#pragma unroll
      for (int j = 0; j < 6; j++) if (j < 2 || all3) st_async1(a + to2 + j * 128, u[j], bars + to2 + B_MB + 24);
      if (SELF_STAS) {
#pragma unroll
        for (int j = 0; j < 6; j++) if (j < 2 || all3) st_async1(a + j * 128, u[j], bars + B_MB + 24);
      } else {
#pragma unroll
        for (int j = 0; j < 6; j++) if (j < 2 || all3) sts32(a + j * 128, u[j]);
        __syncwarp();
        if (elect_one()) mbar_arrive(bars + B_MB + 24);
      }
    }
  };

  auto send_vt = [&]() {
    if (elect_one()) {
      const uint32_t src = sb + R_VT + warp * 1024;
      bulk_s2s(src + to1, src, 1024, bars + to1 + B_VT);
      bulk_s2s(src + to2, src, 1024, bars + to2 + B_VT);
    }
  };
  auto store_att = [&](int sg) {
    uint32_t* op = reinterpret_cast<uint32_t*>(g_att + (size_t)((sg >> 2) * 64 + head * 2 + rank) * 16384 + (2 * w * 16 + (sg & 3) * 4) * 128) + opaque32(lane);
#pragma unroll
    for (int j = 0; j < 8; j++) op[(j & 1) * 512 + (j >> 1) * 32] = pk[j];
  };

  if (WG == 0) bar_arrive<NB_G, 256>();
#pragma unroll 1
  for (int s = -1; s < NSEG; s++) {
    const uint32_t par = (s + 1) & 1;
    const uint32_t last = s == NSEG - 1;
    TRACE(0);
    {
      float c[NCH][4];
      uint32_t b[3][6];
      const uint32_t ma = L16, m8 = L8;
#pragma unroll
      for (int i = 0; i < 18; i++) {
        if (i < 16) {
          if (i % 4 == 0 && !(i == 4 && TOP2)) mbar_wait(bars + B_MB + (i / 4) * 8, par ^ 1);
          if (i == 0 && TOP2) mbar_wait(bars + B_MB + 8, par ^ 1);
          if (i % 4 == 0) TRACE(1 + i / 4);
          if (i < 12) { lds128(b[i % 3], ma + R_M1 + i * 768); lds64(b[i % 3] + 4, m8 + R_M1 + 512 + i * 768); }
          else { ldsm4(b[i % 3], ma + R_M2 + 4096 + (i - 12) * 768); ldsm2(b[i % 3] + 4, ma + R_M2 + 4096 + 512 + (i - 12) * 768); }
          if (WG == 1 && i == BX_I) {
            bar_sync<NB_G, 256>();
            if (!last && elect_one()) load_chunk(sb + R_GB + w * 4096, s + 1, g0, bars + B_FB);
          }
          if (i == CX_I) {
            if (isC && s >= 0) send_vt();
            if (WG == 1 && ATT_LATE && !isC && s > 0) store_att(s - 1);
          }
          __syncwarp();
        }
        if (i >= 2) {
          const int j = i - 2;
#pragma unroll
          for (int q = 0; q < 3; q++) {
            const uint32_t* f = W[3 * j + q];
            if (3 * j + q < NCH) hmma0(c[3 * j + q], f[0], f[1], f[2], f[3], b[j % 3][2 * q], b[j % 3][2 * q + 1]);
            else hmma(c[(3 * j + q) % NCH], f[0], f[1], f[2], f[3], b[j % 3][2 * q], b[j % 3][2 * q + 1]);
          }
        }
        if (i == 14) zero_regs<16>(acc);
        if (i == 16) mbar_wait(bars + B_FA, last);
      }
#pragma unroll
      for (int j = 0; j < 4; j++) acc[16 + j] = NCH == 3 ? (c[0][j] + c[1][j]) + c[2][j] : (c[0][j] + c[1][j]) + (c[2][j] + c[NCH - 1][j]);
    }
    TRACE(5);
    bar_sync<NB_H, 256>();
    WG_FENCE();
#pragma unroll
    for (int k = 0; k < 16; k++) wg_ss40<0>(acc, dsc.tail_a[WG * 16 + k], dsc.tail_b[k]);
    WG_COMMIT();
    uint32_t vt[4][4];
    {
      const uint32_t a = opaque32(L4 + w * 256 + (isC ? WG * 1024 + R_VM : R_QK + 4096 + WG * 5120));
      const uint32_t qa = L16 + R_QK, xa = opaque32(LV + w * 2048 + (WG == 0 ? 0 : (opaque32(lane) & 8) * 64 + R_QK + 5120 - R_VT));
      const uint32_t d = opaque32(L4 + R_XS + rank * 640 + w * 256);
      if (s == 0) {
        mbar_wait_safe(bars + B_WO, 0);
        TS(10);
        if (WG == 1 && head == 0 && rank == 0 && w == 0 && elect_one()) red_add_u32(&g_flags[FL_GO], 1);
      }
      mbar_wait(bars + B_FB, last);
      if (WG == 0) mbar_wait(bars + B_VT, par);
      WG_WAIT(0);
      reg_fence<20>(acc);
      TRACE(6);
      const uint32_t p0 = pack2(acc[16], acc[17]), p1 = pack2(acc[18], acc[19]);
      sts32(a, p0); sts32(a + 128, p1);
      if (isC) {
        st_async1(a + to1, p0, bars + B_VM + to1); st_async1(a + to1 + 128, p1, bars + B_VM + to1);
        st_async1(a + to2, p0, bars + B_VM + to2); st_async1(a + to2 + 128, p1, bars + B_VM + to2);
      }
      if (WG == 0) {
        bar_arrive<NB_A, 256>();
        if (Q_FENCE && !isC) fence_async_smem();
#pragma unroll
        for (int i = 0; i < 4; i++) ldsm4(vt[i], xa + (i >> 1) * 1024 + (i & 1) * 256);
        bar_sync<NB_S, 256>();
      } else {
        bar_sync<NB_A, 256>();
        if (!isC) {
          if (w < 3) {
            uint32_t q[8], k[4][4];
            ldsm4t(q, qa + 4096); ldsm4t(k[0], xa); ldsm4t(k[1], xa + 256);
            ldsm4t(q + 4, qa + 4096 + 512); ldsm4t(k[2], xa + 512); ldsm4t(k[3], xa + 768);
            float x[4], y[4];
            hmma0(x, k[0][0], k[0][1], k[0][2], k[0][3], q[0], q[1]); hmma0(y, k[1][0], k[1][1], k[1][2], k[1][3], q[2], q[3]);
            hmma(x, k[2][0], k[2][1], k[2][2], k[2][3], q[4], q[5]); hmma(y, k[3][0], k[3][1], k[3][2], k[3][3], q[6], q[7]);
            const uint32_t s0 = pack2(x[0] + y[0], x[1] + y[1]), s1 = pack2(x[2] + y[2], x[3] + y[3]);
            st_async1(d + to1, s0, bars + B_XS + to1);
            st_async1(d + to2, s0, bars + B_XS + to2);
            if (w < 2) { st_async1(d + to1 + 128, s1, bars + B_XS + to1); st_async1(d + to2 + 128, s1, bars + B_XS + to2); sts32(d + 128, s1); }
            sts32(d, s0);
          }
        }
        bar_arrive<NB_S, 256>();
      }
    }
    if (WG == 1) {
      if (!last && elect_one()) load_chunk(sb + R_GA + w * 4096, s + 1, g1, bars + B_FA);
      {
        if (w > 0 && elect_one()) mbar_expect(bars + B_MB + 8 * w, w < 3 ? 3072 : SELF_STAS ? 28 * 256 : isC ? 18 * 256 : 19 * 256);
      }
      fence_async_smem();
      bar_sync<NB_B, 256>();
    }
    TRACE(7);
    WG_FENCE();
#pragma unroll
    for (int k = 0; k < 16; k++) wg_rs32<1>(acc, W[k][0], W[k][1], W[k][2], W[k][3], dsc.tok[16 + k]);
    WG_COMMIT();
    uint32_t wa[3][4];
    const uint32_t oxa = L16 + R_OX;
    if (WG == 0) {
      const uint32_t vma = oxa - (R_OX - R_VM) + w * 512, oa = opaque32(L4 + w * 512 + R_OX);
      TRACE(8);
      mbar_wait(bars + B_XS, par);
      TRACE(9);
      float sv[10];
      {
        uint32_t x[10];
        ldsm4t(x, oxa - (R_OX - R_XS)); ldsm4t(x + 4, oxa - (R_OX - R_XS) + 512); ldsm2t(x + 8, oxa - (R_OX - R_XS) + 1024);
        bar_arrive<NB_B, 256>();
#pragma unroll
        for (int j = 0; j < 5; j++) x[j] = hadd2(x[j], x[j + 5]);
        exp10(sv, x);
      }
      WG_WAIT(0);
      bar_arrive<NB_X, 256>();
      mbar_wait(bars + B_VM, par);
      uint32_t vm[4];
      ldsm4(vm, vma);
      uint32_t pb[5];
#pragma unroll
      for (int j = 0; j < 5; j++) pb[j] = pack2(sv[2 * j], sv[2 * j + 1]);
      TRACE(10);
      float o0[4], o1[4], sm[4];
      const uint32_t ONE = 0x3f803f80u;
      hmma0(o0, vt[0][0], vt[0][1], vt[0][2], vt[0][3], pb[0], pb[1]);
      hmma0(o1, vt[2][0], vt[2][1], vt[2][2], vt[2][3], pb[0], pb[1]);
      hmma0(sm, ONE, ONE, ONE, ONE, pb[0], pb[1]);
      hmma(sm, ONE, ONE, ONE, ONE, pb[2], pb[3]);
      hmma(o0, vt[1][0], vt[1][1], vt[1][2], vt[1][3], pb[2], pb[3]);
      hmma(o1, vt[3][0], vt[3][1], vt[3][2], vt[3][3], pb[2], pb[3]);
      hmma_k8(sm, ONE, ONE, pb[4]);
      hmma_k8(o0, vm[0], vm[1], pb[4]);
      hmma_k8(o1, vm[2], vm[3], pb[4]);
#pragma unroll
      for (int i = 0; i < 3; i++) ldsm4t(wa[i], woa + i * 4096);
      __syncwarp();
      const float i0 = rcp(sm[0]), i1 = rcp(sm[1]);
      sts32(oa, pack2(o0[0] * i0, o0[1] * i1)); sts32(oa + 128, pack2(o0[2] * i0, o0[3] * i1));
      sts32(oa + 256, pack2(o1[0] * i0, o1[1] * i1)); sts32(oa + 384, pack2(o1[2] * i0, o1[3] * i1));
      TRACE(11);
      bar_sync<NB_C, 128>();
    } else {
      if (!isC) {
        constexpr uint64_t dQ = mkdesc(0x400 + R_QK, 128, 1024, 0), dK = mkdesc(0x400 + R_QK + 5120, 128, 1024, 0);
        float sc[16];
        zero_regs<16>(sc);
        WG_FENCE();
#pragma unroll
        for (int k = 0; k < 4; k++) wg_ss32<1>(sc, dK + k * 16, dQ + k * 16);
        WG_COMMIT();
        const uint32_t top = rank == 0 ? to2 : to1, e = L4 + R_P + w * 256;
        WG_WAIT(0);
        bar_sync<NB_X, 256>();
        if (!last && elect_one()) load_chunk(sb + R_GB + w * 4096, s + 1, g2, bars + B_FB);
        reg_fence<16>(sc);
        if (w < 3) {
#pragma unroll
          for (int j = 0; j < 8; j++) {
            if ((j & 1) ? (j > 1 && (w == 0 || (w == 1 && j == 7))) : (j >= 4 || w != 1)) {
              const uint32_t t = pack2(sc[2 * j], sc[2 * j + 1]), o = (j >> 1) * 768 + (j & 1) * 128;
              st_async1(e + top + 3072 + o, t, bars + top + B_TS);
              sts32(e + o, t);
            }
          }
          __syncwarp();
          if (elect_one()) mbar_arrive(bars + B_TS);
        }
      } else {
        WG_WAIT(0);
        bar_sync<NB_X, 256>();
        if (!last && elect_one()) load_chunk(sb + R_GB + w * 4096, s + 1, g2, bars + B_FB);
      }
      TRACE(8);
      mbar_wait(bars + B_FA, 1);
      TRACE(11);
    }
    if (has_wo) {
      float* rslot = SLOT(s);
      uint32_t ob[4][4];
      float c[3][4];
      if (WG == 1) {
#pragma unroll
        for (int i = 0; i < 3; i++) ldsm4t(wa[i], woa + i * 4096);
        bar_sync<NB_D, 256>();
      }
      ldsm4t(ob[0], oxa);
      __syncwarp();
#pragma unroll
      for (int k = 0; k < 8; k++) {
        uint32_t nx[3][4];
        if ((k & 1) == 0 && k < 6) { ldsm4t(ob[(k >> 1) + 1], oxa + ((k >> 1) + 1) * 512); __syncwarp(); }
#pragma unroll
        for (int i = 0; i < 3; i++) {
          const uint32_t* o = ob[k >> 1] + (k & 1) * 2;
          if (k < 7) { ldsm4t(nx[i], woa + i * 4096 + (k + 1) * 512); if (i == 2) __syncwarp(); }
          if (k == 0) hmma0(c[i], wa[i][0], wa[i][1], wa[i][2], wa[i][3], o[0], o[1]);
          else hmma(c[i], wa[i][0], wa[i][1], wa[i][2], wa[i][3], o[0], o[1]);
#pragma unroll
          for (int q = 0; q < 4; q++) if (k < 7) wa[i][q] = nx[i][q];
        }
        if (k == ND_K && WG == 0) bar_arrive<NB_D, 256>();
      }
      const float* cv = &c[0][0];
      uint32_t r[6];
#pragma unroll
      for (int j = 0; j < 6; j++) r[j] = pack2(cv[2 * j], cv[2 * j + 1]);
      asm volatile("{\n.reg .pred p;\nsetp.lt.s32 p, %8, 0;\n@p bra.uni SKIP;\n"
                   "red.relaxed.gpu.global.add.noftz.v4.bf16x2 [%0], {%1, %2, %3, %7};\n"
                   "red.relaxed.gpu.global.add.noftz.v4.bf16x2 [%0+1024], {%4, %5, %6, %7};\nSKIP:\n}"
                   :: "l"(rslot), "r"(r[0]), "r"(r[1]), "r"(r[2]), "r"(r[3]), "r"(r[4]), "r"(r[5]), "r"(0x3f800000), "r"(s) : "memory");
    } else {
      bar_arrive<NB_D, 256>();
      if ((s & 3) == 0) {
        fence_gpu();
        if (s > 0 && elect_one()) red_add_u32(&g_flags[FL_ATT + 2 * (s - 4)], 1);
      }
      if (rank == 0 || head < 16)
        reinterpret_cast<uint4*>(g_slot)[((s + ZS) & 3) * 3072 + ((s + ZS) & 4) * 8 + rank * 2048 + head * 64 + opaque32(lane)] = make_uint4(0, 0, 0, 0);
      if (HPF && head < 16 && rank == 0 && s + HPF < NSEG && elect_one())
        asm volatile("cp.async.bulk.prefetch.L2.global [%0], 4096;" :: "l"(g_h + (size_t)((s + HPF) * 16 + head) * 4096) : "memory");
    }
    const uint32_t t_red = clk32();
    uint32_t v[8];
    const float* slot = SLOT(s);
    TRACE(13);
    if (WG == 0) {
      if (!isC) {
        const int ln = opaque32(lane), kg = w - (ln >> 3);
        const uint32_t r16 = sb + R_P + w * 768 + (ln & 7) * 16;
        const uint32_t ta = r16 + (kg >= 0 ? kg * 128 : 640);
        const int dg = (ln >> 2) - 2 * (ln & 3);
        const uint32_t keep = dg > 0 ? 0xffffffffu : dg == 0 ? 0x0000ffffu : 0u;
        mbar_wait(bars + B_TS, par);
        uint32_t x[6], y[4];
        ldsm4t(x, ta); ldsm4t(y, ta + 3072); ldsm2t(x + 4, r16 + 512 + ((ln >> 3) & 1) * 3072);
#pragma unroll
        for (int j = 0; j < 5; j++) x[j] = hadd2(x[j], j < 4 ? y[j] : x[5]);
        x[0] = (x[0] & keep) | (0xff80ff80u & ~keep);
        float sv[10];
        exp10(sv, x);
        float sum = (((sv[0] + sv[1]) + (sv[2] + sv[3])) + ((sv[4] + sv[5]) + (sv[6] + sv[7]))) + (sv[8] + sv[9]);
        sum += __shfl_xor_sync(0xffffffffu, sum, 1);
        sum += __shfl_xor_sync(0xffffffffu, sum, 2);
        const float inv = rcp(sum);
#pragma unroll
        for (int j = 0; j < 5; j++) x[j] = pack2(sv[2 * j] * inv, sv[2 * j + 1] * inv);
        stsm4(r16 + (kg & 3) * 128, x);
        sts32(sb + ln * 4 + w * 768 + R_P + 512, x[4]);
        fence_async_smem();
        bar_arrive<NB_P, 256>();
      }
      while (clk32() - t_red < POLL_DELAY) {}
      load_red(v, slot);
      bar_sync<NB_E, 256>();
    } else {
      mbar_wait(bars + B_FB, 1);
    }
    TRACE(14);
    float ao[16];
    if (WG == 1) zero_regs<16>(ao);
    WG_FENCE();
#pragma unroll
    for (int k = 0; k < 32; k++) {
      if (WG == 0 && k == 16) WG_COMMIT();
      wg_rs32<1>(acc, W[16 + k][0], W[16 + k][1], W[16 + k][2], W[16 + k][3], dsc.tok[k]);
    }
    WG_COMMIT();
    TRACE(12);
    if (WG == 1) {
      if (!isC) {
        constexpr uint64_t dP = mkdesc(0x400 + R_P, 128, 768, 0);
        const uint64_t dV = mkdesc(0x400 + R_VT, 128, 512, 0) + rank * 256, dM = mkdesc(0x400 + R_VM, 0, 128, 0) + rank * 64;
        bar_sync<NB_P, 256>();
        WG_FENCE();
        wg_ss32<0>(ao, dV, dP); wg_ss32<0>(ao, dV + 16, dP + 16); wg_ss32<0>(ao, dM, dP + 32);
        WG_COMMIT();
      }
      bar_arrive<NB_E, 256>();
      if (elect_one()) mbar_expect(bars + B_XS + 8 * w, arm_bytes);
      while (clk32() - t_red < POLL_DELAY1) {}
      load_red(v, slot);
      bar_arrive<NB_W0, 128>();
    } else {
      WG_WAIT(1);
      bar_arrive<NB_F, 256>();
      sched_fence(head, 100);
      v[3] = opaque32(v[3]);
      const uint32_t tries = finish_red(v, slot);
      forward(std::integral_constant<int, 0>(), v, s, tries);
      TRACE(16);
    }
    WG_WAIT(0);
    reg_fence<16>(acc);
    if (WG == 0) bar_arrive<NB_G, 256>();
    TRACE(15);
    {
      uint32_t pq[8];
#pragma unroll
      for (int j = 0; j < 8; j++) pq[j] = pack2(acc[2 * j], acc[2 * j + 1]);
      if (WG == 1) {
        reg_fence<16>(ao);
#pragma unroll
        for (int j = 0; j < 8; j++) pk[j] = pack2(ao[2 * j], ao[2 * j + 1]);
      }
      if (!isC) {
        const uint32_t q = L4 + w * 256 + R_QK + WG * 5120;
#pragma unroll
        for (int j = 0; j < 8; j++) sts32(q + (j >> 1) * 1024 + (j & 1) * 128, pq[j]);
        if (WG == 1 && !ATT_LATE && s >= 0) store_att(s);
      } else {
        const uint32_t a = LV + warp * 1024;
        stsm4(a, pq); stsm4(a + 256, pq + 4);
      }
    }
    TRACE(17);
    if (WG == 1) {
      auto refill = [&]() {
        bar_sync<NB_F, 256>();
        if (s < NSEG - 2 && elect_one()) load_chunk(sb + R_GA + w * 4096, s + 2, 12 + w, bars + B_FA);
      };
      if (RF_FIRST) refill();
      if (has_wo) { v[3] = opaque32(v[3]); const uint32_t tries = finish_red(v, slot); forward(std::integral_constant<int, 1>(), v, s, tries); }
      if (!RF_FIRST) refill();
      TRACE(16);
    }
    if (isC && V_FENCE) { fence_async_smem(); __syncwarp(); }
    TRACE(18);
  }
  if (WG == 1 && ATT_LATE && !isC) store_att(NSEG - 1);
  if (WG == 1) bar_sync<NB_G, 256>();
  mbar_wait_safe(bars + B_MB + 8, 0); mbar_wait_safe(bars + B_MB + 16, 0); mbar_wait_safe(bars + B_MB + 24, 0);
#undef L16
#undef L8
#undef L4
#undef SLOT
#undef LV
}

__global__ void __cluster_dims__(3, 1, 1) __launch_bounds__(256, 1)
kernel_R(const __grid_constant__ CUtensorMap tmq, const __grid_constant__ CUtensorMap tmk, const __grid_constant__ CUtensorMap tmv,
         const __grid_constant__ CUtensorMap tmo, const __grid_constant__ CUtensorMap tmm, const __nv_bfloat16* __restrict__ x,
         const __nv_bfloat16* __restrict__ mem0, const __nv_bfloat16* __restrict__ cvec, const __grid_constant__ RDesc dsc) {
  extern __shared__ __align__(1024) uint8_t smem[];
  const uint32_t sb = smem_u32(smem);
  uint32_t rank; asm("mov.u32 %0, %%cluster_ctarank;" : "=r"(rank));
  rank = __shfl_sync(0xffffffffu, rank, 0);
  const int cta = blockIdx.x, head = __shfl_sync(0xffffffffu, cta / 3, 0);
  const int tid = threadIdx.x, lane = tid & 31;
  const int warp = __shfl_sync(0xffffffffu, tid >> 5, 0);
  const int wg = warp >> 2, w = warp & 3;
  const uint32_t bars = sb + R_BAR;
  const CUtensorMap* tmw = rank == 2 ? &tmv : (wg == 0 ? &tmq : &tmk);
  const int fcol = head * 128 + (rank == 2 ? wg * 64 : (int)rank * 64);

  asm volatile("griddepcontrol.launch_dependents;");
  uint32_t W[48][4];
  {
    if (sb != (rank << 24) + 0x400) __trap();
    if (tid == 0) {
      sts64(bars + 248, rank, head);
      mbar_init(bars + B_MB, 4); mbar_init(bars + B_MB + 8, 1); mbar_init(bars + B_MB + 16, 1); mbar_init(bars + B_MB + 24, SELF_STAS ? 1 : rank == 2 ? 5 : 4);
      for (int i = B_XS; i <= B_X; i += 8) mbar_init(bars + i, i == B_FA || i == B_FB || (i == B_TS && rank < 2) ? 4 : 1);
      asm volatile("fence.mbarrier_init.release.cluster;" ::: "memory");
      fence_async_smem();
    }
    __syncthreads();
    asm volatile("barrier.cluster.arrive.relaxed.aligned;" ::: "memory");
    TS(0);
    const int nwm = rank == 0 ? 6 : 5, wm0 = rank == 0 ? 0 : 5 * rank + 1, nrg = cta < 64 ? 3 : 2;
    if (elect_one()) {
      if (warp == 0) { mbar_expect(bars + B_WM, nwm * 8192); mbar_expect(bars + B_X, nrg * 16384); }
      if (warp < nwm) tma2d_p(sb + R_GA + warp * 8192, &tmm, head * 64, (wm0 + warp) * 64, bars + B_WM, POL_RW);
#pragma unroll 1
      for (int r = 0; r < nrg; r++) bulk_g2s(sb + R_TAIL + (r * 8 + warp) * 2064, x + (size_t)((cta + 96 * r) * 8 + warp) * D_, 2048, bars + B_X);
      if (w == 0) mbar_expect(bars + B_STG + wg * 16, 49152);
      if (w < 2) tma2d_p(sb + R_WO + wg * 49152 + w * 8192, tmw, fcol, rot_chunk(w, rank) * 64, bars + B_STG + wg * 16, POL_RW);
    }
    float* scr = reinterpret_cast<float*>(smem + R_VT);
#pragma unroll 1
    for (int i = tid; i < nwm * 64; i += 256) {
      const float c = __bfloat162float(cvec[wm0 * 64 + i]);
      scr[i] = __bfloat162float(__float2bfloat16(c / (1.f + __expf(-c))));
    }
    if (tid < 128) {
      uint32_t e[4] = {0u, 0u, 0u, 0u};
      if (cta >= 72 && (tid & 32)) {
        const uint16_t* mp = reinterpret_cast<const uint16_t*>(mem0) + 2 * (lane & 3) * D_ + (lane >> 2);
#pragma unroll
        for (int q = 0; q < 3; q++) {
          const int n = 3 * (tid >> 6) + q, col = wo_tile(3 * (cta & 7) + (n >> 1), (cta - 72) >> 3) * 16 + 8 * (n & 1);
          e[q] = mp[col] | (uint32_t)mp[col + D_] << 16;
        }
        e[3] = 0x42000000u;
      }
      reinterpret_cast<uint4*>(g_slot)[cta * 128 + tid] = make_uint4(e[0], e[1], e[2], e[3]);
    }
    __syncthreads();
    TS(1);
    mbar_wait_safe(bars + B_WM, 0);
    if (elect_one()) tma2d_p(sb + R_WO + wg * 49152 + (2 + w) * 8192, tmw, fcol, rot_chunk(2 + w, rank) * 64, bars + B_STG + wg * 16, POL_RW);
    {
      float a[8];
#pragma unroll
      for (int j = 0; j < 8; j++) a[j] = 0.f;
#pragma unroll 2
      for (int i = 0; i < 2 * nwm; i++) {
        uint32_t u[4];
        lds128(u, sb + R_GA + i * 4096 + tid * 16);
        const float sc = scr[i * 32 + (tid >> 3)];
#pragma unroll
        for (int j = 0; j < 4; j++) { a[2 * j] += sc * bf_lo(u[j]); a[2 * j + 1] += sc * bf_hi(u[j]); }
      }
#pragma unroll
      for (int j = 0; j < 8; j++) { a[j] += __shfl_xor_sync(0xffffffffu, a[j], 8); a[j] += __shfl_xor_sync(0xffffffffu, a[j], 16); }
      if (lane < 8) {
        sts128(sb + R_VT + 1536 + warp * 256 + lane * 32, __float_as_uint(a[0]), __float_as_uint(a[1]), __float_as_uint(a[2]), __float_as_uint(a[3]));
        sts128(sb + R_VT + 1552 + warp * 256 + lane * 32, __float_as_uint(a[4]), __float_as_uint(a[5]), __float_as_uint(a[6]), __float_as_uint(a[7]));
      }
    }
    __syncthreads();
    TS(2);
    if (warp == 7) {
      float t0 = 0.f, t1 = 0.f;
#pragma unroll
      for (int i = 0; i < 8; i++) { float t[2]; lds64f(t, sb + R_VT + 1536 + i * 256 + lane * 8); t0 += t[0]; t1 += t[1]; }
      reinterpret_cast<float2*>(g_modp + rank * 2048 + head * 64)[lane] = make_float2(t0, t1);
      fence_gpu();
      __syncwarp();
      if (lane == 0) red_add_u32(&g_flags[FL_S1], 1);
      __syncwarp();
    }
    mbar_wait_safe(bars + B_X, 0);
#pragma unroll 1
    for (int r = 0; r < nrg; r++) {
      float f[32];
#pragma unroll
      for (int i = 0; i < 4; i++) {
        uint32_t u[4];
        lds128(u, sb + R_TAIL + (r * 8 + warp) * 2064 + i * 512 + lane * 16);
#pragma unroll
        for (int j = 0; j < 4; j++) { f[8 * i + 2 * j] = bf_lo(u[j]); f[8 * i + 2 * j + 1] = bf_hi(u[j]); }
      }
      float t = 0.f;
#pragma unroll
      for (int i = 0; i < 32; i++) t += f[i];
#pragma unroll
      for (int o = 1; o < 32; o <<= 1) t += __shfl_xor_sync(0xffffffffu, t, o);
      const float mean = t * (1.f / D_);
      t = 0.f;
#pragma unroll
      for (int i = 0; i < 32; i++) t = fmaf(f[i] - mean, f[i] - mean, t);
#pragma unroll
      for (int o = 1; o < 32; o <<= 1) t += __shfl_xor_sync(0xffffffffu, t, o);
      const float rstd = rsqrtf(t * (1.f / D_) + 1e-5f);
      if (lane == 0) sts64(sb + R_VT + 3584 + (r * 8 + warp) * 8, __float_as_uint(rstd), __float_as_uint(-mean * rstd));
    }
    TS(3);
    if (w < PF1 && elect_one()) tma2d_prefetch_p(tmw, fcol, rot_chunk(6 + w, rank) * 64, POL_RW);
    if (tid == 0) wait_flag(&g_flags[FL_S1], 96);
    __syncthreads();
    TS(4);
    {
      float4 p[6];
#pragma unroll
      for (int i = 0; i < 6; i++) p[i] = __ldcg(reinterpret_cast<const float4*>(g_modp + (i >> 1) * 2048) + 2 * tid + (i & 1));
      if (w < PF2 && elect_one()) tma2d_prefetch_p(tmw, fcol, (9 + w) * 64, POL_RW);
      sts128(sb + R_VT + 5120 + tid * 16, pack2(p[0].x + p[2].x + p[4].x, p[0].y + p[2].y + p[4].y), pack2(p[0].z + p[2].z + p[4].z, p[0].w + p[2].w + p[4].w),
             pack2(p[1].x + p[3].x + p[5].x, p[1].y + p[3].y + p[5].y), pack2(p[1].z + p[3].z + p[5].z, p[1].w + p[3].w + p[5].w));
    }
    __syncthreads();
#pragma unroll 2
    for (int it = 0; it < 4 * nrg; it++) {
      const int r = it >> 2, rg = cta + 96 * r, c = 16 * warp + (lane >> 3) + 4 * (it & 3);
      uint32_t a[4], b[4], u[4], o[4];
      float t[2];
      lds128(u, sb + R_TAIL + (r * 8 + (lane & 7)) * 2064 + c * 16);
      lds128(a, sb + R_VT + 5120 + c * 16); lds128(b, sb + R_VT + 7168 + c * 16);
      lds64f(t, sb + R_VT + 3584 + (r * 8 + (lane & 7)) * 8);
#pragma unroll
      for (int j = 0; j < 4; j++)
        o[j] = pack2(fmaf(fmaf(bf_lo(u[j]), t[0], t[1]), 1.f + bf_lo(b[j]), bf_lo(a[j])), fmaf(fmaf(bf_hi(u[j]), t[0], t[1]), 1.f + bf_hi(b[j]), bf_hi(a[j])));
      *reinterpret_cast<uint4*>(g_h + (size_t)(rg >> 2) * 65536 + (lane & 7) * 16 + (c & 7) * 128 +
                                (c < 96 ? (c >> 3) * 4096 + (rg & 3) * 1024 : 49152 + (rg & 3) * 4096 + ((c >> 3) - 12) * 1024)) =
          make_uint4(o[0], o[1], o[2], o[3]);
    }
    TS(5);
    __syncthreads();
    TS(6);
    if (w < PF3 && elect_one()) tma2d_p(sb + R_TAIL + warp * 8192, tmw, fcol, 768 + w * 64, bars + B_TAIL, POL_RW);
    if (warp == 3 && lane == 0) { fence_gpu(); red_add_u32(&g_flags[FL_S2], 1); }
    __syncwarp();

    const uint32_t a0 = opaque32(sb + R_WO + wg * 49152 + ((lane >> 4) * 8 + (lane & 7)) * 128 + (((2 * w + ((lane >> 3) & 1)) ^ (lane & 7)) << 4));
    mbar_wait_safe(bars + B_STG + wg * 16, 0);
    TS(7);
#pragma unroll
    for (int i = 0; i < 24; i++) ldsm4t(W[i], a0 + i * 2048);
    if (tid == 0) wait_flag(&g_flags[FL_S2], 96);
    __syncthreads();
    asm volatile("fence.proxy.async.global;" ::: "memory");
    if (elect_one()) {
      if (wg == 0) load_chunk(sb + R_GA + w * 4096, 0, 12 + w, bars + B_FA);
      if (w == 0) mbar_expect(bars + B_STG + wg * 16 + 8, 49152);
#pragma unroll 1
      for (int c = w; c < 6; c += 4) tma2d_p(sb + R_WO + wg * 49152 + c * 8192, tmw, fcol, rot_chunk(6 + c, rank) * 64, bars + B_STG + wg * 16 + 8, POL_RW);
      if (warp == 0) mbar_expect(bars + B_TAIL, 65536);
      if (w >= PF3) tma2d_p(sb + R_TAIL + warp * 8192, tmw, fcol, 768 + w * 64, bars + B_TAIL, POL_RW);
      if (wg == 1) mbar_expect(bars + B_XS + 8 * w, w == 2 ? 0 : arm_size(w, rank == 2));
#pragma unroll 1
      for (int i = warp; i < PF4; i += 8) tma2d_prefetch(&tmo, 16 * wo_tile(i, rank), head * 128);
    }
    TS(8);
    mbar_wait_safe(bars + B_STG + wg * 16 + 8, 0);
    TS(9);
#pragma unroll
    for (int i = 0; i < 24; i++) ldsm4t(W[24 + i], a0 + i * 2048);
    __syncthreads();
    if (elect_one()) {
      const int n = rank == 2 ? 22 : 21;
      if (warp == 0) mbar_expect(bars + B_WO, n * 4096);
#pragma unroll 1
      for (int i = warp; i < n; i += 8) tma2d(sb + R_WO + i * 4096, &tmo, 16 * wo_tile(i, rank), head * 128, bars + B_WO);
    }
    sts32(sb + R_P + warp * 768 + 640 + lane * 4, wg == 0 ? 0u : 0xff80ff80u);
    mbar_wait_safe(bars + B_TAIL, 0);
    asm volatile("barrier.cluster.wait.aligned;\nbarrier.cluster.arrive.relaxed.aligned;\nbarrier.cluster.wait.aligned;" ::: "memory");
  }
  uint32_t rh[2];
  lds64(rh, bars + 248);
  rh[0] = __shfl_sync(0xffffffffu, rh[0], 0); rh[1] = __shfl_sync(0xffffffffu, rh[1], 0);
  if (wg == 0) r_main<0>(W, dsc, rh[1], rh[0], lane, w);
  else r_main<1>(W, dsc, rh[1], rh[0], lane, w);
  __syncthreads();
  if (rank < 2 && threadIdx.x == 0) { fence_gpu(); red_add_u32(&g_flags[FL_ATT + 8 * 15], 1); }
  asm volatile("barrier.cluster.arrive.release.aligned;\nbarrier.cluster.wait.acquire.aligned;" ::: "memory");
}

template <int TA> __device__ __forceinline__ void wg_ss256(float* d, uint64_t a, uint64_t b) {
  asm volatile("wgmma.mma_async.sync.aligned.m64n256k16.f32.bf16.bf16 {%0,%1,%2,%3,%4,%5,%6,%7,%8,%9,%10,%11,%12,%13,%14,%15,%16,%17,%18,%19,%20,%21,%22,%23,%24,%25,%26,%27,%28,%29,%30,%31,%32,%33,%34,%35,%36,%37,%38,%39,%40,%41,%42,%43,%44,%45,%46,%47,%48,%49,%50,%51,%52,%53,%54,%55,%56,%57,%58,%59,%60,%61,%62,%63,%64,%65,%66,%67,%68,%69,%70,%71,%72,%73,%74,%75,%76,%77,%78,%79,%80,%81,%82,%83,%84,%85,%86,%87,%88,%89,%90,%91,%92,%93,%94,%95,%96,%97,%98,%99,%100,%101,%102,%103,%104,%105,%106,%107,%108,%109,%110,%111,%112,%113,%114,%115,%116,%117,%118,%119,%120,%121,%122,%123,%124,%125,%126,%127}, %128, %129, 1, 1, 1, %130, 1;"
               : "+f"(d[0]), "+f"(d[1]), "+f"(d[2]), "+f"(d[3]), "+f"(d[4]), "+f"(d[5]), "+f"(d[6]), "+f"(d[7]),
                 "+f"(d[8]), "+f"(d[9]), "+f"(d[10]), "+f"(d[11]), "+f"(d[12]), "+f"(d[13]), "+f"(d[14]), "+f"(d[15]),
                 "+f"(d[16]), "+f"(d[17]), "+f"(d[18]), "+f"(d[19]), "+f"(d[20]), "+f"(d[21]), "+f"(d[22]), "+f"(d[23]),
                 "+f"(d[24]), "+f"(d[25]), "+f"(d[26]), "+f"(d[27]), "+f"(d[28]), "+f"(d[29]), "+f"(d[30]), "+f"(d[31]),
                 "+f"(d[32]), "+f"(d[33]), "+f"(d[34]), "+f"(d[35]), "+f"(d[36]), "+f"(d[37]), "+f"(d[38]), "+f"(d[39]),
                 "+f"(d[40]), "+f"(d[41]), "+f"(d[42]), "+f"(d[43]), "+f"(d[44]), "+f"(d[45]), "+f"(d[46]), "+f"(d[47]),
                 "+f"(d[48]), "+f"(d[49]), "+f"(d[50]), "+f"(d[51]), "+f"(d[52]), "+f"(d[53]), "+f"(d[54]), "+f"(d[55]),
                 "+f"(d[56]), "+f"(d[57]), "+f"(d[58]), "+f"(d[59]), "+f"(d[60]), "+f"(d[61]), "+f"(d[62]), "+f"(d[63]),
                 "+f"(d[64]), "+f"(d[65]), "+f"(d[66]), "+f"(d[67]), "+f"(d[68]), "+f"(d[69]), "+f"(d[70]), "+f"(d[71]),
                 "+f"(d[72]), "+f"(d[73]), "+f"(d[74]), "+f"(d[75]), "+f"(d[76]), "+f"(d[77]), "+f"(d[78]), "+f"(d[79]),
                 "+f"(d[80]), "+f"(d[81]), "+f"(d[82]), "+f"(d[83]), "+f"(d[84]), "+f"(d[85]), "+f"(d[86]), "+f"(d[87]),
                 "+f"(d[88]), "+f"(d[89]), "+f"(d[90]), "+f"(d[91]), "+f"(d[92]), "+f"(d[93]), "+f"(d[94]), "+f"(d[95]),
                 "+f"(d[96]), "+f"(d[97]), "+f"(d[98]), "+f"(d[99]), "+f"(d[100]), "+f"(d[101]), "+f"(d[102]), "+f"(d[103]),
                 "+f"(d[104]), "+f"(d[105]), "+f"(d[106]), "+f"(d[107]), "+f"(d[108]), "+f"(d[109]), "+f"(d[110]), "+f"(d[111]),
                 "+f"(d[112]), "+f"(d[113]), "+f"(d[114]), "+f"(d[115]), "+f"(d[116]), "+f"(d[117]), "+f"(d[118]), "+f"(d[119]),
                 "+f"(d[120]), "+f"(d[121]), "+f"(d[122]), "+f"(d[123]), "+f"(d[124]), "+f"(d[125]), "+f"(d[126]), "+f"(d[127])
               : "l"(a), "l"(b), "n"(TA));
}
template <int TA> __device__ __forceinline__ void wg_ss128(float* d, uint64_t a, uint64_t b) {
  asm volatile("wgmma.mma_async.sync.aligned.m64n128k16.f32.bf16.bf16 {%0,%1,%2,%3,%4,%5,%6,%7,%8,%9,%10,%11,%12,%13,%14,%15,%16,%17,%18,%19,%20,%21,%22,%23,%24,%25,%26,%27,%28,%29,%30,%31,%32,%33,%34,%35,%36,%37,%38,%39,%40,%41,%42,%43,%44,%45,%46,%47,%48,%49,%50,%51,%52,%53,%54,%55,%56,%57,%58,%59,%60,%61,%62,%63}, %64, %65, 1, 1, 1, %66, 1;"
               : "+f"(d[0]), "+f"(d[1]), "+f"(d[2]), "+f"(d[3]), "+f"(d[4]), "+f"(d[5]), "+f"(d[6]), "+f"(d[7]),
                 "+f"(d[8]), "+f"(d[9]), "+f"(d[10]), "+f"(d[11]), "+f"(d[12]), "+f"(d[13]), "+f"(d[14]), "+f"(d[15]),
                 "+f"(d[16]), "+f"(d[17]), "+f"(d[18]), "+f"(d[19]), "+f"(d[20]), "+f"(d[21]), "+f"(d[22]), "+f"(d[23]),
                 "+f"(d[24]), "+f"(d[25]), "+f"(d[26]), "+f"(d[27]), "+f"(d[28]), "+f"(d[29]), "+f"(d[30]), "+f"(d[31]),
                 "+f"(d[32]), "+f"(d[33]), "+f"(d[34]), "+f"(d[35]), "+f"(d[36]), "+f"(d[37]), "+f"(d[38]), "+f"(d[39]),
                 "+f"(d[40]), "+f"(d[41]), "+f"(d[42]), "+f"(d[43]), "+f"(d[44]), "+f"(d[45]), "+f"(d[46]), "+f"(d[47]),
                 "+f"(d[48]), "+f"(d[49]), "+f"(d[50]), "+f"(d[51]), "+f"(d[52]), "+f"(d[53]), "+f"(d[54]), "+f"(d[55]),
                 "+f"(d[56]), "+f"(d[57]), "+f"(d[58]), "+f"(d[59]), "+f"(d[60]), "+f"(d[61]), "+f"(d[62]), "+f"(d[63])
               : "l"(a), "l"(b), "n"(TA));
}
template <int TA> __device__ __forceinline__ void wg_ss256_first(float* d, uint64_t a, uint64_t b) {
  asm volatile("wgmma.mma_async.sync.aligned.m64n256k16.f32.bf16.bf16 {%0,%1,%2,%3,%4,%5,%6,%7,%8,%9,%10,%11,%12,%13,%14,%15,%16,%17,%18,%19,%20,%21,%22,%23,%24,%25,%26,%27,%28,%29,%30,%31,%32,%33,%34,%35,%36,%37,%38,%39,%40,%41,%42,%43,%44,%45,%46,%47,%48,%49,%50,%51,%52,%53,%54,%55,%56,%57,%58,%59,%60,%61,%62,%63,%64,%65,%66,%67,%68,%69,%70,%71,%72,%73,%74,%75,%76,%77,%78,%79,%80,%81,%82,%83,%84,%85,%86,%87,%88,%89,%90,%91,%92,%93,%94,%95,%96,%97,%98,%99,%100,%101,%102,%103,%104,%105,%106,%107,%108,%109,%110,%111,%112,%113,%114,%115,%116,%117,%118,%119,%120,%121,%122,%123,%124,%125,%126,%127}, %128, %129, 0, 1, 1, %130, 1;"
               : "=f"(d[0]), "=f"(d[1]), "=f"(d[2]), "=f"(d[3]), "=f"(d[4]), "=f"(d[5]), "=f"(d[6]), "=f"(d[7]),
                 "=f"(d[8]), "=f"(d[9]), "=f"(d[10]), "=f"(d[11]), "=f"(d[12]), "=f"(d[13]), "=f"(d[14]), "=f"(d[15]),
                 "=f"(d[16]), "=f"(d[17]), "=f"(d[18]), "=f"(d[19]), "=f"(d[20]), "=f"(d[21]), "=f"(d[22]), "=f"(d[23]),
                 "=f"(d[24]), "=f"(d[25]), "=f"(d[26]), "=f"(d[27]), "=f"(d[28]), "=f"(d[29]), "=f"(d[30]), "=f"(d[31]),
                 "=f"(d[32]), "=f"(d[33]), "=f"(d[34]), "=f"(d[35]), "=f"(d[36]), "=f"(d[37]), "=f"(d[38]), "=f"(d[39]),
                 "=f"(d[40]), "=f"(d[41]), "=f"(d[42]), "=f"(d[43]), "=f"(d[44]), "=f"(d[45]), "=f"(d[46]), "=f"(d[47]),
                 "=f"(d[48]), "=f"(d[49]), "=f"(d[50]), "=f"(d[51]), "=f"(d[52]), "=f"(d[53]), "=f"(d[54]), "=f"(d[55]),
                 "=f"(d[56]), "=f"(d[57]), "=f"(d[58]), "=f"(d[59]), "=f"(d[60]), "=f"(d[61]), "=f"(d[62]), "=f"(d[63]),
                 "=f"(d[64]), "=f"(d[65]), "=f"(d[66]), "=f"(d[67]), "=f"(d[68]), "=f"(d[69]), "=f"(d[70]), "=f"(d[71]),
                 "=f"(d[72]), "=f"(d[73]), "=f"(d[74]), "=f"(d[75]), "=f"(d[76]), "=f"(d[77]), "=f"(d[78]), "=f"(d[79]),
                 "=f"(d[80]), "=f"(d[81]), "=f"(d[82]), "=f"(d[83]), "=f"(d[84]), "=f"(d[85]), "=f"(d[86]), "=f"(d[87]),
                 "=f"(d[88]), "=f"(d[89]), "=f"(d[90]), "=f"(d[91]), "=f"(d[92]), "=f"(d[93]), "=f"(d[94]), "=f"(d[95]),
                 "=f"(d[96]), "=f"(d[97]), "=f"(d[98]), "=f"(d[99]), "=f"(d[100]), "=f"(d[101]), "=f"(d[102]), "=f"(d[103]),
                 "=f"(d[104]), "=f"(d[105]), "=f"(d[106]), "=f"(d[107]), "=f"(d[108]), "=f"(d[109]), "=f"(d[110]), "=f"(d[111]),
                 "=f"(d[112]), "=f"(d[113]), "=f"(d[114]), "=f"(d[115]), "=f"(d[116]), "=f"(d[117]), "=f"(d[118]), "=f"(d[119]),
                 "=f"(d[120]), "=f"(d[121]), "=f"(d[122]), "=f"(d[123]), "=f"(d[124]), "=f"(d[125]), "=f"(d[126]), "=f"(d[127])
               : "l"(a), "l"(b), "n"(TA));
}
template <int TA> __device__ __forceinline__ void wg_ss128_first(float* d, uint64_t a, uint64_t b) {
  asm volatile("wgmma.mma_async.sync.aligned.m64n128k16.f32.bf16.bf16 {%0,%1,%2,%3,%4,%5,%6,%7,%8,%9,%10,%11,%12,%13,%14,%15,%16,%17,%18,%19,%20,%21,%22,%23,%24,%25,%26,%27,%28,%29,%30,%31,%32,%33,%34,%35,%36,%37,%38,%39,%40,%41,%42,%43,%44,%45,%46,%47,%48,%49,%50,%51,%52,%53,%54,%55,%56,%57,%58,%59,%60,%61,%62,%63}, %64, %65, 0, 1, 1, %66, 1;"
               : "=f"(d[0]), "=f"(d[1]), "=f"(d[2]), "=f"(d[3]), "=f"(d[4]), "=f"(d[5]), "=f"(d[6]), "=f"(d[7]),
                 "=f"(d[8]), "=f"(d[9]), "=f"(d[10]), "=f"(d[11]), "=f"(d[12]), "=f"(d[13]), "=f"(d[14]), "=f"(d[15]),
                 "=f"(d[16]), "=f"(d[17]), "=f"(d[18]), "=f"(d[19]), "=f"(d[20]), "=f"(d[21]), "=f"(d[22]), "=f"(d[23]),
                 "=f"(d[24]), "=f"(d[25]), "=f"(d[26]), "=f"(d[27]), "=f"(d[28]), "=f"(d[29]), "=f"(d[30]), "=f"(d[31]),
                 "=f"(d[32]), "=f"(d[33]), "=f"(d[34]), "=f"(d[35]), "=f"(d[36]), "=f"(d[37]), "=f"(d[38]), "=f"(d[39]),
                 "=f"(d[40]), "=f"(d[41]), "=f"(d[42]), "=f"(d[43]), "=f"(d[44]), "=f"(d[45]), "=f"(d[46]), "=f"(d[47]),
                 "=f"(d[48]), "=f"(d[49]), "=f"(d[50]), "=f"(d[51]), "=f"(d[52]), "=f"(d[53]), "=f"(d[54]), "=f"(d[55]),
                 "=f"(d[56]), "=f"(d[57]), "=f"(d[58]), "=f"(d[59]), "=f"(d[60]), "=f"(d[61]), "=f"(d[62]), "=f"(d[63])
               : "l"(a), "l"(b), "n"(TA));
}

constexpr int H_STAGE = 49152, H_NST = 4;
constexpr int H_STG = H_NST * H_STAGE;
constexpr int H_VEC = H_STG + 3 * 8192;
constexpr int H_GATE = H_VEC + 6656;
constexpr int H_BAR = H_GATE + 1024;
constexpr int H_SMEM = H_BAR + 256;
constexpr int HB_FULL = 0, HB_EMPTY = 32, HB_IFULL = 64, HB_IEMPTY = 80, HB_VFULL = 96, HB_STGF = 112, HB_ITEM = 120, HB_Q = 128, HB_SRDY = 160, HB_SFREE = 184;
constexpr int NB_HX = 4, NB_HY = 5, NB_HZ = 6;
enum { IT_END = 0, IT_MOD = 1, IT_XT = 2, IT_OUT = 3, IT_WS = 4, IT_F1 = 5, IT_F2 = 6, IT_STAT = 7 };
constexpr int N_MOD = 32, N_WS = 28, N_XT = 2, N_STAT = 4;
constexpr int MAX_ITEMS = 1400;
struct HList { uint32_t n; uint32_t it[MAX_ITEMS]; };
#define HT(i)

#define POL_WO L2_NORMAL
#define POL_W2 L2_NORMAL
#define POL_ATT L2_FIRST
#define POL_ACT L2_FIRST
#define POL_PRE L2_FIRST
__device__ __forceinline__ void mbar_arrive_n(uint32_t b, uint32_t n) { asm volatile("mbarrier.arrive.shared::cta.b64 _, [%0], %1;" :: "r"(b), "r"(n) : "memory"); }
__device__ __forceinline__ void bulk_s2g(void* dst, uint32_t src, uint32_t bytes) {
  asm volatile("cp.async.bulk.global.shared::cta.bulk_group [%0], [%1], %2;" :: "l"(dst), "r"(src), "r"(bytes) : "memory");
}
__device__ __forceinline__ void tma2d_add(const CUtensorMap* m, int c0, int c1, uint32_t src) {
  asm volatile("cp.reduce.async.bulk.tensor.2d.global.shared::cta.add.tile.bulk_group [%0, {%2, %3}], [%1];" :: "l"(m), "r"(src), "r"(c0), "r"(c1) : "memory");
}
__device__ __forceinline__ void bulk_commit() { asm volatile("cp.async.bulk.commit_group;" ::: "memory"); }
template <int N> __device__ __forceinline__ void bulk_wait_read() { asm volatile("cp.async.bulk.wait_group.read %0;" :: "n"(N) : "memory"); }
__device__ __forceinline__ void bulk_wait_all() { asm volatile("cp.async.bulk.wait_group 0;" ::: "memory"); }
__device__ __forceinline__ uint32_t hfma2(uint32_t a, uint32_t b, uint32_t c) { uint32_t t; asm("fma.rn.bf16x2 %0, %1, %2, %3;" : "=r"(t) : "r"(a), "r"(b), "r"(c)); return t; }
__device__ __forceinline__ float lds32f(uint32_t a) { return __uint_as_float(lds32(a)); }

template <int BN, int TA, int K0, int K1>
__device__ __forceinline__ void h_mma(float* acc, uint64_t da, uint64_t db) {
#pragma unroll
  for (int k = K0; k < K1; k++) {
    const uint64_t a = da + k * (TA ? 256 : 2), b = db + k * 128;
    if (BN == 256) wg_ss256<TA>(acc, a, b); else wg_ss128<TA>(acc, a, b);
  }
}
template <int BN, int TA>
__device__ __forceinline__ void h_mainloop(float* acc, uint32_t sb, int nst, uint32_t& st, uint32_t& ph, int wg, bool leader, uint32_t clk_q) {
  const uint64_t da0 = TA ? mkdesc(sb + wg * 1024, 2048, 128, 0) : mkdesc(sb + wg * 8192, 16, 1024, 1);
  const uint64_t db0 = mkdesc(sb + 16384, 8192, 1024, 1);
  const uint32_t full = sb + H_BAR + HB_FULL, empty = sb + H_BAR + HB_EMPTY;
  uint32_t prev = st;
  {
    mbar_wait(full + st * 8, ph);
    HT(1);
    const uint64_t da = da0 + st * (H_STAGE >> 4), db = db0 + st * (H_STAGE >> 4);
    WG_FENCE();
    if (BN == 256) wg_ss256_first<TA>(acc, da, db); else wg_ss128_first<TA>(acc, da, db);
    h_mma<BN, TA, 1, 4>(acc, da, db);
    WG_COMMIT();
    if (++st == H_NST) { st = 0; ph ^= 1; }
  }
  {
    mbar_wait(full + st * 8, ph);
    const uint64_t da = da0 + st * (H_STAGE >> 4), db = db0 + st * (H_STAGE >> 4);
    WG_FENCE();
    h_mma<BN, TA, 0, 3>(acc, da, db);
    WG_COMMIT();
    h_mma<BN, TA, 3, 4>(acc, da, db);
    WG_COMMIT();
    WG_WAIT(1);
    if (leader) mbar_arrive(empty + prev * 8);
    if (wg) bar_arrive<NB_HY, 256>(); else bar_sync<NB_HY, 256>();
    prev = st;
    if (++st == H_NST) { st = 0; ph ^= 1; }
  }
#pragma unroll 1
  for (int i = 4; i < nst; i++) {
    mbar_wait(full + st * 8, ph);
    const uint64_t da = da0 + st * (H_STAGE >> 4), db = db0 + st * (H_STAGE >> 4);
    WG_FENCE();
    h_mma<BN, TA, 0, 4>(acc, da, db);
    WG_COMMIT();
    WG_WAIT(1);
    if (leader) mbar_arrive(empty + prev * 8);
    prev = st;
    if (++st == H_NST) { st = 0; ph ^= 1; }
  }
  if (wg) {
    WG_WAIT(0);
    if (leader) mbar_arrive(empty + prev * 8);
    bar_sync<NB_HX, 256>();
  }
  {
    mbar_wait(full + st * 8, ph);
    const uint64_t da = da0 + st * (H_STAGE >> 4), db = db0 + st * (H_STAGE >> 4);
    WG_FENCE();
    h_mma<BN, TA, 0, 4>(acc, da, db);
    WG_COMMIT();
    WG_WAIT(1);
    if (leader && !wg) mbar_arrive(empty + prev * 8);
    prev = st;
    if (++st == H_NST) { st = 0; ph ^= 1; }
  }
  {
    mbar_wait(full + st * 8, ph);
    const uint64_t da = da0 + st * (H_STAGE >> 4), db = db0 + st * (H_STAGE >> 4);
    WG_FENCE();
    h_mma<BN, TA, 0, 3>(acc, da, db);
    WG_COMMIT();
    h_mma<BN, TA, 3, 4>(acc, da, db);
    WG_COMMIT();
    WG_WAIT(1);
    if (leader) mbar_arrive(empty + prev * 8);
    if (!wg) bar_arrive<NB_HX, 256>();
  }
}
__device__ __forceinline__ void h_release(uint32_t sb, uint32_t& st, uint32_t& ph, bool leader) {
  if (leader) mbar_arrive(sb + H_BAR + HB_EMPTY + st * 8);
  if (++st == H_NST) { st = 0; ph ^= 1; }
}

__device__ __forceinline__ uint32_t stg_acquire(uint32_t sb, uint32_t g, uint32_t& b) {
  const uint32_t q = (g * 43691u) >> 17;
  b = g - 3 * q;
  mbar_wait(sb + H_BAR + HB_SFREE + b * 8, (q & 1) ^ 1);
  return sb + H_STG + b * 8192;
}
__device__ __forceinline__ void stg_release(uint32_t sb, uint32_t b, int lane) {
  __syncwarp();
  if (lane == 0) mbar_arrive(sb + H_BAR + HB_SRDY + b * 8);
}
__device__ __forceinline__ uint32_t hmul2(uint32_t a, uint32_t b) { uint32_t t; asm("mul.rn.bf16x2 %0, %1, %2;" : "=r"(t) : "r"(a), "r"(b)); return t; }
template <int BN>
__device__ __forceinline__ void h_gated(float* acc, uint32_t va, uint32_t vb, uint32_t vp, uint32_t sb, uint32_t& st, uint32_t& ph, uint32_t g0, int wg, bool leader,
                                        int warp, int lane, uint32_t clk_q) {
  uint32_t gt[BN / 8];
  mbar_wait(vb, vp);
#pragma unroll
  for (int i = 0; i < BN / 32; i++) lds128(gt + 4 * i, va + i * 64 + (lane & 3) * 16);
  WG_WAIT(0);
  reg_fence<BN / 2>(acc);
  h_release(sb, st, ph, leader);
  HT(2);
  const uint32_t ro = ((warp & 3) * 16 + (lane & 7)) * 128, x0 = ((lane >> 3) ^ (lane & 7)) << 4;
  if (BN == 256 && wg) bar_sync<NB_HZ, 256>();
#pragma unroll
  for (int u = 0; u < BN / 64; u++) {
    uint32_t b;
    const uint32_t base = stg_acquire(sb, g0 + u, b) + ro;
    if (BN == 256 && u == 1 && !wg) bar_arrive<NB_HZ, 256>();
#pragma unroll
    for (int c2 = 0; c2 < 2; c2++) {
      const int c = 2 * u + c2;
#pragma unroll
      for (int h = 0; h < 2; h++) {
        uint32_t y[4];
#pragma unroll
        for (int j = 0; j < 4; j++) { const float* a = acc + c * 16 + j * 4 + h * 2; y[j] = hmul2(pack2(a[0], a[1]), gt[4 * c + j]); }
        stsm4(base + h * 1024 + (x0 ^ (c2 << 6)), y);
      }
    }
    stg_release(sb, b, lane);
  }
}

template <int BN>
__device__ __forceinline__ void h_swiglu(float* acc, uint32_t vb, uint32_t vp, uint32_t sb, uint32_t& st, uint32_t& ph, uint32_t g0, int wg, bool leader,
                                         int warp, int lane, uint32_t clk_q) {
  float rs[2], rh[2];
  mbar_wait(vb, vp);
  {
    const uint64_t da = mkdesc(sb + H_VEC + 4096 + wg * 1024, 0, 128, 0), db = mkdesc(sb + H_VEC, 1024, 0, 1);
    WG_FENCE();
    if (BN == 256) wg_ss256<0>(acc, da, db); else wg_ss128<0>(acc, da, db);
    WG_COMMIT();
  }
#pragma unroll
  for (int h = 0; h < 2; h++) { rs[h] = lds32f(sb + H_VEC + 6144 + (warp * 16 + h * 8 + (lane >> 2)) * 4); rh[h] = 0.5f * rs[h]; }
  WG_WAIT(1);
  h_release(sb, st, ph, leader);
  WG_WAIT(0);
  reg_fence<BN / 2>(acc);
  HT(2);
  const uint32_t ro = ((warp & 3) * 16 + (lane & 7)) * 128, x0 = ((lane >> 3) ^ (lane & 7)) << 4;
#pragma unroll
  for (int uu = 0; uu < BN / 128; uu++) {
    uint32_t b;
    const uint32_t base = stg_acquire(sb, g0 + uu, b) + ro;
#pragma unroll
    for (int c2 = 0; c2 < 2; c2++) {
      const int c = 2 * uu + c2;
      uint32_t y[2][4];
#pragma unroll
      for (int j = 0; j < 4; j++) {
        const float* g = acc + 16 * c + 4 * j; const float* u = g + BN / 4;
        float o[4];
#pragma unroll
        for (int e = 0; e < 4; e++) {
          const float g2 = rh[e >> 1] * g[e];
          const float h = g2 * (rs[e >> 1] * u[e]);
          float t; asm("tanh.approx.f32 %0, %1;" : "=f"(t) : "f"(g2));
          o[e] = fmaf(h, t, h);
        }
        y[0][j] = pack2(o[0], o[1]); y[1][j] = pack2(o[2], o[3]);
      }
      stsm4(base + (x0 ^ (c2 << 6)), y[0]); stsm4(base + 1024 + (x0 ^ (c2 << 6)), y[1]);
    }
    stg_release(sb, b, lane);
  }
}

template <bool WS>
__device__ __forceinline__ void h_vecmat(uint32_t sb, int idx, uint32_t& st, uint32_t& ph, int tid, const __nv_bfloat16* cvec, uint8_t* w13s, uint8_t* bext,
                                         __nv_bfloat16* mod, __nv_bfloat16* gate) {
  const uint32_t stg = sb + H_STG, bars = sb + H_BAR;
  const int lane = tid & 31, warp = tid >> 5;
#pragma unroll
  for (int i = 0; i < 4; i++) {
    const int k = tid + 256 * i;
    if (WS) {
      const uint32_t s = __ldcg(reinterpret_cast<const uint16_t*>(mod) + 3 * D_ + k), c = __ldcg(reinterpret_cast<const uint16_t*>(mod) + 4 * D_ + k);
      sts32(stg + k * 4, s << 16); sts32(stg + 4096 + k * 4, c | c << 16);
    } else {
      const float c = __bfloat162float(cvec[k]);
      sts32(stg + k * 4, __float_as_uint(__bfloat162float(__float2bfloat16(c / (1.f + __expf(-c))))));
    }
  }
  bar_sync<1, 256>();
  float v[4][8], u[4][8];
#pragma unroll
  for (int b = 0; b < 4; b++)
#pragma unroll
    for (int e = 0; e < 8; e++) { v[b][e] = 0.f; u[b][e] = 0.f; }
  const int r0 = tid >> 3;
  const uint32_t off = 16384 + r0 * 128 + (((tid & 7) ^ (r0 & 7)) << 4);
  uint32_t prev = 0;
#pragma unroll 1
  for (int i = 0; i < (WS ? 16 : 8); i++) {
    mbar_wait(bars + HB_FULL + st * 8, ph);
    const uint32_t base = sb + st * H_STAGE + off;
#pragma unroll
    for (int ri = 0; ri < 2; ri++) {
      const uint32_t ka = stg + ((WS ? i * 64 : i * 128) + r0 + 32 * ri) * 4;
      const float m0 = lds32f(ka), m1 = WS ? m0 : lds32f(ka + 256);
      const uint32_t c2 = WS ? lds32(ka + 4096) : 0;
#pragma unroll
      for (int b = 0; b < 4; b++) {
        uint32_t w[4];
        lds128(w, base + b * 8192 + ri * 4096);
        const float m = b < 2 ? m0 : m1;
#pragma unroll
        for (int e = 0; e < 4; e++) {
          v[b][2 * e] = fmaf(m, bf_lo(w[e]), v[b][2 * e]); v[b][2 * e + 1] = fmaf(m, bf_hi(w[e]), v[b][2 * e + 1]);
          if (WS) { w[e] = hfma2(w[e], c2, w[e]); u[b][2 * e] += bf_lo(w[e]); u[b][2 * e + 1] += bf_hi(w[e]); }
        }
        if (WS) sts128(base + b * 8192 + ri * 4096, w[0], w[1], w[2], w[3]);
      }
    }
    if (WS) fence_async_smem();
    bar_sync<1, 256>();
    if (tid == 0) {
      if (WS) {
        bulk_s2g(w13s + (size_t)(idx * 16 + i) * 32768, sb + st * H_STAGE + 16384, 32768);
        bulk_commit();
        if (i > 0) { bulk_wait_read<1>(); mbar_arrive_n(bars + HB_EMPTY + prev * 8, 2); }
      } else mbar_arrive_n(bars + HB_EMPTY + st * 8, 2);
    }
    prev = st;
    if (++st == H_NST) { st = 0; ph ^= 1; }
  }
  if (WS && tid == 0) {
    bulk_wait_read<0>(); mbar_arrive_n(bars + HB_EMPTY + prev * 8, 2);
    bulk_wait_all(); fence_async_all(); fence_gpu();
  }
#pragma unroll
  for (int b = 0; b < 4; b++)
#pragma unroll
    for (int e = 0; e < 8; e++) {
      v[b][e] += __shfl_xor_sync(0xffffffffu, v[b][e], 8); v[b][e] += __shfl_xor_sync(0xffffffffu, v[b][e], 16);
      if (WS) { u[b][e] += __shfl_xor_sync(0xffffffffu, u[b][e], 8); u[b][e] += __shfl_xor_sync(0xffffffffu, u[b][e], 16); }
    }
  if (lane < 8) {
#pragma unroll
    for (int b = 0; b < 4; b++) {
      const uint32_t a = stg + warp * 2048 + b * 256 + lane * 32;
      sts128(a, __float_as_uint(v[b][0]), __float_as_uint(v[b][1]), __float_as_uint(v[b][2]), __float_as_uint(v[b][3]));
      sts128(a + 16, __float_as_uint(v[b][4]), __float_as_uint(v[b][5]), __float_as_uint(v[b][6]), __float_as_uint(v[b][7]));
      if (WS) {
        sts128(a + 1024, __float_as_uint(u[b][0]), __float_as_uint(u[b][1]), __float_as_uint(u[b][2]), __float_as_uint(u[b][3]));
        sts128(a + 1040, __float_as_uint(u[b][4]), __float_as_uint(u[b][5]), __float_as_uint(u[b][6]), __float_as_uint(u[b][7]));
      }
    }
  }
  bar_sync<1, 256>();
  float sv = 0.f, su = 0.f;
#pragma unroll
  for (int i = 0; i < 8; i++) {
    sv += lds32f(stg + i * 2048 + tid * 4);
    su += WS ? lds32f(stg + i * 2048 + 1024 + tid * 4) : lds32f(stg + i * 2048 + (tid ^ 128) * 4);
  }
  if (WS) {
    const __nv_bfloat16 uh = __float2bfloat16(su), ul = __float2bfloat16(su - __bfloat162float(uh));
    const __nv_bfloat16 vh = __float2bfloat16(sv), vl = __float2bfloat16(sv - __bfloat162float(vh)), z = __float2bfloat16(0.f);
    uint8_t* p = bext + idx * 4096 + (tid >> 6) * 1024 + (tid & 7) * 2;
#pragma unroll
    for (int r = 0; r < 8; r++)
      *reinterpret_cast<__nv_bfloat16*>(p + r * 128 + ((((tid & 63) >> 3) ^ r) << 4)) = r == 0 || r == 2 ? uh : r == 1 ? ul : r == 3 || r == 5 ? vh : r == 4 ? vl : z;
  } else if (tid < 128) {
    const int n = idx * 128 + tid, vec = n >> 10, col = n & 1023;
    const __nv_bfloat16 r = __float2bfloat16(sv + su);
    mod[2048 + n] = r;
    if (vec == 0 || vec == 3) gate[(vec ? D_ : 0) + (col & ~31) + ((col >> 1) & 3) * 8 + ((col >> 3) & 3) * 2 + (col & 1)] = r;
  }
}

__global__ void __launch_bounds__(384, 1)
kernel_H(const __grid_constant__ CUtensorMap tmo, const __grid_constant__ CUtensorMap tm1, const __grid_constant__ CUtensorMap tm3,
         const __grid_constant__ CUtensorMap tm2, const __grid_constant__ CUtensorMap tmm, const __grid_constant__ CUtensorMap tmx,
         const __grid_constant__ CUtensorMap tmy, const __nv_bfloat16* __restrict__ x, const __nv_bfloat16* __restrict__ cvec, __nv_bfloat16* out, const __grid_constant__ HList list) {
  extern __shared__ __align__(1024) uint8_t smem[];
  constexpr uint32_t sb = 0x400, bars = sb + H_BAR;
  const int tid = threadIdx.x, lane = tid & 31;
  const int warp = __shfl_sync(0xffffffffu, tid >> 5, 0);
  if (tid == 0) {
    if (smem_u32(smem) != sb) __trap();
    for (int i = 0; i < H_NST; i++) { mbar_init(bars + HB_FULL + i * 8, 1); mbar_init(bars + HB_EMPTY + i * 8, 2); }
    for (int i = 0; i < 2; i++) { mbar_init(bars + HB_IFULL + i * 8, 1); mbar_init(bars + HB_IEMPTY + i * 8, 1); mbar_init(bars + HB_VFULL + i * 8, 1); }
    for (int i = 0; i < 3; i++) { mbar_init(bars + HB_SRDY + i * 8, 4); mbar_init(bars + HB_SFREE + i * 8, 1); }
    mbar_init(bars + HB_STGF, 1);
    fence_async_smem();
  }
  __syncthreads();
  if (warp >= 8) {
    asm volatile("setmaxnreg.dec.sync.aligned.u32 40;");
    if (warp == 8) {
      uint32_t st = 0, ph = 1, nv = 0, q = 0;
      if (lane == 0) q = atomicAdd(&g_flags[FL_HEAD], 1);
#pragma unroll 1
      for (uint32_t n = 0;; n++) {
        q = __shfl_sync(0xffffffffu, q, 0);
        const uint32_t it = q < list.n ? list.it[q] : 0;
        const int type = it & 7, mt = (it >> 3) & 15, idx = (it >> 7) & 63, sz = (it >> 13) & 3, kb0 = (it >> 15) & 63, nkb = (it >> 21) & 127;
        {
          int f = FL_GO; uint32_t target = 0;
          if (type == IT_OUT) { f = lane == 0 ? FL_ATT + 8 * mt : lane == 1 ? FL_XT + 8 * mt : FL_MOD; target = lane == 0 ? 64 : lane == 1 ? N_XT : N_MOD; }
          else if (type == IT_F1) { f = lane == 0 ? FL_OUT + 8 * mt : FL_WS; target = lane == 0 ? 1024 : N_WS; }
          else if (type == IT_F2) { f = FL_F1 + 8 * mt; target = 56; }
          else if (type == IT_STAT) { f = FL_OUT + 8 * mt; target = 1024; }
          else if (type == IT_WS) { f = FL_MOD; target = N_MOD; }
          else if (type != IT_END) target = 1;
          if (lane < 3) wait_flag(&g_flags[f], target);
          __syncwarp();
          asm volatile("fence.proxy.async.global;" ::: "memory");
        }
        mbar_wait(bars + HB_IEMPTY + (n & 1) * 8, ((n >> 1) & 1) ^ 1);
        if (elect_one()) {
          sts32(bars + HB_ITEM + (n & 1) * 4, it);
          mbar_arrive(bars + HB_IFULL + (n & 1) * 8);
        }
        if (type == IT_END) break;
        const bool gemm = type == IT_OUT || type == IT_F1 || type == IT_F2;
        const int nst = gemm ? nkb : type == IT_WS ? 16 : type == IT_MOD ? 8 : 0;
        const int bn = 256 >> sz;
        const uint8_t* ap = type == IT_OUT ? g_att + (size_t)mt * 64 * 16384 : g_act + (size_t)mt * 56 * 16384;
        const uint8_t* wp = g_w13s + (size_t)(idx >> sz) * 16 * 32768 + (sz ? (idx & 1) * 8192 : 0);
        const CUtensorMap* tb = type == IT_OUT ? &tmo : type == IT_F2 ? &tm2 : type == IT_WS ? &tm1 : &tmm;
        const CUtensorMap* tc = type == IT_WS ? &tm3 : tb;
        const int c0 = gemm ? idx * bn : type == IT_WS ? idx * 128 : 2048 + idx * 128, dcol = gemm ? 128 : 0, kmul = type == IT_MOD ? 128 : 64, drow = type == IT_MOD ? 64 : 0;
        const uint32_t bytes = gemm ? 16384 + bn * 128 : 32768;
        const uint64_t pa = type == IT_OUT ? POL_ATT : POL_ACT, pb = type == IT_OUT ? POL_WO : type == IT_F2 ? POL_W2 : POL_PRE;
        if (nst < 2 && lane == 0) q = atomicAdd(&g_flags[FL_HEAD], 1);
#pragma unroll 1
        for (int i = 0; i < nst; i++) {
          const int kb = kb0 + i;
          const uint32_t d = sb + st * H_STAGE, fb = bars + HB_FULL + st * 8;
          if (i == nst - 2 && lane == 0) q = atomicAdd(&g_flags[FL_HEAD], 1);
          mbar_wait(bars + HB_EMPTY + st * 8, ph);
          if (elect_one()) {
            mbar_expect(fb, bytes);
            if (type == IT_F1) {
              tma2d(d, &tmx, kb * 64, mt * 128, fb);
              if (sz == 0) bulk_g2s(d + 16384, wp + (size_t)kb * 32768, 32768, fb);
              else { bulk_g2s(d + 16384, wp + (size_t)kb * 32768, 8192, fb); bulk_g2s(d + 24576, wp + (size_t)kb * 32768 + 16384, 8192, fb); }
            } else {
              if (gemm) bulk_g2s_p(d, ap + (size_t)kb * 16384, 16384, fb, pa);
              tma2d_p(d + 16384, tb, c0, kb * kmul, fb, pb);
              tma2d_p(d + 24576, tb, c0 + 64, kb * kmul, fb, pb);
              if (sz == 0) { tma2d_p(d + 32768, tc, c0 + dcol, kb * kmul + drow, fb, pb); tma2d_p(d + 40960, tc, c0 + dcol + 64, kb * kmul + drow, fb, pb); }
            }
          }
          if (++st == H_NST) { st = 0; ph ^= 1; }
        }
        if (gemm) {
          if (type == IT_F1) {
            if (lane == 0) wait_flag(&g_flags[FL_STAT + 8 * mt], N_STAT);
            __syncwarp();
            asm volatile("fence.proxy.async.global;" ::: "memory");
          }
          if (elect_one()) {
            const uint32_t v = sb + H_VEC, fb = bars + HB_VFULL + (nv & 1) * 8;
            if (type == IT_F1) {
              mbar_expect(fb, (4096 >> sz) + 2560);
              if (sz == 0) bulk_g2s(v, g_bext + idx * 4096, 4096, fb);
              else { const uint8_t* p = g_bext + (idx >> 1) * 4096 + (idx & 1) * 1024; bulk_g2s(v, p, 1024, fb); bulk_g2s(v + 1024, p + 2048, 1024, fb); }
              bulk_g2s(v + 4096, g_ext + mt * 2560, 2560, fb);
            } else {
              mbar_expect(fb, bn * 2);
              bulk_g2s(sb + H_GATE + (nv & 1) * 512, g_gate + (type == IT_F2 ? D_ : 0) + c0, bn * 2, fb);
            }
          }
          nv++;
        }
      }
    } else if (warp == 9) {
      uint32_t g = 0;
#pragma unroll 1
      for (uint32_t n = 0;; n++) {
        mbar_wait(bars + HB_IFULL + (n & 1) * 8, (n >> 1) & 1);
        const uint32_t it = lds32(bars + HB_ITEM + (n & 1) * 4);
        const int type = it & 7, mt = (it >> 3) & 15, idx = (it >> 7) & 63, sz = (it >> 13) & 3, nkb = (it >> 21) & 127;
        if (type == IT_END) break;
        const bool gated = type == IT_OUT || type == IT_F2, gemm = gated || type == IT_F1;
        if (!gemm) { if (n & 1) bar_sync<3, 288>(); else bar_sync<2, 288>(); }
        if (lane == 0) {
          if (gemm) {
            const int nu = (gated ? 4 : 2) >> sz;
            uint32_t pb = 0;
#pragma unroll 1
            for (int u = 0; u < 2 * nu; u++, g++) {
              const uint32_t r = (g * 43691u) >> 17, b = g - 3 * r, src = sb + H_STG + b * 8192;
              const int w = u >= nu, uu = u - w * nu;
              mbar_wait(bars + HB_SRDY + b * 8, r & 1);
              if (u == 2 * nu - 1) mbar_arrive(bars + HB_IEMPTY + (n & 1) * 8);
              fence_async_smem();
              if (gated) tma2d_add(&tmy, idx * (256 >> sz) + uu * 64, mt * 128 + w * 64, src);
              else bulk_s2g(g_act + (size_t)(mt * 56 + idx * nu + uu) * 16384 + w * 8192, src, 8192);
              bulk_commit();
              if (u > 0) { bulk_wait_read<1>(); mbar_arrive(bars + HB_SFREE + pb * 8); }
              pb = b;
            }
            bulk_wait_read<0>();
            mbar_arrive(bars + HB_SFREE + pb * 8);
            mbar_arrive(bars + HB_STGF);
            bulk_wait_all(); fence_async_all();
          } else {
            mbar_arrive(bars + HB_STGF);
            mbar_arrive(bars + HB_IEMPTY + (n & 1) * 8);
          }
          if (type != IT_F2) {
            const uint32_t inc = type == IT_OUT ? (4 >> sz) * nkb : type == IT_F1 ? 2 >> sz : 1;
            fence_gpu();
            red_add_u32(&g_flags[type == IT_MOD ? FL_MOD : type == IT_WS ? FL_WS :
                                 (type == IT_XT ? FL_XT : type == IT_OUT ? FL_OUT : type == IT_STAT ? FL_STAT : FL_F1) + 8 * mt], inc);
          }
        }
        __syncwarp();
      }
      asm volatile("griddepcontrol.wait;" ::: "memory");
      uint32_t k = 0;
      if (lane == 0) { fence_gpu(); k = atomicAdd(&g_flags[FL_EXIT], 1); }
      k = __shfl_sync(0xffffffffu, k, 0);
      if (k == gridDim.x - 1) {
        fence_gpu();
        for (int i = lane; i < 1024; i += 32) g_flags[i] = 0;
      }
    }
  } else {
    asm volatile("setmaxnreg.inc.sync.aligned.u32 232;");
    const int wg = warp >> 2;
    const bool leader = (tid & 127) == 0;
    uint32_t st = 0, ph = 0, nv = 0, g = 0;
#pragma unroll 1
    for (uint32_t n = 0;; n++) {
      mbar_wait(bars + HB_IFULL + (n & 1) * 8, (n >> 1) & 1);
      const uint32_t it = __shfl_sync(0xffffffffu, lds32(bars + HB_ITEM + (n & 1) * 4), 0);
      const int type = it & 7, mt = (it >> 3) & 15, idx = (it >> 7) & 63, sz = (it >> 13) & 3, nkb = (it >> 21) & 127;
      if (type == IT_END) break;
      constexpr uint32_t clk_q = 0;
      if (type == IT_OUT || type == IT_F1 || type == IT_F2) {
        const uint32_t va = sb + H_GATE + (nv & 1) * 512, vb = bars + HB_VFULL + (nv & 1) * 8, vp = (nv >> 1) & 1;
        const uint32_t nu = (type == IT_F1 ? 2 : 4) >> sz, g0 = g + wg * nu;
        nv++; g += 2 * nu;
        if (sz == 0) {
          float acc[128];
          if (type == IT_OUT) h_mainloop<256, 1>(acc, sb, nkb, st, ph, wg, leader, clk_q);
          else h_mainloop<256, 0>(acc, sb, nkb, st, ph, wg, leader, clk_q);
          if (type == IT_F1) h_swiglu<256>(acc, vb, vp, sb, st, ph, g0, wg, leader, warp, lane, clk_q);
          else h_gated<256>(acc, va, vb, vp, sb, st, ph, g0, wg, leader, warp, lane, clk_q);
        } else {
          float acc[64];
          if (type == IT_OUT) h_mainloop<128, 1>(acc, sb, nkb, st, ph, wg, leader, clk_q);
          else h_mainloop<128, 0>(acc, sb, nkb, st, ph, wg, leader, clk_q);
          if (type == IT_F1) h_swiglu<128>(acc, vb, vp, sb, st, ph, g0, wg, leader, warp, lane, clk_q);
          else h_gated<128>(acc, va, vb, vp, sb, st, ph, g0, wg, leader, warp, lane, clk_q);
        }
        HT(3);
        continue;
      } else if (type == IT_XT) {
        const uint4* xp = reinterpret_cast<const uint4*>(x + (size_t)(mt * 128 + idx * 64) * D_) + tid;
        uint4* op = reinterpret_cast<uint4*>(out + (size_t)(mt * 128 + idx * 64) * D_) + tid;
#pragma unroll 1
        for (int b = 0; b < 2; b++) {
          uint4 v[16];
#pragma unroll
          for (int i = 0; i < 16; i++) v[i] = __ldcs(xp + (b * 16 + i) * 256);
#pragma unroll
          for (int i = 0; i < 16; i++) op[(b * 16 + i) * 256] = v[i];
        }
      } else if (type == IT_STAT) {
        const int row0 = mt * 128 + idx * 32 + warp * 4;
        const uint4* xp = reinterpret_cast<const uint4*>(out + (size_t)row0 * D_) + lane;
        uint4 v[16];
#pragma unroll
        for (int i = 0; i < 16; i++) v[i] = __ldcg(xp + (i >> 2) * 128 + (i & 3) * 32);
        float s[4], m[4];
#pragma unroll
        for (int r = 0; r < 4; r++) {
          s[r] = 0.f;
#pragma unroll
          for (int i = 0; i < 4; i++) {
            const uint4 w = v[4 * r + i];
            s[r] += ((bf_lo(w.x) + bf_hi(w.x)) + (bf_lo(w.y) + bf_hi(w.y))) + ((bf_lo(w.z) + bf_hi(w.z)) + (bf_lo(w.w) + bf_hi(w.w)));
          }
        }
#pragma unroll
        for (int o = 1; o < 32; o <<= 1)
#pragma unroll
          for (int r = 0; r < 4; r++) s[r] += __shfl_xor_sync(0xffffffffu, s[r], o);
#pragma unroll
        for (int r = 0; r < 4; r++) {
          m[r] = s[r] * (1.f / D_);
          float a = 0.f, b = 0.f;
#pragma unroll
          for (int i = 0; i < 4; i++) {
            const uint4 w = v[4 * r + i];
            const uint32_t ww[4] = {w.x, w.y, w.z, w.w};
#pragma unroll
            for (int e = 0; e < 4; e++) { const float p = bf_lo(ww[e]) - m[r], t = bf_hi(ww[e]) - m[r]; a = fmaf(p, p, a); b = fmaf(t, t, b); }
          }
          s[r] = a + b;
        }
#pragma unroll
        for (int o = 1; o < 32; o <<= 1)
#pragma unroll
          for (int r = 0; r < 4; r++) s[r] += __shfl_xor_sync(0xffffffffu, s[r], o);
        if (lane < 4) {
          const float sr = lane == 0 ? s[0] : lane == 1 ? s[1] : lane == 2 ? s[2] : s[3], mr = lane == 0 ? m[0] : lane == 1 ? m[1] : lane == 2 ? m[2] : m[3];
          const float var = sr * (1.f / D_) + 1e-5f, rs = rsqrtf(var);
          const float a = -0.5f * mr, b = 0.5f * var * rs;
          const float ah = __bfloat162float(__float2bfloat16(a)), bh = __bfloat162float(__float2bfloat16(b));
          const int r = (row0 & 127) + lane;
          *reinterpret_cast<uint4*>(g_ext + mt * 2560 + r * 16) = make_uint4(pack2(ah, ah), pack2(a - ah, bh), pack2(bh, b - bh), 0u);
          *reinterpret_cast<float*>(g_ext + mt * 2560 + 2048 + r * 4) = rs;
        }
      } else {
        mbar_wait(bars + HB_STGF, (n & 1) ^ 1);
        if (type == IT_WS) h_vecmat<true>(sb, idx, st, ph, tid, cvec, g_w13s, g_bext, g_mod, g_gate);
        else h_vecmat<false>(sb, idx, st, ph, tid, cvec, g_w13s, g_bext, g_mod, g_gate);
      }
      HT(3);
      if (n & 1) bar_arrive<3, 288>(); else bar_arrive<2, 288>();
    }
  }
}

const uint32_t h_items[] = {
  0x1, 0x81, 0x101, 0x181, 0x201, 0x281, 0x301, 0x381, 0x401, 0x481, 0x501, 0x581, 0x601, 0x681,
  0x701, 0x781, 0x801, 0x881, 0x901, 0x981, 0xa01, 0xa81, 0xb01, 0xb81, 0xc01, 0xc81, 0xd01, 0xd81,
  0xe01, 0xe81, 0xf01, 0xf81, 0x2, 0x82, 0xa, 0x8a, 0x12, 0x92, 0x1a, 0x9a, 0x22, 0xa2,
  0x2a, 0xaa, 0x32, 0xb2, 0x3a, 0xba, 0x4, 0x84, 0x104, 0x184, 0x42, 0xc2, 0x4a, 0xca,
  0x52, 0xd2, 0x5a, 0xda, 0x62, 0xe2, 0x6a, 0xea, 0x72, 0xf2, 0x7a, 0xfa, 0x204, 0x284,
  0x304, 0x384, 0x404, 0x484, 0x504, 0x584, 0x604, 0x684, 0x704, 0x784, 0x804, 0x884, 0x904, 0x984,
  0xa04, 0xa84, 0xb04, 0xb84, 0xc04, 0xc84, 0xd04, 0xd84, 0x1000003, 0x1000083, 0x1000103, 0x1000183, 0x1040003, 0x1040083,
  0x1040103, 0x1040183, 0x1080003, 0x1080083, 0x1080103, 0x1080183, 0x10c0003, 0x10c0083, 0x10c0103, 0x10c0183, 0x1100003, 0x1100083, 0x1100103, 0x1100183,
  0x1140003, 0x1140083, 0x1140103, 0x1140183, 0x1180003, 0x1180083, 0x1180103, 0x1180183, 0x11c0003, 0x11c0083, 0x11c0103, 0x11c0183, 0x400000b, 0x400008b,
  0x400010b, 0x400018b, 0x410000b, 0x410008b, 0x410010b, 0x410018b, 0x7, 0x87, 0x107, 0x187, 0x2000005, 0x2000085, 0x2000105, 0x2000185,
  0x2000205, 0x2000285, 0x2000305, 0x2000385, 0x2000405, 0x2000485, 0x2000505, 0x2000585, 0x2000605, 0x2000685, 0x2000705, 0x2000785, 0x2000805, 0x2000885,
  0x2000905, 0x2000985, 0x2000a05, 0x2000a85, 0x2000b05, 0x2000b85, 0x2000c05, 0x2000c85, 0x2000d05, 0x2000d85, 0x4000013, 0x4000093, 0x4000113, 0x4000193,
  0x4100013, 0x4100093, 0x4100113, 0x4100193, 0x3800006, 0x3800086, 0x3800106, 0x3800186, 0x38e0006, 0x38e0086, 0x38e0106, 0x38e0186, 0xf, 0x8f,
  0x10f, 0x18f, 0x200000d, 0x200008d, 0x200010d, 0x200018d, 0x200020d, 0x200028d, 0x200030d, 0x200038d, 0x200040d, 0x200048d, 0x200050d, 0x200058d,
  0x200060d, 0x200068d, 0x200070d, 0x200078d, 0x200080d, 0x200088d, 0x200090d, 0x200098d, 0x400001b, 0x400009b, 0x400011b, 0x400019b, 0x410001b, 0x410009b,
  0x410011b, 0x410019b, 0x2000a0d, 0x2000a8d, 0x2000b0d, 0x2000b8d, 0x2000c0d, 0x2000c8d, 0x2000d0d, 0x2000d8d, 0x17, 0x97, 0x117, 0x197,
  0x2000015, 0x2000095, 0x2000115, 0x2000195, 0x2000215, 0x2000295, 0x2000315, 0x2000395, 0x2000415, 0x2000495, 0x2000515, 0x2000595, 0x2000615, 0x2000695,
  0x2000715, 0x2000795, 0x2000815, 0x2000895, 0x2000915, 0x2000995, 0x4000023, 0x40000a3, 0x4000123, 0x40001a3, 0x4100023, 0x41000a3, 0x4100123, 0x41001a3,
  0x2000a15, 0x2000a95, 0x2000b15, 0x2000b95, 0x2000c15, 0x2000c95, 0x2000d15, 0x2000d95, 0x380000e, 0x380008e, 0x380010e, 0x380018e, 0x38e000e, 0x38e008e,
  0x38e010e, 0x38e018e, 0x400002b, 0x40000ab, 0x400012b, 0x40001ab, 0x410002b, 0x41000ab, 0x410012b, 0x41001ab, 0x1f, 0x9f, 0x11f, 0x19f,
  0x200001d, 0x200009d, 0x200011d, 0x200019d, 0x200021d, 0x200029d, 0x200031d, 0x200039d, 0x200041d, 0x200049d, 0x200051d, 0x200059d, 0x200061d, 0x200069d,
  0x200071d, 0x200079d, 0x200081d, 0x200089d, 0x200091d, 0x200099d, 0x2000a1d, 0x2000a9d, 0x2000b1d, 0x2000b9d, 0x2000c1d, 0x2000c9d, 0x2000d1d, 0x2000d9d,
  0x27, 0xa7, 0x127, 0x1a7, 0x4000033, 0x40000b3, 0x4000133, 0x40001b3, 0x4100033, 0x41000b3, 0x4100133, 0x41001b3, 0x2000025, 0x20000a5,
  0x2000125, 0x20001a5, 0x2000225, 0x20002a5, 0x2000325, 0x20003a5, 0x2000425, 0x20004a5, 0x2000525, 0x20005a5, 0x2000625, 0x20006a5, 0x2000725, 0x20007a5,
  0x2000825, 0x20008a5, 0x2000925, 0x20009a5, 0x2000a25, 0x2000aa5, 0x2000b25, 0x2000ba5, 0x2000c25, 0x2000ca5, 0x2000d25, 0x2000da5, 0x2f, 0xaf,
  0x12f, 0x1af, 0x400003b, 0x40000bb, 0x400013b, 0x40001bb, 0x410003b, 0x41000bb, 0x410013b, 0x41001bb, 0x200002d, 0x20000ad, 0x200012d, 0x20001ad,
  0x200022d, 0x20002ad, 0x200032d, 0x20003ad, 0x200042d, 0x20004ad, 0x200052d, 0x20005ad, 0x200062d, 0x20006ad, 0x200072d, 0x20007ad, 0x200082d, 0x20008ad,
  0x200092d, 0x20009ad, 0x2000a2d, 0x2000aad, 0x2000b2d, 0x2000bad, 0x2000c2d, 0x2000cad, 0x2000d2d, 0x2000dad, 0x37, 0xb7, 0x137, 0x1b7,
  0x4000043, 0x40000c3, 0x4000143, 0x40001c3, 0x2000035, 0x20000b5, 0x2000135, 0x20001b5, 0x2000235, 0x20002b5, 0x2000335, 0x20003b5, 0x4100043, 0x41000c3,
  0x4100143, 0x41001c3, 0x2000435, 0x20004b5, 0x2000535, 0x20005b5, 0x2000635, 0x20006b5, 0x2000735, 0x20007b5, 0x2000835, 0x20008b5, 0x2000935, 0x20009b5,
  0x2000a35, 0x2000ab5, 0x2000b35, 0x2000bb5, 0x2000c35, 0x2000cb5, 0x2000d35, 0x2000db5, 0x3800016, 0x3800096, 0x3800116, 0x3800196, 0x38e0016, 0x38e0096,
  0x38e0116, 0x38e0196, 0x3f, 0xbf, 0x13f, 0x1bf, 0x200003d, 0x20000bd, 0x200013d, 0x20001bd, 0x200023d, 0x20002bd, 0x200033d, 0x20003bd,
  0x200043d, 0x20004bd, 0x200053d, 0x20005bd, 0x400004b, 0x40000cb, 0x400014b, 0x40001cb, 0x410004b, 0x41000cb, 0x410014b, 0x41001cb, 0x200063d, 0x20006bd,
  0x200073d, 0x20007bd, 0x200083d, 0x20008bd, 0x200093d, 0x20009bd, 0x47, 0xc7, 0x147, 0x1c7, 0x2000a3d, 0x2000abd, 0x2000b3d, 0x2000bbd,
  0x2000c3d, 0x2000cbd, 0x2000d3d, 0x2000dbd, 0x2000045, 0x20000c5, 0x2000145, 0x20001c5, 0x2000245, 0x20002c5, 0x2000345, 0x20003c5, 0x2000445, 0x20004c5,
  0x2000545, 0x20005c5, 0x4000053, 0x40000d3, 0x4000153, 0x40001d3, 0x4100053, 0x41000d3, 0x4100153, 0x41001d3, 0x2000645, 0x20006c5, 0x2000745, 0x20007c5,
  0x2000845, 0x20008c5, 0x2000945, 0x20009c5, 0x2000a45, 0x2000ac5, 0x2000b45, 0x2000bc5, 0x2000c45, 0x2000cc5, 0x2000d45, 0x2000dc5, 0x380001e, 0x380009e,
  0x380011e, 0x380019e, 0x38e001e, 0x38e009e, 0x38e011e, 0x38e019e, 0x3800026, 0x38000a6, 0x3800126, 0x38001a6, 0x4f, 0xcf, 0x14f, 0x1cf,
  0x400005b, 0x40000db, 0x400015b, 0x40001db, 0x410005b, 0x41000db, 0x410015b, 0x41001db, 0x200004d, 0x20000cd, 0x200014d, 0x20001cd, 0x200024d, 0x20002cd,
  0x200034d, 0x20003cd, 0x200044d, 0x20004cd, 0x200054d, 0x20005cd, 0x200064d, 0x20006cd, 0x200074d, 0x20007cd, 0x57, 0xd7, 0x157, 0x1d7,
  0x200084d, 0x20008cd, 0x200094d, 0x20009cd, 0x2000a4d, 0x2000acd, 0x2000b4d, 0x2000bcd, 0x4000063, 0x40000e3, 0x4000163, 0x40001e3, 0x4100063, 0x41000e3,
  0x4100163, 0x41001e3, 0x2000c4d, 0x2000ccd, 0x2000d4d, 0x2000dcd, 0x2000055, 0x20000d5, 0x2000155, 0x20001d5, 0x2000255, 0x20002d5, 0x2000355, 0x20003d5,
  0x2000455, 0x20004d5, 0x2000555, 0x20005d5, 0x2000655, 0x20006d5, 0x2000755, 0x20007d5, 0x2000855, 0x20008d5, 0x2000955, 0x20009d5, 0x2000a55, 0x2000ad5,
  0x2000b55, 0x2000bd5, 0x2000c55, 0x2000cd5, 0x2000d55, 0x2000dd5, 0x5f, 0xdf, 0x15f, 0x1df, 0x200006b, 0x20000eb, 0x200016b, 0x20001eb,
  0x208006b, 0x20800eb, 0x208016b, 0x20801eb, 0x210006b, 0x21000eb, 0x210016b, 0x21001eb, 0x218006b, 0x21800eb, 0x218016b, 0x21801eb, 0x200005d, 0x20000dd,
  0x200015d, 0x20001dd, 0x200025d, 0x20002dd, 0x200035d, 0x20003dd, 0x200045d, 0x20004dd, 0x200055d, 0x20005dd, 0x200065d, 0x20006dd, 0x200075d, 0x20007dd,
  0x200085d, 0x20008dd, 0x200095d, 0x20009dd, 0x67, 0xe7, 0x167, 0x1e7, 0x2000073, 0x20000f3, 0x2000173, 0x20001f3, 0x2080073, 0x20800f3,
  0x2080173, 0x20801f3, 0x2100073, 0x21000f3, 0x2100173, 0x21001f3, 0x2180073, 0x21800f3, 0x2180173, 0x21801f3, 0x2000a5d, 0x2000add, 0x2000b5d, 0x2000bdd,
  0x2000c5d, 0x2000cdd, 0x2000d5d, 0x2000ddd, 0x2000065, 0x20000e5, 0x2000165, 0x20001e5, 0x2000265, 0x20002e5, 0x2000365, 0x20003e5, 0x6f, 0xef,
  0x16f, 0x1ef, 0x2000465, 0x20004e5, 0x2000565, 0x20005e5, 0x2000665, 0x20006e5, 0x2000765, 0x20007e5, 0x2000865, 0x20008e5, 0x2000965, 0x20009e5,
  0x2000a65, 0x2000ae5, 0x2000b65, 0x2000be5, 0x100207b, 0x10020fb, 0x100217b, 0x10021fb, 0x100227b, 0x10022fb, 0x100237b, 0x10023fb, 0x104207b, 0x10420fb,
  0x104217b, 0x10421fb, 0x104227b, 0x10422fb, 0x104237b, 0x10423fb, 0x108207b, 0x10820fb, 0x108217b, 0x10821fb, 0x108227b, 0x10822fb, 0x108237b, 0x10823fb,
  0x10c207b, 0x10c20fb, 0x10c217b, 0x10c21fb, 0x10c227b, 0x10c22fb, 0x10c237b, 0x10c23fb, 0x110207b, 0x11020fb, 0x110217b, 0x11021fb, 0x110227b, 0x11022fb,
  0x110237b, 0x11023fb, 0x114207b, 0x11420fb, 0x114217b, 0x11421fb, 0x114227b, 0x11422fb, 0x114237b, 0x11423fb, 0x118207b, 0x11820fb, 0x118217b, 0x11821fb,
  0x77, 0xf7, 0x177, 0x1f7, 0x118227b, 0x11822fb, 0x118237b, 0x11823fb, 0x11c207b, 0x11c20fb, 0x11c217b, 0x11c21fb, 0x11c227b, 0x11c22fb,
  0x11c237b, 0x11c23fb, 0x2000c65, 0x2000ce5, 0x2000d65, 0x2000de5, 0x200006d, 0x20000ed, 0x200016d, 0x20001ed, 0x200026d, 0x20002ed, 0x200036d, 0x20003ed,
  0x200046d, 0x20004ed, 0x200056d, 0x20005ed, 0x200066d, 0x20006ed, 0x200076d, 0x20007ed, 0x200086d, 0x20008ed, 0x200096d, 0x20009ed, 0x2000a6d, 0x2000aed,
  0x2000b6d, 0x2000bed, 0x2000c6d, 0x2000ced, 0x2000d6d, 0x2000ded, 0x1ce0026, 0x1ce00a6, 0x1ce0126, 0x1ce01a6, 0x1d50026, 0x1d500a6, 0x1d50126, 0x1d501a6,
  0x2000075, 0x20000f5, 0x2000175, 0x20001f5, 0x1c0002e, 0x1c000ae, 0x1c0012e, 0x1c001ae, 0x2000275, 0x20002f5, 0x2000375, 0x20003f5, 0x1c7002e, 0x1c700ae,
  0x2000475, 0x20004f5, 0x2000575, 0x20005f5, 0x2000675, 0x20006f5, 0x2000775, 0x20007f5, 0x2000875, 0x20008f5, 0x2000975, 0x20009f5, 0x2000a75, 0x2000af5,
  0x2000b75, 0x2000bf5, 0x2000c75, 0x2000cf5, 0x2000d75, 0x2000df5, 0x1c7012e, 0x1c701ae, 0x1ce002e, 0x1ce00ae, 0x1ce012e, 0x1ce01ae, 0x1d5002e, 0x1d500ae,
  0x1d5012e, 0x1d501ae, 0x1c00036, 0x1c000b6, 0x1c00136, 0x1c001b6, 0x1c70036, 0x1c700b6, 0x1c70136, 0x1c701b6, 0x1ce0036, 0x1ce00b6, 0x1ce0136, 0x1ce01b6,
  0x1d50036, 0x1d500b6, 0x1d50136, 0x1d501b6, 0x1c0003e, 0x1c000be, 0x1c0013e, 0x1c001be, 0x1c7003e, 0x1c700be, 0x1c7013e, 0x1c701be, 0x1ce003e, 0x1ce00be,
  0x1ce013e, 0x1ce01be, 0x1d5003e, 0x1d500be, 0x1d5013e, 0x1d501be, 0x1c00046, 0x1c000c6, 0x1c00146, 0x1c001c6, 0x7f, 0xff, 0x17f, 0x1ff,
  0x200207d, 0x20020fd, 0x200217d, 0x20021fd, 0x200227d, 0x20022fd, 0x200237d, 0x20023fd, 0x200247d, 0x20024fd, 0x200257d, 0x20025fd, 0x200267d, 0x20026fd,
  0x200277d, 0x20027fd, 0x200287d, 0x20028fd, 0x200297d, 0x20029fd, 0x2002a7d, 0x2002afd, 0x2002b7d, 0x2002bfd, 0x2002c7d, 0x2002cfd, 0x2002d7d, 0x2002dfd,
  0x2002e7d, 0x2002efd, 0x2002f7d, 0x2002ffd, 0x200307d, 0x20030fd, 0x200317d, 0x20031fd, 0x200327d, 0x20032fd, 0x200337d, 0x20033fd, 0x200347d, 0x20034fd,
  0x200357d, 0x20035fd, 0x200367d, 0x20036fd, 0x200377d, 0x20037fd, 0x200387d, 0x20038fd, 0x200397d, 0x20039fd, 0x2003a7d, 0x2003afd, 0x2003b7d, 0x2003bfd,
  0x1c70046, 0x1c700c6, 0x1c70146, 0x1c701c6, 0x1ce0046, 0x1ce00c6, 0x1ce0146, 0x1ce01c6, 0x1d50046, 0x1d500c6, 0x1d50146, 0x1d501c6, 0x1c0004e, 0x1c000ce,
  0x1c0014e, 0x1c001ce, 0x1c7004e, 0x1c700ce, 0x1c7014e, 0x1c701ce, 0x1ce004e, 0x1ce00ce, 0x1ce014e, 0x1ce01ce, 0x1d5004e, 0x1d500ce, 0x1d5014e, 0x1d501ce,
  0x1c00056, 0x1c000d6, 0x1c00156, 0x1c001d6, 0x1c70056, 0x1c700d6, 0x1c70156, 0x1c701d6, 0x1ce0056, 0x1ce00d6, 0x1ce0156, 0x1ce01d6, 0x1d50056, 0x1d500d6,
  0x1d50156, 0x1d501d6, 0x1c0005e, 0x1c000de, 0x1c0015e, 0x1c001de, 0x1c7005e, 0x1c700de, 0x1c7015e, 0x1c701de, 0x1ce005e, 0x1ce00de, 0x1ce015e, 0x1ce01de,
  0x1d5005e, 0x1d500de, 0x1d5015e, 0x1d501de, 0x1c00066, 0x1c000e6, 0x1c00166, 0x1c001e6, 0x1c70066, 0x1c700e6, 0x1c70166, 0x1c701e6, 0x1ce0066, 0x1ce00e6,
  0x1ce0166, 0x1ce01e6, 0x1d50066, 0x1d500e6, 0x1d50166, 0x1d501e6, 0x1c0006e, 0x1c000ee, 0x1c0016e, 0x1c001ee, 0x1c7006e, 0x1c700ee, 0x1c7016e, 0x1c701ee,
  0x1ce006e, 0x1ce00ee, 0x1ce016e, 0x1ce01ee, 0x1d5006e, 0x1d500ee, 0x1d5016e, 0x1d501ee, 0x1c00076, 0x1c000f6, 0x1c00176, 0x1c001f6, 0x1c70076, 0x1c700f6,
  0x1c70176, 0x1c701f6, 0x1ce0076, 0x1ce00f6, 0x1ce0176, 0x1ce01f6, 0x1d50076, 0x1d500f6, 0x1d50176, 0x1d501f6, 0xe0207e, 0xe020fe, 0xe0217e, 0xe021fe,
  0xe0227e, 0xe022fe, 0xe0237e, 0xe023fe, 0xe3a07e, 0xe3a0fe, 0xe3a17e, 0xe3a1fe, 0xe3a27e, 0xe3a2fe, 0xe3a37e, 0xe3a3fe, 0xe7207e, 0xe720fe,
  0xe7217e, 0xe721fe, 0xe7227e, 0xe722fe, 0xe7237e, 0xe723fe, 0xeaa07e, 0xeaa0fe, 0xeaa17e, 0xeaa1fe, 0xeaa27e, 0xeaa2fe, 0xeaa37e, 0xeaa3fe,
  0xee207e, 0xee20fe, 0xee217e, 0xee21fe, 0xee227e, 0xee22fe, 0xee237e, 0xee23fe, 0xf1a07e, 0xf1a0fe, 0xf1a17e, 0xf1a1fe, 0xf1a27e, 0xf1a2fe,
  0xf1a37e, 0xf1a3fe, 0xf5207e, 0xf520fe, 0xf5217e, 0xf521fe, 0xf5227e, 0xf522fe, 0xf5237e, 0xf523fe, 0xf8a07e, 0xf8a0fe, 0xf8a17e, 0xf8a1fe,
  0xf8a27e, 0xf8a2fe, 0xf8a37e, 0xf8a3fe,
};

void build_list(HList& l) {
  int n = 0;
  n = sizeof(h_items) / sizeof(h_items[0]);
  for (int i = 0; i < n; i++) l.it[i] = h_items[i];
  l.n = n;
}

typedef CUresult (*EncodeFn)(CUtensorMap*, CUtensorMapDataType, cuuint32_t, void*, const cuuint64_t*, const cuuint64_t*,
                             const cuuint32_t*, const cuuint32_t*, CUtensorMapInterleave, CUtensorMapSwizzle,
                             CUtensorMapL2promotion, CUtensorMapFloatOOBfill);

void make_map(EncodeFn fn, CUtensorMap* m, const void* p, uint64_t cols, uint64_t rows, uint32_t bc, uint32_t br, CUtensorMapSwizzle sw) {
  cuuint64_t dims[2] = {cols, rows};
  cuuint64_t strides[1] = {cols * 2};
  cuuint32_t box[2] = {bc, br};
  cuuint32_t es[2] = {1, 1};
  fn(m, CU_TENSOR_MAP_DATA_TYPE_BFLOAT16, 2, const_cast<void*>(p), dims, strides, box, es, CU_TENSOR_MAP_INTERLEAVE_NONE, sw,
     CU_TENSOR_MAP_L2_PROMOTION_L2_128B, CU_TENSOR_MAP_FLOAT_OOB_FILL_NONE);
}

}

extern "C" void kernel_launch(void* const* d_in, const int* in_sizes, int n_in, void* d_out, int out_size) {
  const __nv_bfloat16* x = (const __nv_bfloat16*)d_in[0];
  const __nv_bfloat16* mem0 = (const __nv_bfloat16*)d_in[1];
  const __nv_bfloat16* cvec = (const __nv_bfloat16*)d_in[11];
  static EncodeFn enc = nullptr;
  if (!enc) {
    cudaDriverEntryPointQueryResult qr;
    void* fp = nullptr;
    cudaGetDriverEntryPoint("cuTensorMapEncodeTiled", &fp, cudaEnableDefault, &qr);
    enc = (EncodeFn)fp;
    cudaFuncSetAttribute(kernel_R, cudaFuncAttributeMaxDynamicSharedMemorySize, R_SMEM);
    cudaFuncSetAttribute(kernel_H, cudaFuncAttributeMaxDynamicSharedMemorySize, H_SMEM);
  }
  CUtensorMap tmq, tmk, tmv, tmo, tmm;
  make_map(enc, &tmm, d_in[12], 6144, 1024, 64, 64, CU_TENSOR_MAP_SWIZZLE_NONE);
  make_map(enc, &tmq, d_in[2], 4096, 1024, 64, 64, CU_TENSOR_MAP_SWIZZLE_128B);
  make_map(enc, &tmk, d_in[3], 4096, 1024, 64, 64, CU_TENSOR_MAP_SWIZZLE_128B);
  make_map(enc, &tmv, d_in[4], 4096, 1024, 64, 64, CU_TENSOR_MAP_SWIZZLE_128B);
  make_map(enc, &tmo, d_in[5], 1024, 4096, 16, 128, CU_TENSOR_MAP_SWIZZLE_32B);
  RDesc dsc;
  for (int k = 0; k < 32; k++) {
    dsc.tok[k] = mkdesc(0x400 + (k < 16 ? R_GA : R_GB) + ((k & 15) >> 2) * 4096 + (k & 3) * 256, 128, 1024, 0);
    dsc.tail_a[k] = mkdesc(0x400 + R_TAIL + k * 2048, 1024, 1024, 1);
    if (k < 16) dsc.tail_b[k] = mkdesc(0x400 + R_GA + k * 256, 128, 4096, 0);
  }
  kernel_R<<<96, 256, R_SMEM, cudaStreamPerThread>>>(tmq, tmk, tmv, tmo, tmm, x, mem0, cvec, dsc);

  CUtensorMap ho, h1, h3, h2, hm, hx, hy;
  make_map(enc, &ho, d_in[5], 1024, 4096, 64, 64, CU_TENSOR_MAP_SWIZZLE_128B);
  make_map(enc, &h1, d_in[8], F_, 1024, 64, 64, CU_TENSOR_MAP_SWIZZLE_128B);
  make_map(enc, &h3, d_in[9], F_, 1024, 64, 64, CU_TENSOR_MAP_SWIZZLE_128B);
  make_map(enc, &h2, d_in[10], 1024, F_, 64, 64, CU_TENSOR_MAP_SWIZZLE_128B);
  make_map(enc, &hm, d_in[12], 6144, 1024, 64, 64, CU_TENSOR_MAP_SWIZZLE_128B);
  make_map(enc, &hx, d_out, 1024, S_, 64, 128, CU_TENSOR_MAP_SWIZZLE_128B);
  make_map(enc, &hy, d_out, 1024, S_, 64, 64, CU_TENSOR_MAP_SWIZZLE_128B);
  HList list;
  build_list(list);
  cudaLaunchConfig_t cfg = {};
  cfg.gridDim = dim3(132); cfg.blockDim = dim3(384); cfg.dynamicSmemBytes = H_SMEM; cfg.stream = cudaStreamPerThread;
  cudaLaunchAttribute at[1];
  at[0].id = cudaLaunchAttributeProgrammaticStreamSerialization;
  at[0].val.programmaticStreamSerializationAllowed = 1;
  cfg.attrs = at;
  cfg.numAttrs = 1;
  cudaLaunchKernelEx(&cfg, kernel_H, ho, h1, h3, h2, hm, hx, hy, x, cvec, (__nv_bfloat16*)d_out, list);
}
```

```cpp
#include <cuda_runtime.h>
#include <cuda_bf16.h>
#include <cuda.h>
#include <stdint.h>
#include <type_traits>

namespace {

constexpr int S_ = 2048, D_ = 1024, NSEG = 64, F_ = 3584;

__device__ __align__(1024) uint8_t g_h[S_ * D_ * 2];
__device__ __align__(1024) uint8_t g_att[S_ * 4096 * 2];
__device__ __align__(1024) uint8_t g_act[S_ * F_ * 2];
__device__ __align__(1024) uint8_t g_w13s[28 * 16 * 32768];
__device__ __align__(1024) uint8_t g_ext[16 * 2560];
__device__ __align__(1024) uint8_t g_bext[28 * 4096];
__device__ __align__(1024) __nv_bfloat16 g_gate[2 * D_];
__device__ __align__(1024) float g_slot[4 * 3 * 8 * 4 * 32 * 4];
__device__ __align__(128) __nv_bfloat16 g_mod[6 * D_];
__device__ __align__(128) float g_modp[3 * 2 * D_];
__device__ __align__(128) uint32_t g_flags[1024];
constexpr int FL_S1 = 0, FL_S2 = 32, FL_MOD = 64, FL_HEAD = 96, FL_EXIT = 128, FL_WS = 160, FL_GO = 192, FL_HEAD2 = 224, FL_ATT = 256, FL_XT = 384, FL_OUT = 512, FL_F1 = 640, FL_STAT = 768;

__device__ __forceinline__ uint32_t smem_u32(const void* p) { return (uint32_t)__cvta_generic_to_shared(p); }
__device__ __forceinline__ uint32_t mapa(uint32_t a, uint32_t r) { uint32_t o; asm("mapa.shared::cluster.u32 %0, %1, %2;" : "=r"(o) : "r"(a), "r"(r)); return o; }
__device__ __forceinline__ uint32_t pack2(float a, float b) { uint32_t r; asm("cvt.rn.bf16x2.f32 %0, %1, %2;" : "=r"(r) : "f"(b), "f"(a)); return r; }
__device__ __forceinline__ float bf_lo(uint32_t w) { return __uint_as_float(w << 16); }
__device__ __forceinline__ float bf_hi(uint32_t w) { return __uint_as_float(w & 0xffff0000u); }
__device__ __forceinline__ float ex2(float x) { float y; asm("ex2.approx.ftz.f32 %0, %1;" : "=f"(y) : "f"(x)); return y; }
__device__ __forceinline__ float rcp(float x) { float y; asm("rcp.approx.ftz.f32 %0, %1;" : "=f"(y) : "f"(x)); return y; }
__device__ __forceinline__ uint32_t clk32() { uint64_t c; asm volatile("mov.u64 %0, %%clock64;" : "=l"(c) :: "memory"); return (uint32_t)c; }

__device__ __forceinline__ void mbar_init(uint32_t b, uint32_t n) { asm volatile("mbarrier.init.shared::cta.b64 [%0], %1;" :: "r"(b), "r"(n) : "memory"); }
__device__ __forceinline__ void mbar_arrive(uint32_t b) { asm volatile("mbarrier.arrive.shared::cta.b64 _, [%0];" :: "r"(b) : "memory"); }
__device__ __forceinline__ void mbar_expect(uint32_t b, uint32_t n) { asm volatile("mbarrier.arrive.expect_tx.shared::cta.b64 _, [%0], %1;" :: "r"(b), "r"(n) : "memory"); }
__device__ __forceinline__ uint32_t mbar_try(uint32_t b, uint32_t par) {
  uint32_t ok;
  asm volatile("{\n.reg .pred p;\nmbarrier.try_wait.parity.shared::cta.b64 p, [%1], %2;\nselp.u32 %0, 1, 0, p;\n}" : "=r"(ok) : "r"(b), "r"(par) : "memory");
  return ok;
}
__device__ __forceinline__ void mbar_wait(uint32_t b, uint32_t par) {
  asm volatile("{\n.reg .pred p;\n"
               "LOOP:\n"
               "mbarrier.try_wait.parity.shared::cta.b64 p, [%0], %1;\n"
               "@!p bra.uni LOOP;\n}" :: "r"(b), "r"(par) : "memory");
}
__device__ __forceinline__ void mbar_wait_safe(uint32_t b, uint32_t par) {
  uint32_t c = 0;
  while (!mbar_try(b, par)) { if (++c > 4000000u) __trap(); }
}
__device__ __forceinline__ bool elect_one() {
  uint32_t p;
  asm volatile("{\n.reg .pred p;\nelect.sync _|p, 0xffffffff;\nselp.u32 %0, 1, 0, p;\n}" : "=r"(p));
  return p;
}
__device__ __forceinline__ void sched_fence(uint32_t x, uint32_t y) { asm volatile("{\n.reg .pred p;\nsetp.eq.u32 p, %0, %1;\n@p trap;\n}" :: "r"(x), "r"(y) : "memory"); }
template <class T> __device__ __forceinline__ T opaque32(T x) { asm volatile("" : "+r"(x)); return x; }
template <class T> __device__ __forceinline__ T opaque64(T x) { asm volatile("" : "+l"(x)); return x; }
template <int ID, int N> __device__ __forceinline__ void bar_sync() { asm volatile("bar.sync %0, %1;" :: "n"(ID), "n"(N) : "memory"); }
template <int ID, int N> __device__ __forceinline__ void bar_arrive() { asm volatile("bar.arrive %0, %1;" :: "n"(ID), "n"(N) : "memory"); }
__device__ __forceinline__ void fence_async_smem() { asm volatile("fence.proxy.async.shared::cta;" ::: "memory"); }
__device__ __forceinline__ void fence_async_all() { asm volatile("fence.proxy.async;" ::: "memory"); }
__device__ __forceinline__ void fence_gpu() { asm volatile("fence.acq_rel.gpu;" ::: "memory"); }
__device__ __forceinline__ void red_add_u32(uint32_t* p, uint32_t v) { asm volatile("red.relaxed.gpu.global.add.u32 [%0], %1;" :: "l"(p), "r"(v) : "memory"); }
__device__ __forceinline__ uint32_t ld_acquire(const uint32_t* p) { uint32_t v; asm volatile("ld.acquire.gpu.global.u32 %0, [%1];" : "=r"(v) : "l"(p) : "memory"); return v; }
__device__ __forceinline__ void wait_flag(const uint32_t* p, uint32_t target) {
  uint32_t c = 0;
  while (ld_acquire(p) < target) { if (++c > 20000000u) __trap(); __nanosleep(20); }
}

__device__ __forceinline__ void tma2d(uint32_t dst, const CUtensorMap* m, int c0, int c1, uint32_t bar) {
  asm volatile("cp.async.bulk.tensor.2d.shared::cluster.global.mbarrier::complete_tx::bytes [%0], [%1, {%3, %4}], [%2];"
               :: "r"(dst), "l"(m), "r"(bar), "r"(c0), "r"(c1) : "memory");
}
constexpr uint64_t L2_NORMAL = 0x1000000000000000ull, L2_FIRST = 0x12F0000000000000ull;
__device__ __forceinline__ void tma2d_p(uint32_t dst, const CUtensorMap* m, int c0, int c1, uint32_t bar, uint64_t pol) {
  asm volatile("cp.async.bulk.tensor.2d.shared::cluster.global.mbarrier::complete_tx::bytes.L2::cache_hint [%0], [%1, {%3, %4}], [%2], %5;"
               :: "r"(dst), "l"(m), "r"(bar), "r"(c0), "r"(c1), "l"(pol) : "memory");
}
__device__ __forceinline__ void bulk_g2s_p(uint32_t dst, const void* src, uint32_t bytes, uint32_t bar, uint64_t pol) {
  asm volatile("cp.async.bulk.shared::cluster.global.mbarrier::complete_tx::bytes.L2::cache_hint [%0], [%1], %2, [%3], %4;"
               :: "r"(dst), "l"(src), "r"(bytes), "r"(bar), "l"(pol) : "memory");
}
#define POL_RW L2_FIRST
__device__ __forceinline__ void tma2d_prefetch_p(const CUtensorMap* m, int c0, int c1, uint64_t pol) {
  asm volatile("cp.async.bulk.prefetch.tensor.2d.L2.global.L2::cache_hint [%0, {%1, %2}], %3;" :: "l"(m), "r"(c0), "r"(c1), "l"(pol) : "memory");
}
__device__ __forceinline__ void tma2d_prefetch(const CUtensorMap* m, int c0, int c1) {
  asm volatile("cp.async.bulk.prefetch.tensor.2d.L2.global [%0, {%1, %2}];" :: "l"(m), "r"(c0), "r"(c1) : "memory");
}
__device__ __forceinline__ void bulk_g2s(uint32_t dst, const void* src, uint32_t bytes, uint32_t bar) {
  asm volatile("cp.async.bulk.shared::cluster.global.mbarrier::complete_tx::bytes [%0], [%1], %2, [%3];"
               :: "r"(dst), "l"(src), "r"(bytes), "r"(bar) : "memory");
}
__device__ __forceinline__ void bulk_s2s(uint32_t dst, uint32_t src, uint32_t bytes, uint32_t bar) {
  asm volatile("cp.async.bulk.shared::cluster.shared::cta.mbarrier::complete_tx::bytes [%0], [%1], %2, [%3];"
               :: "r"(dst), "r"(src), "r"(bytes), "r"(bar) : "memory");
}
__device__ __forceinline__ void st_async1(uint32_t dst, uint32_t a, uint32_t bar) {
  asm volatile("st.async.shared::cluster.mbarrier::complete_tx::bytes.b32 [%0], %1, [%2];" :: "r"(dst), "r"(a), "r"(bar) : "memory");
}
__device__ __forceinline__ void st_async2(uint32_t dst, uint32_t a, uint32_t b, uint32_t bar) {
  asm volatile("st.async.shared::cluster.mbarrier::complete_tx::bytes.v2.b32 [%0], {%1, %2}, [%3];" :: "r"(dst), "r"(a), "r"(b), "r"(bar) : "memory");
}
__device__ __forceinline__ void st_async4(uint32_t dst, const uint32_t* r, uint32_t bar) {
  asm volatile("st.async.shared::cluster.mbarrier::complete_tx::bytes.v4.b32 [%0], {%1, %2, %3, %4}, [%5];"
               :: "r"(dst), "r"(r[0]), "r"(r[1]), "r"(r[2]), "r"(r[3]), "r"(bar) : "memory");
}
__device__ __forceinline__ void sts32(uint32_t a, uint32_t v) { asm volatile("st.shared.b32 [%0], %1;" :: "r"(a), "r"(v) : "memory"); }
__device__ __forceinline__ void sts64(uint32_t a, uint32_t x, uint32_t y) { asm volatile("st.shared.v2.b32 [%0], {%1, %2};" :: "r"(a), "r"(x), "r"(y) : "memory"); }
__device__ __forceinline__ void sts128(uint32_t a, uint32_t x, uint32_t y, uint32_t z, uint32_t w) {
  asm volatile("st.shared.v4.b32 [%0], {%1, %2, %3, %4};" :: "r"(a), "r"(x), "r"(y), "r"(z), "r"(w) : "memory");
}
__device__ __forceinline__ void lds128(uint32_t* r, uint32_t a) {
  asm volatile("ld.shared.v4.b32 {%0, %1, %2, %3}, [%4];" : "=r"(r[0]), "=r"(r[1]), "=r"(r[2]), "=r"(r[3]) : "r"(a) : "memory");
}
__device__ __forceinline__ uint32_t lds32(uint32_t a) { uint32_t r; asm volatile("ld.shared.b32 %0, [%1];" : "=r"(r) : "r"(a) : "memory"); return r; }
__device__ __forceinline__ void lds64(uint32_t* r, uint32_t a) {
  asm volatile("ld.shared.v2.b32 {%0, %1}, [%2];" : "=r"(r[0]), "=r"(r[1]) : "r"(a) : "memory");
}
__device__ __forceinline__ void lds128f(float* r, uint32_t a) {
  asm volatile("ld.shared.v4.f32 {%0, %1, %2, %3}, [%4];" : "=f"(r[0]), "=f"(r[1]), "=f"(r[2]), "=f"(r[3]) : "r"(a) : "memory");
}
__device__ __forceinline__ void lds64f(float* r, uint32_t a) {
  asm volatile("ld.shared.v2.f32 {%0, %1}, [%2];" : "=f"(r[0]), "=f"(r[1]) : "r"(a) : "memory");
}
__device__ __forceinline__ void ldsm4(uint32_t* r, uint32_t a) {
  asm volatile("ldmatrix.sync.aligned.m8n8.x4.shared.b16 {%0, %1, %2, %3}, [%4];" : "=r"(r[0]), "=r"(r[1]), "=r"(r[2]), "=r"(r[3]) : "r"(a) : "memory");
}
__device__ __forceinline__ void ldsm4t(uint32_t* r, uint32_t a) {
  asm volatile("ldmatrix.sync.aligned.m8n8.x4.trans.shared.b16 {%0, %1, %2, %3}, [%4];" : "=r"(r[0]), "=r"(r[1]), "=r"(r[2]), "=r"(r[3]) : "r"(a) : "memory");
}
__device__ __forceinline__ void ldsm2(uint32_t* r, uint32_t a) {
  asm volatile("ldmatrix.sync.aligned.m8n8.x2.shared.b16 {%0, %1}, [%2];" : "=r"(r[0]), "=r"(r[1]) : "r"(a) : "memory");
}
__device__ __forceinline__ void stsm4(uint32_t a, const uint32_t* r) {
  asm volatile("stmatrix.sync.aligned.m8n8.x4.shared.b16 [%0], {%1, %2, %3, %4};" :: "r"(a), "r"(r[0]), "r"(r[1]), "r"(r[2]), "r"(r[3]) : "memory");
}
__device__ __forceinline__ uint32_t hadd2(uint32_t a, uint32_t b) { uint32_t t; asm("add.rn.bf16x2 %0, %1, %2;" : "=r"(t) : "r"(a), "r"(b)); return t; }
__device__ __forceinline__ uint32_t hmax2(uint32_t a, uint32_t b) { uint32_t t; asm("max.bf16x2 %0, %1, %2;" : "=r"(t) : "r"(a), "r"(b)); return t; }
__device__ __forceinline__ void ldsm2t(uint32_t* r, uint32_t a) {
  asm volatile("ldmatrix.sync.aligned.m8n8.x2.trans.shared.b16 {%0, %1}, [%2];" : "=r"(r[0]), "=r"(r[1]) : "r"(a) : "memory");
}
__device__ __forceinline__ uint32_t movm(uint32_t x) { uint32_t y; asm volatile("movmatrix.sync.aligned.m8n8.trans.b16 %0, %1;" : "=r"(y) : "r"(x)); return y; }
__device__ __forceinline__ void hmma(float* d, uint32_t a0, uint32_t a1, uint32_t a2, uint32_t a3, uint32_t b0, uint32_t b1) {
  asm volatile("mma.sync.aligned.m16n8k16.row.col.f32.bf16.bf16.f32 {%0,%1,%2,%3}, {%4,%5,%6,%7}, {%8,%9}, {%0,%1,%2,%3};"
               : "+f"(d[0]), "+f"(d[1]), "+f"(d[2]), "+f"(d[3]) : "r"(a0), "r"(a1), "r"(a2), "r"(a3), "r"(b0), "r"(b1));
}
__device__ __forceinline__ void hmma0(float* d, uint32_t a0, uint32_t a1, uint32_t a2, uint32_t a3, uint32_t b0, uint32_t b1) {
  asm volatile("mma.sync.aligned.m16n8k16.row.col.f32.bf16.bf16.f32 {%0,%1,%2,%3}, {%4,%5,%6,%7}, {%8,%9}, {%10,%10,%10,%10};"
               : "=f"(d[0]), "=f"(d[1]), "=f"(d[2]), "=f"(d[3]) : "r"(a0), "r"(a1), "r"(a2), "r"(a3), "r"(b0), "r"(b1), "f"(0.f));
}
__device__ __forceinline__ void hmma_k8(float* d, uint32_t a0, uint32_t a1, uint32_t b0) {
  asm volatile("mma.sync.aligned.m16n8k8.row.col.f32.bf16.bf16.f32 {%0,%1,%2,%3}, {%4,%5}, {%6}, {%0,%1,%2,%3};"
               : "+f"(d[0]), "+f"(d[1]), "+f"(d[2]), "+f"(d[3]) : "r"(a0), "r"(a1), "r"(b0));
}
__host__ __device__ constexpr uint64_t mkdesc(uint32_t addr, uint32_t lbo, uint32_t sbo, uint32_t sw) {
  return (uint64_t)((addr & 0x3FFFF) >> 4) | ((uint64_t)(lbo >> 4) << 16) | ((uint64_t)(sbo >> 4) << 32) | ((uint64_t)sw << 62);
}
#define WG_FENCE() asm volatile("wgmma.fence.sync.aligned;" ::: "memory")
#define WG_COMMIT() asm volatile("wgmma.commit_group.sync.aligned;" ::: "memory")
#define WG_WAIT(n) asm volatile("wgmma.wait_group.sync.aligned " #n ";" ::: "memory")
template <int N> __device__ __forceinline__ void reg_fence(float* d) {
#pragma unroll
  for (int i = 0; i < N; i++) asm volatile("" : "+f"(d[i]) :: "memory");
}
template <int N> __device__ __forceinline__ void zero_regs(float* d) {
#pragma unroll
  for (int i = 0; i < N; i++) asm volatile("mov.b32 %0, 0;" : "=f"(d[i]));
}
template <int SD>
__device__ __forceinline__ void wg_rs32(float* d, uint32_t a0, uint32_t a1, uint32_t a2, uint32_t a3, uint64_t b) {
  asm volatile("wgmma.mma_async.sync.aligned.m64n32k16.f32.bf16.bf16 {%0,%1,%2,%3,%4,%5,%6,%7,%8,%9,%10,%11,%12,%13,%14,%15}, {%16,%17,%18,%19}, %20, %21, 1, 1, 0;"
               : "+f"(d[0]), "+f"(d[1]), "+f"(d[2]), "+f"(d[3]), "+f"(d[4]), "+f"(d[5]), "+f"(d[6]), "+f"(d[7]),
                 "+f"(d[8]), "+f"(d[9]), "+f"(d[10]), "+f"(d[11]), "+f"(d[12]), "+f"(d[13]), "+f"(d[14]), "+f"(d[15])
               : "r"(a0), "r"(a1), "r"(a2), "r"(a3), "l"(b), "n"(SD));
}
template <int TB>
__device__ __forceinline__ void wg_ss40(float* d, uint64_t a, uint64_t b) {
  asm volatile("wgmma.mma_async.sync.aligned.m64n40k16.f32.bf16.bf16 {%0,%1,%2,%3,%4,%5,%6,%7,%8,%9,%10,%11,%12,%13,%14,%15,%16,%17,%18,%19}, %20, %21, 1, 1, 1, 1, %22;"
               : "+f"(d[0]), "+f"(d[1]), "+f"(d[2]), "+f"(d[3]), "+f"(d[4]), "+f"(d[5]), "+f"(d[6]), "+f"(d[7]),
                 "+f"(d[8]), "+f"(d[9]), "+f"(d[10]), "+f"(d[11]), "+f"(d[12]), "+f"(d[13]), "+f"(d[14]), "+f"(d[15]),
                 "+f"(d[16]), "+f"(d[17]), "+f"(d[18]), "+f"(d[19])
               : "l"(a), "l"(b), "n"(TB));
}
template <int T>
__device__ __forceinline__ void wg_ss32(float* d, uint64_t a, uint64_t b) {
  asm volatile("wgmma.mma_async.sync.aligned.m64n32k16.f32.bf16.bf16 {%0,%1,%2,%3,%4,%5,%6,%7,%8,%9,%10,%11,%12,%13,%14,%15}, %16, %17, 1, 1, 1, %18, %18;"
               : "+f"(d[0]), "+f"(d[1]), "+f"(d[2]), "+f"(d[3]), "+f"(d[4]), "+f"(d[5]), "+f"(d[6]), "+f"(d[7]),
                 "+f"(d[8]), "+f"(d[9]), "+f"(d[10]), "+f"(d[11]), "+f"(d[12]), "+f"(d[13]), "+f"(d[14]), "+f"(d[15])
               : "l"(a), "l"(b), "n"(T));
}

constexpr int R_TAIL = 0;
constexpr int R_WO = 65536;
constexpr int R_QK = R_WO + 86016;
constexpr int R_P = R_QK + 10240;
constexpr int R_GA = R_P + 6400;
constexpr int R_M2 = R_GA + 16384;
constexpr int R_M1 = R_M2 + 7168;
constexpr int R_GB = R_M1 + 9216;
constexpr int R_VT = R_GB + 16384;
constexpr int R_VM = R_VT + 8192;
constexpr int R_XS = R_VM + 2048;
constexpr int R_OX = R_XS + 1280;
constexpr int R_BAR = R_OX + 2048;
constexpr int R_TRC = R_BAR + 256;
constexpr int R_SMEM = R_TRC + 1024;
constexpr int B_MB = 0, B_XS = 32, B_VM = 40, B_VT = 48, B_TS = 56, B_FA = 64, B_FB = 72, B_TAIL = 80, B_WO = 88, B_STG = 96, B_WM = 128, B_X = 136;
constexpr int NB_A = 1, NB_B = 2, NB_X = 3, NB_C = 4, NB_D = 5, NB_E = 6, NB_F = 7, NB_G = 8, NB_H = 9, NB_S = 10, NB_E2 = 11, NB_P = 12, NB_W0 = 13;

#define POLL_DELAY 750
#define POLL_DELAY1 700
#define POLL_STAG 150
#define POLL_K0 20
#define ZS 2
#define HPF 4
#define PF1 2
#define PF2 2
#define PF3 2
#define PF4 0
#define RF_FIRST 0
#define BX_I 5
#define NCH 4
#define TOP2 0
#define CX_I 13
#define ATT_LATE 0
#define V_FENCE 1
#define SELF_STAS 1
#define Q_FENCE 1
#define ND_K 3
#define TRACE(i)
#define TS(i)

__device__ __forceinline__ int rot_chunk(int c, int rank) {
  int G = c;
  if (c < 9) { G = c + 3 * rank; if (G >= 9) G -= 9; }
  return G;
}
__device__ __forceinline__ int wo_tile(int i, int rank) {
  if (i < 12) return 12 * rank + i;
  const int r = i - 12 + 9 * rank;
  return r < 16 ? 48 + r : 20 + r;
}
__device__ __forceinline__ void load_chunk(uint32_t dst, int seg, int G, uint32_t bar) {
  mbar_expect(bar, 4096);
  bulk_g2s(dst, g_h + (size_t)(seg * 16 + G) * 4096, 4096, bar);
}
__device__ __forceinline__ void load_red(uint32_t* v, const float* p) {
#pragma unroll
  for (int j = 0; j < 2; j++)
    asm volatile("ld.relaxed.gpu.global.v4.u32 {%0, %1, %2, %3}, [%4];"
                 : "=r"(v[4 * j]), "=r"(v[4 * j + 1]), "=r"(v[4 * j + 2]), "=r"(v[4 * j + 3]) : "l"(p + j * 256) : "memory");
}
__device__ __forceinline__ bool red_done(const uint32_t* v) { return __all_sync(0xffffffffu, (v[3] & v[7]) == 0x42000000u); }
__device__ __forceinline__ uint32_t finish_red(uint32_t* v, const float* p) {
  uint32_t tries = 0;
  if (__builtin_expect(!red_done(v), 0)) {
    do { if (++tries > 20000000u) __trap(); load_red(v, p); } while (!red_done(v));
  }
  return tries;
}
__device__ __forceinline__ void exp10(float* sv, const uint32_t* x) {
  constexpr float SC = 0.08838834764831845f * 1.4426950408889634f;
  uint32_t m2 = hmax2(hmax2(hmax2(x[0], x[1]), hmax2(x[2], x[3])), x[4]);
  m2 = hmax2(m2, __shfl_xor_sync(0xffffffffu, m2, 1));
  m2 = hmax2(m2, __shfl_xor_sync(0xffffffffu, m2, 2));
  const float nm = -fmaxf(bf_lo(m2), bf_hi(m2)) * SC;
#pragma unroll
  for (int j = 0; j < 5; j++) { sv[2 * j] = ex2(fmaf(bf_lo(x[j]), SC, nm)); sv[2 * j + 1] = ex2(fmaf(bf_hi(x[j]), SC, nm)); }
}

__device__ __forceinline__ uint32_t arm_size(int w, bool isC) {
  return w == 0 ? (isC ? 1280 : 640) : w == 1 ? (isC ? 0 : 2048) : w == 2 ? (isC ? 0 : 8192) : (isC ? 0 : 1792);
}
struct RDesc { uint64_t tok[32], tail_b[16], tail_a[32]; };

template <int WG>
__device__ __forceinline__ void r_main(const uint32_t (&W)[48][4], const RDesc& dsc, int head, uint32_t rank, int lane_, int w) {
  const uint32_t sb = (rank << 24) + 0x400, bars = sb + R_BAR;
  const uint32_t to1 = rank == 0 ? 2u << 24 : 0u - (1u << 24), to2 = rank == 2 ? 0u - (2u << 24) : 1u << 24;
  const bool isC = rank == 2;
  const int lane = opaque32(lane_), warp = WG * 4 + w;
  const int gl = rot_chunk(4 * (lane & 3) + w, rank);
  const int g0 = __shfl_sync(0xffffffffu, gl, 0), g1 = __shfl_sync(0xffffffffu, gl, 1), g2 = __shfl_sync(0xffffffffu, gl, 2);
  const uint32_t arm_bytes = arm_size(w, isC);

#define L16 opaque32(sb + opaque32(lane) * 16)
#define L8 opaque32(sb + opaque32(lane) * 8)
#define L4 opaque32(sb + opaque32(lane) * 4)
#define LV opaque32(sb + R_VT + ((opaque32(lane) >> 3) & 1) * 512 + (opaque32(lane) >> 4) * 128 + (opaque32(lane) & 7) * 16)
#define SLOT(st) opaque64(slot0 + ((st) & 3) * 12288 + ((st) & 4) * 32)
  float* const slot0 = opaque64(g_slot + (rank * 1024 + warp * 128 + lane) * 4);
  const uint32_t woa = opaque32(sb + R_WO + warp * 12288 + ((lane >> 4) * 8 + (lane & 7)) * 32 + ((((lane >> 3) ^ (lane >> 2)) & 1) << 4));
  const bool has_wo = WG == 0 || isC || w < 3;
  float acc[20];
  uint32_t pk[8] = {0u, 0u, 0u, 0u, 0u, 0u, 0u, 0u};

  auto forward = [&](auto rd, const uint32_t* v, int st, uint32_t tries) {
    constexpr int RD = decltype(rd)::value;
    uint32_t u[6];
#pragma unroll
    for (int j = 0; j < 6; j++) u[j] = movm(v[4 * (j / 3) + j % 3]);
    const bool all3 = RD == 0 || w < 3;
    if (RD == 0) {
      const uint32_t a = L16 + R_M1 + w * 768, a2 = L8 + R_M1 + 512 + w * 768;
      st_async4(a + to1 + 3072, u, bars + to1 + B_MB + 8); st_async2(a2 + to1 + 3072, u[4], u[5], bars + to1 + B_MB + 8);
      sts128(a, u[0], u[1], u[2], u[3]); sts64(a2, u[4], u[5]);
      __syncwarp();
      if (elect_one()) mbar_arrive(bars + B_MB);
      st_async4(a + to2 + 6144, u, bars + to2 + B_MB + 16); st_async2(a2 + to2 + 6144, u[4], u[5], bars + to2 + B_MB + 16);
    } else {
      const uint32_t a = L4 + R_M2 + rank * 2304 + w * 768;
#pragma unroll
      for (int j = 0; j < 6; j++) if (j < 2 || all3) st_async1(a + to1 + j * 128, u[j], bars + to1 + B_MB + 24);
#pragma unroll
      for (int j = 0; j < 6; j++) if (j < 2 || all3) st_async1(a + to2 + j * 128, u[j], bars + to2 + B_MB + 24);
      if (SELF_STAS) {
#pragma unroll
        for (int j = 0; j < 6; j++) if (j < 2 || all3) st_async1(a + j * 128, u[j], bars + B_MB + 24);
      } else {
#pragma unroll
        for (int j = 0; j < 6; j++) if (j < 2 || all3) sts32(a + j * 128, u[j]);
        __syncwarp();
        if (elect_one()) mbar_arrive(bars + B_MB + 24);
      }
    }
  };

  auto send_vt = [&]() {
    if (elect_one()) {
      const uint32_t src = sb + R_VT + warp * 1024;
      bulk_s2s(src + to1, src, 1024, bars + to1 + B_VT);
      bulk_s2s(src + to2, src, 1024, bars + to2 + B_VT);
    }
  };
  auto store_att = [&](int sg) {
    uint32_t* op = reinterpret_cast<uint32_t*>(g_att + (size_t)((sg >> 2) * 64 + head * 2 + rank) * 16384 + (2 * w * 16 + (sg & 3) * 4) * 128) + opaque32(lane);
#pragma unroll
    for (int j = 0; j < 8; j++) op[(j & 1) * 512 + (j >> 1) * 32] = pk[j];
  };

  if (WG == 0) bar_arrive<NB_G, 256>();
#pragma unroll 1
  for (int s = -1; s < NSEG; s++) {
    const uint32_t par = (s + 1) & 1;
    const uint32_t last = s == NSEG - 1;
    TRACE(0);
    {
      float c[NCH][4];
      uint32_t b[3][6];
      const uint32_t ma = L16, m8 = L8;
#pragma unroll
      for (int i = 0; i < 18; i++) {
        if (i < 16) {
          if (i % 4 == 0 && !(i == 4 && TOP2)) mbar_wait(bars + B_MB + (i / 4) * 8, par ^ 1);
          if (i == 0 && TOP2) mbar_wait(bars + B_MB + 8, par ^ 1);
          if (i % 4 == 0) TRACE(1 + i / 4);
          if (i < 12) { lds128(b[i % 3], ma + R_M1 + i * 768); lds64(b[i % 3] + 4, m8 + R_M1 + 512 + i * 768); }
          else { ldsm4(b[i % 3], ma + R_M2 + 4096 + (i - 12) * 768); ldsm2(b[i % 3] + 4, ma + R_M2 + 4096 + 512 + (i - 12) * 768); }
          if (WG == 1 && i == BX_I) {
            bar_sync<NB_G, 256>();
            if (!last && elect_one()) load_chunk(sb + R_GB + w * 4096, s + 1, g0, bars + B_FB);
          }
          if (i == CX_I) {
            if (isC && s >= 0) send_vt();
            if (WG == 1 && ATT_LATE && !isC && s > 0) store_att(s - 1);
          }
          __syncwarp();
        }
        if (i >= 2) {
          const int j = i - 2;
#pragma unroll
          for (int q = 0; q < 3; q++) {
            const uint32_t* f = W[3 * j + q];
            if (3 * j + q < NCH) hmma0(c[3 * j + q], f[0], f[1], f[2], f[3], b[j % 3][2 * q], b[j % 3][2 * q + 1]);
            else hmma(c[(3 * j + q) % NCH], f[0], f[1], f[2], f[3], b[j % 3][2 * q], b[j % 3][2 * q + 1]);
          }
        }
        if (i == 14) zero_regs<16>(acc);
        if (i == 16) mbar_wait(bars + B_FA, last);
      }
#pragma unroll
      for (int j = 0; j < 4; j++) acc[16 + j] = NCH == 3 ? (c[0][j] + c[1][j]) + c[2][j] : (c[0][j] + c[1][j]) + (c[2][j] + c[NCH - 1][j]);
    }
    TRACE(5);
    bar_sync<NB_H, 256>();
    WG_FENCE();
#pragma unroll
    for (int k = 0; k < 16; k++) wg_ss40<0>(acc, dsc.tail_a[WG * 16 + k], dsc.tail_b[k]);
    WG_COMMIT();
    uint32_t vt[4][4];
    {
      const uint32_t a = opaque32(L4 + w * 256 + (isC ? WG * 1024 + R_VM : R_QK + 4096 + WG * 5120));
      const uint32_t qa = L16 + R_QK, xa = opaque32(LV + w * 2048 + (WG == 0 ? 0 : (opaque32(lane) & 8) * 64 + R_QK + 5120 - R_VT));
      const uint32_t d = opaque32(L4 + R_XS + rank * 640 + w * 256);
      if (s == 0) {
        mbar_wait_safe(bars + B_WO, 0);
        TS(10);
        if (WG == 1 && head == 0 && rank == 0 && w == 0 && elect_one()) red_add_u32(&g_flags[FL_GO], 1);
      }
      mbar_wait(bars + B_FB, last);
      if (WG == 0) mbar_wait(bars + B_VT, par);
      WG_WAIT(0);
      reg_fence<20>(acc);
      TRACE(6);
      const uint32_t p0 = pack2(acc[16], acc[17]), p1 = pack2(acc[18], acc[19]);
      sts32(a, p0); sts32(a + 128, p1);
      if (isC) {
        st_async1(a + to1, p0, bars + B_VM + to1); st_async1(a + to1 + 128, p1, bars + B_VM + to1);
        st_async1(a + to2, p0, bars + B_VM + to2); st_async1(a + to2 + 128, p1, bars + B_VM + to2);
      }
      if (WG == 0) {
        bar_arrive<NB_A, 256>();
        if (Q_FENCE && !isC) fence_async_smem();
#pragma unroll
        for (int i = 0; i < 4; i++) ldsm4(vt[i], xa + (i >> 1) * 1024 + (i & 1) * 256);
        bar_sync<NB_S, 256>();
      } else {
        bar_sync<NB_A, 256>();
        if (!isC) {
          if (w < 3) {
            uint32_t q[8], k[4][4];
            ldsm4t(q, qa + 4096); ldsm4t(k[0], xa); ldsm4t(k[1], xa + 256);
            ldsm4t(q + 4, qa + 4096 + 512); ldsm4t(k[2], xa + 512); ldsm4t(k[3], xa + 768);
            float x[4], y[4];
            hmma0(x, k[0][0], k[0][1], k[0][2], k[0][3], q[0], q[1]); hmma0(y, k[1][0], k[1][1], k[1][2], k[1][3], q[2], q[3]);
            hmma(x, k[2][0], k[2][1], k[2][2], k[2][3], q[4], q[5]); hmma(y, k[3][0], k[3][1], k[3][2], k[3][3], q[6], q[7]);
            const uint32_t s0 = pack2(x[0] + y[0], x[1] + y[1]), s1 = pack2(x[2] + y[2], x[3] + y[3]);
            st_async1(d + to1, s0, bars + B_XS + to1);
            st_async1(d + to2, s0, bars + B_XS + to2);
            if (w < 2) { st_async1(d + to1 + 128, s1, bars + B_XS + to1); st_async1(d + to2 + 128, s1, bars + B_XS + to2); sts32(d + 128, s1); }
            sts32(d, s0);
          }
        }
        bar_arrive<NB_S, 256>();
      }
    }
    if (WG == 1) {
      if (!last && elect_one()) load_chunk(sb + R_GA + w * 4096, s + 1, g1, bars + B_FA);
      {
        if (w > 0 && elect_one()) mbar_expect(bars + B_MB + 8 * w, w < 3 ? 3072 : SELF_STAS ? 28 * 256 : isC ? 18 * 256 : 19 * 256);
      }
      fence_async_smem();
      bar_sync<NB_B, 256>();
    }
    TRACE(7);
    WG_FENCE();
#pragma unroll
    for (int k = 0; k < 16; k++) wg_rs32<1>(acc, W[k][0], W[k][1], W[k][2], W[k][3], dsc.tok[16 + k]);
    WG_COMMIT();
    uint32_t wa[3][4];
    const uint32_t oxa = L16 + R_OX;
    if (WG == 0) {
      const uint32_t vma = oxa - (R_OX - R_VM) + w * 512, oa = opaque32(L4 + w * 512 + R_OX);
      TRACE(8);
      mbar_wait(bars + B_XS, par);
      TRACE(9);
      float sv[10];
      {
        uint32_t x[10];
        ldsm4t(x, oxa - (R_OX - R_XS)); ldsm4t(x + 4, oxa - (R_OX - R_XS) + 512); ldsm2t(x + 8, oxa - (R_OX - R_XS) + 1024);
        bar_arrive<NB_B, 256>();
#pragma unroll
        for (int j = 0; j < 5; j++) x[j] = hadd2(x[j], x[j + 5]);
        exp10(sv, x);
      }
      WG_WAIT(0);
      bar_arrive<NB_X, 256>();
      mbar_wait(bars + B_VM, par);
      uint32_t vm[4];
      ldsm4(vm, vma);
      uint32_t pb[5];
#pragma unroll
      for (int j = 0; j < 5; j++) pb[j] = pack2(sv[2 * j], sv[2 * j + 1]);
      TRACE(10);
      float o0[4], o1[4], sm[4];
      const uint32_t ONE = 0x3f803f80u;
      hmma0(o0, vt[0][0], vt[0][1], vt[0][2], vt[0][3], pb[0], pb[1]);
      hmma0(o1, vt[2][0], vt[2][1], vt[2][2], vt[2][3], pb[0], pb[1]);
      hmma0(sm, ONE, ONE, ONE, ONE, pb[0], pb[1]);
      hmma(sm, ONE, ONE, ONE, ONE, pb[2], pb[3]);
      hmma(o0, vt[1][0], vt[1][1], vt[1][2], vt[1][3], pb[2], pb[3]);
      hmma(o1, vt[3][0], vt[3][1], vt[3][2], vt[3][3], pb[2], pb[3]);
      hmma_k8(sm, ONE, ONE, pb[4]);
      hmma_k8(o0, vm[0], vm[1], pb[4]);
      hmma_k8(o1, vm[2], vm[3], pb[4]);
#pragma unroll
      for (int i = 0; i < 3; i++) ldsm4t(wa[i], woa + i * 4096);
      __syncwarp();
      const float i0 = rcp(sm[0]), i1 = rcp(sm[1]);
      sts32(oa, pack2(o0[0] * i0, o0[1] * i1)); sts32(oa + 128, pack2(o0[2] * i0, o0[3] * i1));
      sts32(oa + 256, pack2(o1[0] * i0, o1[1] * i1)); sts32(oa + 384, pack2(o1[2] * i0, o1[3] * i1));
      TRACE(11);
      bar_sync<NB_C, 128>();
    } else {
      if (!isC) {
        constexpr uint64_t dQ = mkdesc(0x400 + R_QK, 128, 1024, 0), dK = mkdesc(0x400 + R_QK + 5120, 128, 1024, 0);
        float sc[16];
        zero_regs<16>(sc);
        WG_FENCE();
#pragma unroll
        for (int k = 0; k < 4; k++) wg_ss32<1>(sc, dK + k * 16, dQ + k * 16);
        WG_COMMIT();
        const uint32_t top = rank == 0 ? to2 : to1, e = L4 + R_P + w * 256;
        WG_WAIT(0);
        bar_sync<NB_X, 256>();
        if (!last && elect_one()) load_chunk(sb + R_GB + w * 4096, s + 1, g2, bars + B_FB);
        reg_fence<16>(sc);
        if (w < 3) {
#pragma unroll
          for (int j = 0; j < 8; j++) {
            if ((j & 1) ? (j > 1 && (w == 0 || (w == 1 && j == 7))) : (j >= 4 || w != 1)) {
              const uint32_t t = pack2(sc[2 * j], sc[2 * j + 1]), o = (j >> 1) * 768 + (j & 1) * 128;
              st_async1(e + top + 3072 + o, t, bars + top + B_TS);
              sts32(e + o, t);
            }
          }
          __syncwarp();
          if (elect_one()) mbar_arrive(bars + B_TS);
        }
      } else {
        WG_WAIT(0);
        bar_sync<NB_X, 256>();
        if (!last && elect_one()) load_chunk(sb + R_GB + w * 4096, s + 1, g2, bars + B_FB);
      }
      TRACE(8);
      mbar_wait(bars + B_FA, 1);
      TRACE(11);
    }
    if (has_wo) {
      float* rslot = SLOT(s);
      uint32_t ob[4][4];
      float c[3][4];
      if (WG == 1) {
#pragma unroll
        for (int i = 0; i < 3; i++) ldsm4t(wa[i], woa + i * 4096);
        bar_sync<NB_D, 256>();
      }
      ldsm4t(ob[0], oxa);
      __syncwarp();
#pragma unroll
      for (int k = 0; k < 8; k++) {
        uint32_t nx[3][4];
        if ((k & 1) == 0 && k < 6) { ldsm4t(ob[(k >> 1) + 1], oxa + ((k >> 1) + 1) * 512); __syncwarp(); }
#pragma unroll
        for (int i = 0; i < 3; i++) {
          const uint32_t* o = ob[k >> 1] + (k & 1) * 2;
          if (k < 7) { ldsm4t(nx[i], woa + i * 4096 + (k + 1) * 512); if (i == 2) __syncwarp(); }
          if (k == 0) hmma0(c[i], wa[i][0], wa[i][1], wa[i][2], wa[i][3], o[0], o[1]);
          else hmma(c[i], wa[i][0], wa[i][1], wa[i][2], wa[i][3], o[0], o[1]);
#pragma unroll
          for (int q = 0; q < 4; q++) if (k < 7) wa[i][q] = nx[i][q];
        }
        if (k == ND_K && WG == 0) bar_arrive<NB_D, 256>();
      }
      const float* cv = &c[0][0];
      uint32_t r[6];
#pragma unroll
      for (int j = 0; j < 6; j++) r[j] = pack2(cv[2 * j], cv[2 * j + 1]);
      asm volatile("{\n.reg .pred p;\nsetp.lt.s32 p, %8, 0;\n@p bra.uni SKIP;\n"
                   "red.relaxed.gpu.global.add.noftz.v4.bf16x2 [%0], {%1, %2, %3, %7};\n"
                   "red.relaxed.gpu.global.add.noftz.v4.bf16x2 [%0+1024], {%4, %5, %6, %7};\nSKIP:\n}"
                   :: "l"(rslot), "r"(r[0]), "r"(r[1]), "r"(r[2]), "r"(r[3]), "r"(r[4]), "r"(r[5]), "r"(0x3f800000), "r"(s) : "memory");
    } else {
      bar_arrive<NB_D, 256>();
      if ((s & 3) == 0) {
        fence_gpu();
        if (s > 0 && elect_one()) red_add_u32(&g_flags[FL_ATT + 2 * (s - 4)], 1);
      }
      if (rank == 0 || head < 16)
        reinterpret_cast<uint4*>(g_slot)[((s + ZS) & 3) * 3072 + ((s + ZS) & 4) * 8 + rank * 2048 + head * 64 + opaque32(lane)] = make_uint4(0, 0, 0, 0);
      if (HPF && head < 16 && rank == 0 && s + HPF < NSEG && elect_one())
        asm volatile("cp.async.bulk.prefetch.L2.global [%0], 4096;" :: "l"(g_h + (size_t)((s + HPF) * 16 + head) * 4096) : "memory");
    }
    const uint32_t t_red = clk32();
    uint32_t v[8];
    const float* slot = SLOT(s);
    TRACE(13);
    if (WG == 0) {
      if (!isC) {
        const int ln = opaque32(lane), kg = w - (ln >> 3);
        const uint32_t r16 = sb + R_P + w * 768 + (ln & 7) * 16;
        const uint32_t ta = r16 + (kg >= 0 ? kg * 128 : 640);
        const int dg = (ln >> 2) - 2 * (ln & 3);
        const uint32_t keep = dg > 0 ? 0xffffffffu : dg == 0 ? 0x0000ffffu : 0u;
        mbar_wait(bars + B_TS, par);
        uint32_t x[6], y[4];
        ldsm4t(x, ta); ldsm4t(y, ta + 3072); ldsm2t(x + 4, r16 + 512 + ((ln >> 3) & 1) * 3072);
#pragma unroll
        for (int j = 0; j < 5; j++) x[j] = hadd2(x[j], j < 4 ? y[j] : x[5]);
        x[0] = (x[0] & keep) | (0xff80ff80u & ~keep);
        float sv[10];
        exp10(sv, x);
        float sum = (((sv[0] + sv[1]) + (sv[2] + sv[3])) + ((sv[4] + sv[5]) + (sv[6] + sv[7]))) + (sv[8] + sv[9]);
        sum += __shfl_xor_sync(0xffffffffu, sum, 1);
        sum += __shfl_xor_sync(0xffffffffu, sum, 2);
        const float inv = rcp(sum);
#pragma unroll
        for (int j = 0; j < 5; j++) x[j] = pack2(sv[2 * j] * inv, sv[2 * j + 1] * inv);
        stsm4(r16 + (kg & 3) * 128, x);
        sts32(sb + ln * 4 + w * 768 + R_P + 512, x[4]);
        fence_async_smem();
        bar_arrive<NB_P, 256>();
      }
      while (clk32() - t_red < POLL_DELAY) {}
      load_red(v, slot);
      bar_sync<NB_E, 256>();
    } else {
      mbar_wait(bars + B_FB, 1);
    }
    TRACE(14);
    float ao[16];
    if (WG == 1) zero_regs<16>(ao);
    WG_FENCE();
#pragma unroll
    for (int k = 0; k < 32; k++) {
      if (WG == 0 && k == 16) WG_COMMIT();
      wg_rs32<1>(acc, W[16 + k][0], W[16 + k][1], W[16 + k][2], W[16 + k][3], dsc.tok[k]);
    }
    WG_COMMIT();
    TRACE(12);
    if (WG == 1) {
      if (!isC) {
        constexpr uint64_t dP = mkdesc(0x400 + R_P, 128, 768, 0);
        const uint64_t dV = mkdesc(0x400 + R_VT, 128, 512, 0) + rank * 256, dM = mkdesc(0x400 + R_VM, 0, 128, 0) + rank * 64;
        bar_sync<NB_P, 256>();
        WG_FENCE();
        wg_ss32<0>(ao, dV, dP); wg_ss32<0>(ao, dV + 16, dP + 16); wg_ss32<0>(ao, dM, dP + 32);
        WG_COMMIT();
      }
      bar_arrive<NB_E, 256>();
      if (elect_one()) mbar_expect(bars + B_XS + 8 * w, arm_bytes);
      while (clk32() - t_red < POLL_DELAY1) {}
      load_red(v, slot);
      bar_arrive<NB_W0, 128>();
    } else {
      WG_WAIT(1);
      bar_arrive<NB_F, 256>();
      sched_fence(head, 100);
      v[3] = opaque32(v[3]);
      const uint32_t tries = finish_red(v, slot);
      forward(std::integral_constant<int, 0>(), v, s, tries);
      TRACE(16);
    }
    WG_WAIT(0);
    reg_fence<16>(acc);
    if (WG == 0) bar_arrive<NB_G, 256>();
    TRACE(15);
    {
      uint32_t pq[8];
#pragma unroll
      for (int j = 0; j < 8; j++) pq[j] = pack2(acc[2 * j], acc[2 * j + 1]);
      if (WG == 1) {
        reg_fence<16>(ao);
#pragma unroll
        for (int j = 0; j < 8; j++) pk[j] = pack2(ao[2 * j], ao[2 * j + 1]);
      }
      if (!isC) {
        const uint32_t q = L4 + w * 256 + R_QK + WG * 5120;
#pragma unroll
        for (int j = 0; j < 8; j++) sts32(q + (j >> 1) * 1024 + (j & 1) * 128, pq[j]);
        if (WG == 1 && !ATT_LATE && s >= 0) store_att(s);
      } else {
        const uint32_t a = LV + warp * 1024;
        stsm4(a, pq); stsm4(a + 256, pq + 4);
      }
    }
    TRACE(17);
    if (WG == 1) {
      auto refill = [&]() {
        bar_sync<NB_F, 256>();
        if (s < NSEG - 2 && elect_one()) load_chunk(sb + R_GA + w * 4096, s + 2, 12 + w, bars + B_FA);
      };
      if (RF_FIRST) refill();
      if (has_wo) { v[3] = opaque32(v[3]); const uint32_t tries = finish_red(v, slot); forward(std::integral_constant<int, 1>(), v, s, tries); }
      if (!RF_FIRST) refill();
      TRACE(16);
    }
    if (isC && V_FENCE) { fence_async_smem(); __syncwarp(); }
    TRACE(18);
  }
  if (WG == 1 && ATT_LATE && !isC) store_att(NSEG - 1);
  if (WG == 1) bar_sync<NB_G, 256>();
  mbar_wait_safe(bars + B_MB + 8, 0); mbar_wait_safe(bars + B_MB + 16, 0); mbar_wait_safe(bars + B_MB + 24, 0);
#undef L16
#undef L8
#undef L4
#undef SLOT
#undef LV
}

__global__ void __cluster_dims__(3, 1, 1) __launch_bounds__(256, 1)
kernel_R(const __grid_constant__ CUtensorMap tmq, const __grid_constant__ CUtensorMap tmk, const __grid_constant__ CUtensorMap tmv,
         const __grid_constant__ CUtensorMap tmo, const __grid_constant__ CUtensorMap tmm, const __nv_bfloat16* __restrict__ x,
         const __nv_bfloat16* __restrict__ mem0, const __nv_bfloat16* __restrict__ cvec, const __grid_constant__ RDesc dsc) {
  extern __shared__ __align__(1024) uint8_t smem[];
  const uint32_t sb = smem_u32(smem);
  uint32_t rank; asm("mov.u32 %0, %%cluster_ctarank;" : "=r"(rank));
  rank = __shfl_sync(0xffffffffu, rank, 0);
  const int cta = blockIdx.x, head = __shfl_sync(0xffffffffu, cta / 3, 0);
  const int tid = threadIdx.x, lane = tid & 31;
  const int warp = __shfl_sync(0xffffffffu, tid >> 5, 0);
  const int wg = warp >> 2, w = warp & 3;
  const uint32_t bars = sb + R_BAR;
  const CUtensorMap* tmw = rank == 2 ? &tmv : (wg == 0 ? &tmq : &tmk);
  const int fcol = head * 128 + (rank == 2 ? wg * 64 : (int)rank * 64);

  asm volatile("griddepcontrol.launch_dependents;");
  uint32_t W[48][4];
  {
    if (sb != (rank << 24) + 0x400) __trap();
    if (tid == 0) {
      sts64(bars + 248, rank, head);
      mbar_init(bars + B_MB, 4); mbar_init(bars + B_MB + 8, 1); mbar_init(bars + B_MB + 16, 1); mbar_init(bars + B_MB + 24, SELF_STAS ? 1 : rank == 2 ? 5 : 4);
      for (int i = B_XS; i <= B_X; i += 8) mbar_init(bars + i, i == B_FA || i == B_FB || (i == B_TS && rank < 2) ? 4 : 1);
      asm volatile("fence.mbarrier_init.release.cluster;" ::: "memory");
      fence_async_smem();
    }
    __syncthreads();
    asm volatile("barrier.cluster.arrive.relaxed.aligned;" ::: "memory");
    TS(0);
    const int nwm = rank == 0 ? 6 : 5, wm0 = rank == 0 ? 0 : 5 * rank + 1, nrg = cta < 64 ? 3 : 2;
    if (elect_one()) {
      if (warp == 0) { mbar_expect(bars + B_WM, nwm * 8192); mbar_expect(bars + B_X, nrg * 16384); }
      if (warp < nwm) tma2d_p(sb + R_GA + warp * 8192, &tmm, head * 64, (wm0 + warp) * 64, bars + B_WM, POL_RW);
#pragma unroll 1
      for (int r = 0; r < nrg; r++) bulk_g2s(sb + R_TAIL + (r * 8 + warp) * 2064, x + (size_t)((cta + 96 * r) * 8 + warp) * D_, 2048, bars + B_X);
      if (w == 0) mbar_expect(bars + B_STG + wg * 16, 49152);
      if (w < 2) tma2d_p(sb + R_WO + wg * 49152 + w * 8192, tmw, fcol, rot_chunk(w, rank) * 64, bars + B_STG + wg * 16, POL_RW);
    }
    float* scr = reinterpret_cast<float*>(smem + R_VT);
#pragma unroll 1
    for (int i = tid; i < nwm * 64; i += 256) {
      const float c = __bfloat162float(cvec[wm0 * 64 + i]);
      scr[i] = __bfloat162float(__float2bfloat16(c / (1.f + __expf(-c))));
    }
    if (tid < 128) {
      uint32_t e[4] = {0u, 0u, 0u, 0u};
      if (cta >= 72 && (tid & 32)) {
        const uint16_t* mp = reinterpret_cast<const uint16_t*>(mem0) + 2 * (lane & 3) * D_ + (lane >> 2);
#pragma unroll
        for (int q = 0; q < 3; q++) {
          const int n = 3 * (tid >> 6) + q, col = wo_tile(3 * (cta & 7) + (n >> 1), (cta - 72) >> 3) * 16 + 8 * (n & 1);
          e[q] = mp[col] | (uint32_t)mp[col + D_] << 16;
        }
        e[3] = 0x42000000u;
      }
      reinterpret_cast<uint4*>(g_slot)[cta * 128 + tid] = make_uint4(e[0], e[1], e[2], e[3]);
    }
    __syncthreads();
    TS(1);
    mbar_wait_safe(bars + B_WM, 0);
    if (elect_one()) tma2d_p(sb + R_WO + wg * 49152 + (2 + w) * 8192, tmw, fcol, rot_chunk(2 + w, rank) * 64, bars + B_STG + wg * 16, POL_RW);
    {
      float a[8];
#pragma unroll
      for (int j = 0; j < 8; j++) a[j] = 0.f;
#pragma unroll 2
      for (int i = 0; i < 2 * nwm; i++) {
        uint32_t u[4];
        lds128(u, sb + R_GA + i * 4096 + tid * 16);
        const float sc = scr[i * 32 + (tid >> 3)];
#pragma unroll
        for (int j = 0; j < 4; j++) { a[2 * j] += sc * bf_lo(u[j]); a[2 * j + 1] += sc * bf_hi(u[j]); }
      }
#pragma unroll
      for (int j = 0; j < 8; j++) { a[j] += __shfl_xor_sync(0xffffffffu, a[j], 8); a[j] += __shfl_xor_sync(0xffffffffu, a[j], 16); }
      if (lane < 8) {
        sts128(sb + R_VT + 1536 + warp * 256 + lane * 32, __float_as_uint(a[0]), __float_as_uint(a[1]), __float_as_uint(a[2]), __float_as_uint(a[3]));
        sts128(sb + R_VT + 1552 + warp * 256 + lane * 32, __float_as_uint(a[4]), __float_as_uint(a[5]), __float_as_uint(a[6]), __float_as_uint(a[7]));
      }
    }
    __syncthreads();
    TS(2);
    if (warp == 7) {
      float t0 = 0.f, t1 = 0.f;
#pragma unroll
      for (int i = 0; i < 8; i++) { float t[2]; lds64f(t, sb + R_VT + 1536 + i * 256 + lane * 8); t0 += t[0]; t1 += t[1]; }
      reinterpret_cast<float2*>(g_modp + rank * 2048 + head * 64)[lane] = make_float2(t0, t1);
      fence_gpu();
      __syncwarp();
      if (lane == 0) red_add_u32(&g_flags[FL_S1], 1);
      __syncwarp();
    }
    mbar_wait_safe(bars + B_X, 0);
#pragma unroll 1
    for (int r = 0; r < nrg; r++) {
      float f[32];
#pragma unroll
      for (int i = 0; i < 4; i++) {
        uint32_t u[4];
        lds128(u, sb + R_TAIL + (r * 8 + warp) * 2064 + i * 512 + lane * 16);
#pragma unroll
        for (int j = 0; j < 4; j++) { f[8 * i + 2 * j] = bf_lo(u[j]); f[8 * i + 2 * j + 1] = bf_hi(u[j]); }
      }
      float t = 0.f;
#pragma unroll
      for (int i = 0; i < 32; i++) t += f[i];
#pragma unroll
      for (int o = 1; o < 32; o <<= 1) t += __shfl_xor_sync(0xffffffffu, t, o);
      const float mean = t * (1.f / D_);
      t = 0.f;
#pragma unroll
      for (int i = 0; i < 32; i++) t = fmaf(f[i] - mean, f[i] - mean, t);
#pragma unroll
      for (int o = 1; o < 32; o <<= 1) t += __shfl_xor_sync(0xffffffffu, t, o);
      const float rstd = rsqrtf(t * (1.f / D_) + 1e-5f);
      if (lane == 0) sts64(sb + R_VT + 3584 + (r * 8 + warp) * 8, __float_as_uint(rstd), __float_as_uint(-mean * rstd));
    }
    TS(3);
    if (w < PF1 && elect_one()) tma2d_prefetch_p(tmw, fcol, rot_chunk(6 + w, rank) * 64, POL_RW);
    if (tid == 0) wait_flag(&g_flags[FL_S1], 96);
    __syncthreads();
    TS(4);
    {
      float4 p[6];
#pragma unroll
      for (int i = 0; i < 6; i++) p[i] = __ldcg(reinterpret_cast<const float4*>(g_modp + (i >> 1) * 2048) + 2 * tid + (i & 1));
      if (w < PF2 && elect_one()) tma2d_prefetch_p(tmw, fcol, (9 + w) * 64, POL_RW);
      sts128(sb + R_VT + 5120 + tid * 16, pack2(p[0].x + p[2].x + p[4].x, p[0].y + p[2].y + p[4].y), pack2(p[0].z + p[2].z + p[4].z, p[0].w + p[2].w + p[4].w),
             pack2(p[1].x + p[3].x + p[5].x, p[1].y + p[3].y + p[5].y), pack2(p[1].z + p[3].z + p[5].z, p[1].w + p[3].w + p[5].w));
    }
    __syncthreads();
#pragma unroll 2
    for (int it = 0; it < 4 * nrg; it++) {
      const int r = it >> 2, rg = cta + 96 * r, c = 16 * warp + (lane >> 3) + 4 * (it & 3);
      uint32_t a[4], b[4], u[4], o[4];
      float t[2];
      lds128(u, sb + R_TAIL + (r * 8 + (lane & 7)) * 2064 + c * 16);
      lds128(a, sb + R_VT + 5120 + c * 16); lds128(b, sb + R_VT + 7168 + c * 16);
      lds64f(t, sb + R_VT + 3584 + (r * 8 + (lane & 7)) * 8);
#pragma unroll
      for (int j = 0; j < 4; j++)
        o[j] = pack2(fmaf(fmaf(bf_lo(u[j]), t[0], t[1]), 1.f + bf_lo(b[j]), bf_lo(a[j])), fmaf(fmaf(bf_hi(u[j]), t[0], t[1]), 1.f + bf_hi(b[j]), bf_hi(a[j])));
      *reinterpret_cast<uint4*>(g_h + (size_t)(rg >> 2) * 65536 + (lane & 7) * 16 + (c & 7) * 128 +
                                (c < 96 ? (c >> 3) * 4096 + (rg & 3) * 1024 : 49152 + (rg & 3) * 4096 + ((c >> 3) - 12) * 1024)) =
          make_uint4(o[0], o[1], o[2], o[3]);
    }
    TS(5);
    __syncthreads();
    TS(6);
    if (w < PF3 && elect_one()) tma2d_p(sb + R_TAIL + warp * 8192, tmw, fcol, 768 + w * 64, bars + B_TAIL, POL_RW);
    if (warp == 3 && lane == 0) { fence_gpu(); red_add_u32(&g_flags[FL_S2], 1); }
    __syncwarp();

    const uint32_t a0 = opaque32(sb + R_WO + wg * 49152 + ((lane >> 4) * 8 + (lane & 7)) * 128 + (((2 * w + ((lane >> 3) & 1)) ^ (lane & 7)) << 4));
    mbar_wait_safe(bars + B_STG + wg * 16, 0);
    TS(7);
#pragma unroll
    for (int i = 0; i < 24; i++) ldsm4t(W[i], a0 + i * 2048);
    if (tid == 0) wait_flag(&g_flags[FL_S2], 96);
    __syncthreads();
    asm volatile("fence.proxy.async.global;" ::: "memory");
    if (elect_one()) {
      if (wg == 0) load_chunk(sb + R_GA + w * 4096, 0, 12 + w, bars + B_FA);
      if (w == 0) mbar_expect(bars + B_STG + wg * 16 + 8, 49152);
#pragma unroll 1
      for (int c = w; c < 6; c += 4) tma2d_p(sb + R_WO + wg * 49152 + c * 8192, tmw, fcol, rot_chunk(6 + c, rank) * 64, bars + B_STG + wg * 16 + 8, POL_RW);
      if (warp == 0) mbar_expect(bars + B_TAIL, 65536);
      if (w >= PF3) tma2d_p(sb + R_TAIL + warp * 8192, tmw, fcol, 768 + w * 64, bars + B_TAIL, POL_RW);
      if (wg == 1) mbar_expect(bars + B_XS + 8 * w, w == 2 ? 0 : arm_size(w, rank == 2));
#pragma unroll 1
      for (int i = warp; i < PF4; i += 8) tma2d_prefetch(&tmo, 16 * wo_tile(i, rank), head * 128);
    }
    TS(8);
    mbar_wait_safe(bars + B_STG + wg * 16 + 8, 0);
    TS(9);
#pragma unroll
    for (int i = 0; i < 24; i++) ldsm4t(W[24 + i], a0 + i * 2048);
    __syncthreads();
    if (elect_one()) {
      const int n = rank == 2 ? 22 : 21;
      if (warp == 0) mbar_expect(bars + B_WO, n * 4096);
#pragma unroll 1
      for (int i = warp; i < n; i += 8) tma2d(sb + R_WO + i * 4096, &tmo, 16 * wo_tile(i, rank), head * 128, bars + B_WO);
    }
    sts32(sb + R_P + warp * 768 + 640 + lane * 4, wg == 0 ? 0u : 0xff80ff80u);
    mbar_wait_safe(bars + B_TAIL, 0);
    asm volatile("barrier.cluster.wait.aligned;\nbarrier.cluster.arrive.relaxed.aligned;\nbarrier.cluster.wait.aligned;" ::: "memory");
  }
  uint32_t rh[2];
  lds64(rh, bars + 248);
  rh[0] = __shfl_sync(0xffffffffu, rh[0], 0); rh[1] = __shfl_sync(0xffffffffu, rh[1], 0);
  if (wg == 0) r_main<0>(W, dsc, rh[1], rh[0], lane, w);
  else r_main<1>(W, dsc, rh[1], rh[0], lane, w);
  __syncthreads();
  if (rank < 2 && threadIdx.x == 0) { fence_gpu(); red_add_u32(&g_flags[FL_ATT + 8 * 15], 1); }
  asm volatile("barrier.cluster.arrive.release.aligned;\nbarrier.cluster.wait.acquire.aligned;" ::: "memory");
}

template <int TA> __device__ __forceinline__ void wg_ss256(float* d, uint64_t a, uint64_t b) {
  asm volatile("wgmma.mma_async.sync.aligned.m64n256k16.f32.bf16.bf16 {%0,%1,%2,%3,%4,%5,%6,%7,%8,%9,%10,%11,%12,%13,%14,%15,%16,%17,%18,%19,%20,%21,%22,%23,%24,%25,%26,%27,%28,%29,%30,%31,%32,%33,%34,%35,%36,%37,%38,%39,%40,%41,%42,%43,%44,%45,%46,%47,%48,%49,%50,%51,%52,%53,%54,%55,%56,%57,%58,%59,%60,%61,%62,%63,%64,%65,%66,%67,%68,%69,%70,%71,%72,%73,%74,%75,%76,%77,%78,%79,%80,%81,%82,%83,%84,%85,%86,%87,%88,%89,%90,%91,%92,%93,%94,%95,%96,%97,%98,%99,%100,%101,%102,%103,%104,%105,%106,%107,%108,%109,%110,%111,%112,%113,%114,%115,%116,%117,%118,%119,%120,%121,%122,%123,%124,%125,%126,%127}, %128, %129, 1, 1, 1, %130, 1;"
               : "+f"(d[0]), "+f"(d[1]), "+f"(d[2]), "+f"(d[3]), "+f"(d[4]), "+f"(d[5]), "+f"(d[6]), "+f"(d[7]),
                 "+f"(d[8]), "+f"(d[9]), "+f"(d[10]), "+f"(d[11]), "+f"(d[12]), "+f"(d[13]), "+f"(d[14]), "+f"(d[15]),
                 "+f"(d[16]), "+f"(d[17]), "+f"(d[18]), "+f"(d[19]), "+f"(d[20]), "+f"(d[21]), "+f"(d[22]), "+f"(d[23]),
                 "+f"(d[24]), "+f"(d[25]), "+f"(d[26]), "+f"(d[27]), "+f"(d[28]), "+f"(d[29]), "+f"(d[30]), "+f"(d[31]),
                 "+f"(d[32]), "+f"(d[33]), "+f"(d[34]), "+f"(d[35]), "+f"(d[36]), "+f"(d[37]), "+f"(d[38]), "+f"(d[39]),
                 "+f"(d[40]), "+f"(d[41]), "+f"(d[42]), "+f"(d[43]), "+f"(d[44]), "+f"(d[45]), "+f"(d[46]), "+f"(d[47]),
                 "+f"(d[48]), "+f"(d[49]), "+f"(d[50]), "+f"(d[51]), "+f"(d[52]), "+f"(d[53]), "+f"(d[54]), "+f"(d[55]),
                 "+f"(d[56]), "+f"(d[57]), "+f"(d[58]), "+f"(d[59]), "+f"(d[60]), "+f"(d[61]), "+f"(d[62]), "+f"(d[63]),
                 "+f"(d[64]), "+f"(d[65]), "+f"(d[66]), "+f"(d[67]), "+f"(d[68]), "+f"(d[69]), "+f"(d[70]), "+f"(d[71]),
                 "+f"(d[72]), "+f"(d[73]), "+f"(d[74]), "+f"(d[75]), "+f"(d[76]), "+f"(d[77]), "+f"(d[78]), "+f"(d[79]),
                 "+f"(d[80]), "+f"(d[81]), "+f"(d[82]), "+f"(d[83]), "+f"(d[84]), "+f"(d[85]), "+f"(d[86]), "+f"(d[87]),
                 "+f"(d[88]), "+f"(d[89]), "+f"(d[90]), "+f"(d[91]), "+f"(d[92]), "+f"(d[93]), "+f"(d[94]), "+f"(d[95]),
                 "+f"(d[96]), "+f"(d[97]), "+f"(d[98]), "+f"(d[99]), "+f"(d[100]), "+f"(d[101]), "+f"(d[102]), "+f"(d[103]),
                 "+f"(d[104]), "+f"(d[105]), "+f"(d[106]), "+f"(d[107]), "+f"(d[108]), "+f"(d[109]), "+f"(d[110]), "+f"(d[111]),
                 "+f"(d[112]), "+f"(d[113]), "+f"(d[114]), "+f"(d[115]), "+f"(d[116]), "+f"(d[117]), "+f"(d[118]), "+f"(d[119]),
                 "+f"(d[120]), "+f"(d[121]), "+f"(d[122]), "+f"(d[123]), "+f"(d[124]), "+f"(d[125]), "+f"(d[126]), "+f"(d[127])
               : "l"(a), "l"(b), "n"(TA));
}
template <int TA> __device__ __forceinline__ void wg_ss128(float* d, uint64_t a, uint64_t b) {
  asm volatile("wgmma.mma_async.sync.aligned.m64n128k16.f32.bf16.bf16 {%0,%1,%2,%3,%4,%5,%6,%7,%8,%9,%10,%11,%12,%13,%14,%15,%16,%17,%18,%19,%20,%21,%22,%23,%24,%25,%26,%27,%28,%29,%30,%31,%32,%33,%34,%35,%36,%37,%38,%39,%40,%41,%42,%43,%44,%45,%46,%47,%48,%49,%50,%51,%52,%53,%54,%55,%56,%57,%58,%59,%60,%61,%62,%63}, %64, %65, 1, 1, 1, %66, 1;"
               : "+f"(d[0]), "+f"(d[1]), "+f"(d[2]), "+f"(d[3]), "+f"(d[4]), "+f"(d[5]), "+f"(d[6]), "+f"(d[7]),
                 "+f"(d[8]), "+f"(d[9]), "+f"(d[10]), "+f"(d[11]), "+f"(d[12]), "+f"(d[13]), "+f"(d[14]), "+f"(d[15]),
                 "+f"(d[16]), "+f"(d[17]), "+f"(d[18]), "+f"(d[19]), "+f"(d[20]), "+f"(d[21]), "+f"(d[22]), "+f"(d[23]),
                 "+f"(d[24]), "+f"(d[25]), "+f"(d[26]), "+f"(d[27]), "+f"(d[28]), "+f"(d[29]), "+f"(d[30]), "+f"(d[31]),
                 "+f"(d[32]), "+f"(d[33]), "+f"(d[34]), "+f"(d[35]), "+f"(d[36]), "+f"(d[37]), "+f"(d[38]), "+f"(d[39]),
                 "+f"(d[40]), "+f"(d[41]), "+f"(d[42]), "+f"(d[43]), "+f"(d[44]), "+f"(d[45]), "+f"(d[46]), "+f"(d[47]),
                 "+f"(d[48]), "+f"(d[49]), "+f"(d[50]), "+f"(d[51]), "+f"(d[52]), "+f"(d[53]), "+f"(d[54]), "+f"(d[55]),
                 "+f"(d[56]), "+f"(d[57]), "+f"(d[58]), "+f"(d[59]), "+f"(d[60]), "+f"(d[61]), "+f"(d[62]), "+f"(d[63])
               : "l"(a), "l"(b), "n"(TA));
}
template <int TA> __device__ __forceinline__ void wg_ss256_first(float* d, uint64_t a, uint64_t b) {
  asm volatile("wgmma.mma_async.sync.aligned.m64n256k16.f32.bf16.bf16 {%0,%1,%2,%3,%4,%5,%6,%7,%8,%9,%10,%11,%12,%13,%14,%15,%16,%17,%18,%19,%20,%21,%22,%23,%24,%25,%26,%27,%28,%29,%30,%31,%32,%33,%34,%35,%36,%37,%38,%39,%40,%41,%42,%43,%44,%45,%46,%47,%48,%49,%50,%51,%52,%53,%54,%55,%56,%57,%58,%59,%60,%61,%62,%63,%64,%65,%66,%67,%68,%69,%70,%71,%72,%73,%74,%75,%76,%77,%78,%79,%80,%81,%82,%83,%84,%85,%86,%87,%88,%89,%90,%91,%92,%93,%94,%95,%96,%97,%98,%99,%100,%101,%102,%103,%104,%105,%106,%107,%108,%109,%110,%111,%112,%113,%114,%115,%116,%117,%118,%119,%120,%121,%122,%123,%124,%125,%126,%127}, %128, %129, 0, 1, 1, %130, 1;"
               : "=f"(d[0]), "=f"(d[1]), "=f"(d[2]), "=f"(d[3]), "=f"(d[4]), "=f"(d[5]), "=f"(d[6]), "=f"(d[7]),
                 "=f"(d[8]), "=f"(d[9]), "=f"(d[10]), "=f"(d[11]), "=f"(d[12]), "=f"(d[13]), "=f"(d[14]), "=f"(d[15]),
                 "=f"(d[16]), "=f"(d[17]), "=f"(d[18]), "=f"(d[19]), "=f"(d[20]), "=f"(d[21]), "=f"(d[22]), "=f"(d[23]),
                 "=f"(d[24]), "=f"(d[25]), "=f"(d[26]), "=f"(d[27]), "=f"(d[28]), "=f"(d[29]), "=f"(d[30]), "=f"(d[31]),
                 "=f"(d[32]), "=f"(d[33]), "=f"(d[34]), "=f"(d[35]), "=f"(d[36]), "=f"(d[37]), "=f"(d[38]), "=f"(d[39]),
                 "=f"(d[40]), "=f"(d[41]), "=f"(d[42]), "=f"(d[43]), "=f"(d[44]), "=f"(d[45]), "=f"(d[46]), "=f"(d[47]),
                 "=f"(d[48]), "=f"(d[49]), "=f"(d[50]), "=f"(d[51]), "=f"(d[52]), "=f"(d[53]), "=f"(d[54]), "=f"(d[55]),
                 "=f"(d[56]), "=f"(d[57]), "=f"(d[58]), "=f"(d[59]), "=f"(d[60]), "=f"(d[61]), "=f"(d[62]), "=f"(d[63]),
                 "=f"(d[64]), "=f"(d[65]), "=f"(d[66]), "=f"(d[67]), "=f"(d[68]), "=f"(d[69]), "=f"(d[70]), "=f"(d[71]),
                 "=f"(d[72]), "=f"(d[73]), "=f"(d[74]), "=f"(d[75]), "=f"(d[76]), "=f"(d[77]), "=f"(d[78]), "=f"(d[79]),
                 "=f"(d[80]), "=f"(d[81]), "=f"(d[82]), "=f"(d[83]), "=f"(d[84]), "=f"(d[85]), "=f"(d[86]), "=f"(d[87]),
                 "=f"(d[88]), "=f"(d[89]), "=f"(d[90]), "=f"(d[91]), "=f"(d[92]), "=f"(d[93]), "=f"(d[94]), "=f"(d[95]),
                 "=f"(d[96]), "=f"(d[97]), "=f"(d[98]), "=f"(d[99]), "=f"(d[100]), "=f"(d[101]), "=f"(d[102]), "=f"(d[103]),
                 "=f"(d[104]), "=f"(d[105]), "=f"(d[106]), "=f"(d[107]), "=f"(d[108]), "=f"(d[109]), "=f"(d[110]), "=f"(d[111]),
                 "=f"(d[112]), "=f"(d[113]), "=f"(d[114]), "=f"(d[115]), "=f"(d[116]), "=f"(d[117]), "=f"(d[118]), "=f"(d[119]),
                 "=f"(d[120]), "=f"(d[121]), "=f"(d[122]), "=f"(d[123]), "=f"(d[124]), "=f"(d[125]), "=f"(d[126]), "=f"(d[127])
               : "l"(a), "l"(b), "n"(TA));
}
template <int TA> __device__ __forceinline__ void wg_ss128_first(float* d, uint64_t a, uint64_t b) {
  asm volatile("wgmma.mma_async.sync.aligned.m64n128k16.f32.bf16.bf16 {%0,%1,%2,%3,%4,%5,%6,%7,%8,%9,%10,%11,%12,%13,%14,%15,%16,%17,%18,%19,%20,%21,%22,%23,%24,%25,%26,%27,%28,%29,%30,%31,%32,%33,%34,%35,%36,%37,%38,%39,%40,%41,%42,%43,%44,%45,%46,%47,%48,%49,%50,%51,%52,%53,%54,%55,%56,%57,%58,%59,%60,%61,%62,%63}, %64, %65, 0, 1, 1, %66, 1;"
               : "=f"(d[0]), "=f"(d[1]), "=f"(d[2]), "=f"(d[3]), "=f"(d[4]), "=f"(d[5]), "=f"(d[6]), "=f"(d[7]),
                 "=f"(d[8]), "=f"(d[9]), "=f"(d[10]), "=f"(d[11]), "=f"(d[12]), "=f"(d[13]), "=f"(d[14]), "=f"(d[15]),
                 "=f"(d[16]), "=f"(d[17]), "=f"(d[18]), "=f"(d[19]), "=f"(d[20]), "=f"(d[21]), "=f"(d[22]), "=f"(d[23]),
                 "=f"(d[24]), "=f"(d[25]), "=f"(d[26]), "=f"(d[27]), "=f"(d[28]), "=f"(d[29]), "=f"(d[30]), "=f"(d[31]),
                 "=f"(d[32]), "=f"(d[33]), "=f"(d[34]), "=f"(d[35]), "=f"(d[36]), "=f"(d[37]), "=f"(d[38]), "=f"(d[39]),
                 "=f"(d[40]), "=f"(d[41]), "=f"(d[42]), "=f"(d[43]), "=f"(d[44]), "=f"(d[45]), "=f"(d[46]), "=f"(d[47]),
                 "=f"(d[48]), "=f"(d[49]), "=f"(d[50]), "=f"(d[51]), "=f"(d[52]), "=f"(d[53]), "=f"(d[54]), "=f"(d[55]),
                 "=f"(d[56]), "=f"(d[57]), "=f"(d[58]), "=f"(d[59]), "=f"(d[60]), "=f"(d[61]), "=f"(d[62]), "=f"(d[63])
               : "l"(a), "l"(b), "n"(TA));
}

constexpr uint32_t H_SB = 0x400;
constexpr int H_STAGE = 49152, H_NST = 4;
constexpr int H_STG = H_NST * H_STAGE;
constexpr int H_VEC = H_STG + 3 * 8192;
constexpr int H_GATE = H_VEC + 6656;
constexpr int H_BAR = H_GATE + 1024;
constexpr int H_SMEM = H_BAR + 256;
constexpr int HB_FULL = 0, HB_EMPTY = 32, HB_IFULL = 64, HB_IEMPTY = 80, HB_VFULL = 96, HB_STGF = 112, HB_ITEM = 120, HB_Q = 128, HB_SRDY = 160, HB_SFREE = 184,
              HB_MFULL = 208, HB_MEMPTY = 224, HB_MAIL = 240;
constexpr int NB_HX = 4, NB_HY = 5, NB_HZ = 6;
enum { IT_END = 0, IT_MOD = 1, IT_XT = 2, IT_OUT = 3, IT_WS = 4, IT_F1 = 5, IT_F2 = 6, IT_STAT = 7 };
constexpr int N_MOD = 32, N_WS = 28, N_XT = 2, N_STAT = 4;
constexpr int MAX_ITEMS = 1400;
#define NH2 94
constexpr int NH1 = 36;
struct HList { uint32_t n, head, tbase; uint32_t it[MAX_ITEMS]; };
#define HT(i)

#define POL_WO L2_NORMAL
#define POL_W2 L2_NORMAL
#define POL_ATT L2_FIRST
#define POL_ACT L2_FIRST
#define POL_PRE L2_FIRST
__device__ __forceinline__ void mbar_arrive_n(uint32_t b, uint32_t n) { asm volatile("mbarrier.arrive.shared::cta.b64 _, [%0], %1;" :: "r"(b), "r"(n) : "memory"); }
__device__ __forceinline__ void mbar_arrive_cl(uint32_t b) { asm volatile("mbarrier.arrive.shared::cluster.b64 _, [%0];" :: "r"(b) : "memory"); }
__device__ __forceinline__ void h_free(uint32_t b, uint32_t pm) { mbar_arrive(b); mbar_arrive_cl(b ^ pm); }
__device__ __forceinline__ void tma2d_mc(uint32_t dst, const CUtensorMap* m, int c0, int c1, uint32_t bar, uint64_t pol) {
  asm volatile("cp.async.bulk.tensor.2d.shared::cluster.global.mbarrier::complete_tx::bytes.multicast::cluster.L2::cache_hint [%0], [%1, {%3, %4}], [%2], %5, %6;"
               :: "r"(dst), "l"(m), "r"(bar), "r"(c0), "r"(c1), "h"((uint16_t)3), "l"(pol) : "memory");
}
__device__ __forceinline__ void bulk_mc(uint32_t dst, const void* src, uint32_t bytes, uint32_t bar, uint64_t pol) {
  asm volatile("cp.async.bulk.shared::cluster.global.mbarrier::complete_tx::bytes.multicast::cluster.L2::cache_hint [%0], [%1], %2, [%3], %4, %5;"
               :: "r"(dst), "l"(src), "r"(bytes), "r"(bar), "h"((uint16_t)3), "l"(pol) : "memory");
}
__device__ __forceinline__ void cluster_sync() {
  asm volatile("barrier.cluster.arrive.release.aligned;\nbarrier.cluster.wait.acquire.aligned;" ::: "memory");
}
__device__ __forceinline__ void bulk_s2g(void* dst, uint32_t src, uint32_t bytes) {
  asm volatile("cp.async.bulk.global.shared::cta.bulk_group [%0], [%1], %2;" :: "l"(dst), "r"(src), "r"(bytes) : "memory");
}
__device__ __forceinline__ void tma2d_add(const CUtensorMap* m, int c0, int c1, uint32_t src) {
  asm volatile("cp.reduce.async.bulk.tensor.2d.global.shared::cta.add.tile.bulk_group [%0, {%2, %3}], [%1];" :: "l"(m), "r"(src), "r"(c0), "r"(c1) : "memory");
}
__device__ __forceinline__ void bulk_commit() { asm volatile("cp.async.bulk.commit_group;" ::: "memory"); }
template <int N> __device__ __forceinline__ void bulk_wait_read() { asm volatile("cp.async.bulk.wait_group.read %0;" :: "n"(N) : "memory"); }
__device__ __forceinline__ void bulk_wait_all() { asm volatile("cp.async.bulk.wait_group 0;" ::: "memory"); }
__device__ __forceinline__ uint32_t hfma2(uint32_t a, uint32_t b, uint32_t c) { uint32_t t; asm("fma.rn.bf16x2 %0, %1, %2, %3;" : "=r"(t) : "r"(a), "r"(b), "r"(c)); return t; }
__device__ __forceinline__ float lds32f(uint32_t a) { return __uint_as_float(lds32(a)); }

template <int BN, int TA, int K0, int K1>
__device__ __forceinline__ void h_mma(float* acc, uint64_t da, uint64_t db) {
#pragma unroll
  for (int k = K0; k < K1; k++) {
    const uint64_t a = da + k * (TA ? 256 : 2), b = db + k * 128;
    if (BN == 256) wg_ss256<TA>(acc, a, b); else wg_ss128<TA>(acc, a, b);
  }
}
template <int BN, int TA>
__device__ __forceinline__ void h_mainloop(float* acc, uint32_t sb, uint32_t pm, int nst, uint32_t& st, uint32_t& ph, int wg, bool leader, uint32_t clk_q) {
  const uint64_t da0 = TA ? mkdesc(H_SB + wg * 1024, 2048, 128, 0) : mkdesc(H_SB + wg * 8192, 16, 1024, 1);
  const uint64_t db0 = mkdesc(H_SB + 16384, 8192, 1024, 1);
  const uint32_t full = sb + H_BAR + HB_FULL, empty = sb + H_BAR + HB_EMPTY;
  uint32_t prev = st;
  {
    mbar_wait(full + st * 8, ph);
    HT(1);
    const uint64_t da = da0 + st * (H_STAGE >> 4), db = db0 + st * (H_STAGE >> 4);
    WG_FENCE();
    if (BN == 256) wg_ss256_first<TA>(acc, da, db); else wg_ss128_first<TA>(acc, da, db);
    h_mma<BN, TA, 1, 4>(acc, da, db);
    WG_COMMIT();
    if (++st == H_NST) { st = 0; ph ^= 1; }
  }
  {
    mbar_wait(full + st * 8, ph);
    const uint64_t da = da0 + st * (H_STAGE >> 4), db = db0 + st * (H_STAGE >> 4);
    WG_FENCE();
    h_mma<BN, TA, 0, 3>(acc, da, db);
    WG_COMMIT();
    h_mma<BN, TA, 3, 4>(acc, da, db);
    WG_COMMIT();
    WG_WAIT(1);
    if (leader) h_free(empty + prev * 8, pm);
    if (wg) bar_arrive<NB_HY, 256>(); else bar_sync<NB_HY, 256>();
    prev = st;
    if (++st == H_NST) { st = 0; ph ^= 1; }
  }
#pragma unroll 1
  for (int i = 4; i < nst; i++) {
    mbar_wait(full + st * 8, ph);
    const uint64_t da = da0 + st * (H_STAGE >> 4), db = db0 + st * (H_STAGE >> 4);
    WG_FENCE();
    h_mma<BN, TA, 0, 4>(acc, da, db);
    WG_COMMIT();
    WG_WAIT(1);
    if (leader) h_free(empty + prev * 8, pm);
    prev = st;
    if (++st == H_NST) { st = 0; ph ^= 1; }
  }
  if (wg) {
    WG_WAIT(0);
    if (leader) h_free(empty + prev * 8, pm);
    bar_sync<NB_HX, 256>();
  }
  {
    mbar_wait(full + st * 8, ph);
    const uint64_t da = da0 + st * (H_STAGE >> 4), db = db0 + st * (H_STAGE >> 4);
    WG_FENCE();
    h_mma<BN, TA, 0, 4>(acc, da, db);
    WG_COMMIT();
    WG_WAIT(1);
    if (leader && !wg) h_free(empty + prev * 8, pm);
    prev = st;
    if (++st == H_NST) { st = 0; ph ^= 1; }
  }
  {
    mbar_wait(full + st * 8, ph);
    const uint64_t da = da0 + st * (H_STAGE >> 4), db = db0 + st * (H_STAGE >> 4);
    WG_FENCE();
    h_mma<BN, TA, 0, 3>(acc, da, db);
    WG_COMMIT();
    h_mma<BN, TA, 3, 4>(acc, da, db);
    WG_COMMIT();
    WG_WAIT(1);
    if (leader) h_free(empty + prev * 8, pm);
    if (!wg) bar_arrive<NB_HX, 256>();
  }
}
__device__ __forceinline__ void h_release(uint32_t sb, uint32_t pm, uint32_t& st, uint32_t& ph, bool leader) {
  if (leader) h_free(sb + H_BAR + HB_EMPTY + st * 8, pm);
  if (++st == H_NST) { st = 0; ph ^= 1; }
}

__device__ __forceinline__ uint32_t stg_acquire(uint32_t sb, uint32_t g, uint32_t& b) {
  const uint32_t q = (g * 43691u) >> 17;
  b = g - 3 * q;
  mbar_wait(sb + H_BAR + HB_SFREE + b * 8, (q & 1) ^ 1);
  return sb + H_STG + b * 8192;
}
__device__ __forceinline__ void stg_release(uint32_t sb, uint32_t b, int lane) {
  __syncwarp();
  if (lane == 0) mbar_arrive(sb + H_BAR + HB_SRDY + b * 8);
}
__device__ __forceinline__ uint32_t hmul2(uint32_t a, uint32_t b) { uint32_t t; asm("mul.rn.bf16x2 %0, %1, %2;" : "=r"(t) : "r"(a), "r"(b)); return t; }
template <int BN>
__device__ __forceinline__ void h_gated(float* acc, uint32_t va, uint32_t vb, uint32_t vp, uint32_t sb, uint32_t pm, uint32_t& st, uint32_t& ph, uint32_t g0, int wg, bool leader,
                                        int warp, int lane, uint32_t clk_q) {
  uint32_t gt[BN / 8];
  mbar_wait(vb, vp);
#pragma unroll
  for (int i = 0; i < BN / 32; i++) lds128(gt + 4 * i, va + i * 64 + (lane & 3) * 16);
  WG_WAIT(0);
  reg_fence<BN / 2>(acc);
  h_release(sb, pm, st, ph, leader);
  HT(2);
  const uint32_t ro = ((warp & 3) * 16 + (lane & 7)) * 128, x0 = ((lane >> 3) ^ (lane & 7)) << 4;
  if (BN == 256 && wg) bar_sync<NB_HZ, 256>();
#pragma unroll
  for (int u = 0; u < BN / 64; u++) {
    uint32_t b;
    const uint32_t base = stg_acquire(sb, g0 + u, b) + ro;
    if (BN == 256 && u == 1 && !wg) bar_arrive<NB_HZ, 256>();
#pragma unroll
    for (int c2 = 0; c2 < 2; c2++) {
      const int c = 2 * u + c2;
#pragma unroll
      for (int h = 0; h < 2; h++) {
        uint32_t y[4];
#pragma unroll
        for (int j = 0; j < 4; j++) { const float* a = acc + c * 16 + j * 4 + h * 2; y[j] = hmul2(pack2(a[0], a[1]), gt[4 * c + j]); }
        stsm4(base + h * 1024 + (x0 ^ (c2 << 6)), y);
      }
    }
    stg_release(sb, b, lane);
  }
}

template <int BN>
__device__ __forceinline__ void h_swiglu(float* acc, uint32_t vb, uint32_t vp, uint32_t sb, uint32_t pm, uint32_t& st, uint32_t& ph, uint32_t g0, int wg, bool leader,
                                         int warp, int lane, uint32_t clk_q) {
  float rs[2], rh[2];
  mbar_wait(vb, vp);
  {
    const uint64_t da = mkdesc(H_SB + H_VEC + 4096 + wg * 1024, 0, 128, 0), db = mkdesc(H_SB + H_VEC, 1024, 0, 1);
    WG_FENCE();
    if (BN == 256) wg_ss256<0>(acc, da, db); else wg_ss128<0>(acc, da, db);
    WG_COMMIT();
  }
#pragma unroll
  for (int h = 0; h < 2; h++) { rs[h] = lds32f(sb + H_VEC + 6144 + (warp * 16 + h * 8 + (lane >> 2)) * 4); rh[h] = 0.5f * rs[h]; }
  WG_WAIT(1);
  h_release(sb, pm, st, ph, leader);
  WG_WAIT(0);
  reg_fence<BN / 2>(acc);
  HT(2);
  const uint32_t ro = ((warp & 3) * 16 + (lane & 7)) * 128, x0 = ((lane >> 3) ^ (lane & 7)) << 4;
#pragma unroll
  for (int uu = 0; uu < BN / 128; uu++) {
    uint32_t b;
    const uint32_t base = stg_acquire(sb, g0 + uu, b) + ro;
#pragma unroll
    for (int c2 = 0; c2 < 2; c2++) {
      const int c = 2 * uu + c2;
      uint32_t y[2][4];
#pragma unroll
      for (int j = 0; j < 4; j++) {
        const float* g = acc + 16 * c + 4 * j; const float* u = g + BN / 4;
        float o[4];
#pragma unroll
        for (int e = 0; e < 4; e++) {
          const float g2 = rh[e >> 1] * g[e];
          const float h = g2 * (rs[e >> 1] * u[e]);
          float t; asm("tanh.approx.f32 %0, %1;" : "=f"(t) : "f"(g2));
          o[e] = fmaf(h, t, h);
        }
        y[0][j] = pack2(o[0], o[1]); y[1][j] = pack2(o[2], o[3]);
      }
      stsm4(base + (x0 ^ (c2 << 6)), y[0]); stsm4(base + 1024 + (x0 ^ (c2 << 6)), y[1]);
    }
    stg_release(sb, b, lane);
  }
}

template <bool WS>
__device__ __forceinline__ void h_vecmat(uint32_t sb, int idx, uint32_t& st, uint32_t& ph, int tid, const __nv_bfloat16* cvec, uint8_t* w13s, uint8_t* bext,
                                         __nv_bfloat16* mod, __nv_bfloat16* gate) {
  const uint32_t stg = sb + H_STG, bars = sb + H_BAR;
  const int lane = tid & 31, warp = tid >> 5;
#pragma unroll
  for (int i = 0; i < 4; i++) {
    const int k = tid + 256 * i;
    if (WS) {
      const uint32_t s = __ldcg(reinterpret_cast<const uint16_t*>(mod) + 3 * D_ + k), c = __ldcg(reinterpret_cast<const uint16_t*>(mod) + 4 * D_ + k);
      sts32(stg + k * 4, s << 16); sts32(stg + 4096 + k * 4, c | c << 16);
    } else {
      const float c = __bfloat162float(cvec[k]);
      sts32(stg + k * 4, __float_as_uint(__bfloat162float(__float2bfloat16(c / (1.f + __expf(-c))))));
    }
  }
  bar_sync<1, 256>();
  float v[4][8], u[4][8];
#pragma unroll
  for (int b = 0; b < 4; b++)
#pragma unroll
    for (int e = 0; e < 8; e++) { v[b][e] = 0.f; u[b][e] = 0.f; }
  const int r0 = tid >> 3;
  const uint32_t off = 16384 + r0 * 128 + (((tid & 7) ^ (r0 & 7)) << 4);
  uint32_t prev = 0;
#pragma unroll 1
  for (int i = 0; i < (WS ? 16 : 8); i++) {
    mbar_wait(bars + HB_FULL + st * 8, ph);
    const uint32_t base = sb + st * H_STAGE + off;
#pragma unroll
    for (int ri = 0; ri < 2; ri++) {
      const uint32_t ka = stg + ((WS ? i * 64 : i * 128) + r0 + 32 * ri) * 4;
      const float m0 = lds32f(ka), m1 = WS ? m0 : lds32f(ka + 256);
      const uint32_t c2 = WS ? lds32(ka + 4096) : 0;
#pragma unroll
      for (int b = 0; b < 4; b++) {
        uint32_t w[4];
        lds128(w, base + b * 8192 + ri * 4096);
        const float m = b < 2 ? m0 : m1;
#pragma unroll
        for (int e = 0; e < 4; e++) {
          v[b][2 * e] = fmaf(m, bf_lo(w[e]), v[b][2 * e]); v[b][2 * e + 1] = fmaf(m, bf_hi(w[e]), v[b][2 * e + 1]);
          if (WS) { w[e] = hfma2(w[e], c2, w[e]); u[b][2 * e] += bf_lo(w[e]); u[b][2 * e + 1] += bf_hi(w[e]); }
        }
        if (WS) sts128(base + b * 8192 + ri * 4096, w[0], w[1], w[2], w[3]);
      }
    }
    if (WS) fence_async_smem();
    bar_sync<1, 256>();
    if (tid == 0) {
      if (WS) {
        bulk_s2g(w13s + (size_t)(idx * 16 + i) * 32768, sb + st * H_STAGE + 16384, 32768);
        bulk_commit();
        if (i > 0) { bulk_wait_read<1>(); mbar_arrive_n(bars + HB_EMPTY + prev * 8, 4); }
      } else mbar_arrive_n(bars + HB_EMPTY + st * 8, 4);
    }
    prev = st;
    if (++st == H_NST) { st = 0; ph ^= 1; }
  }
  if (WS && tid == 0) {
    bulk_wait_read<0>(); mbar_arrive_n(bars + HB_EMPTY + prev * 8, 4);
    bulk_wait_all(); fence_async_all(); fence_gpu();
  }
#pragma unroll
  for (int b = 0; b < 4; b++)
#pragma unroll
    for (int e = 0; e < 8; e++) {
      v[b][e] += __shfl_xor_sync(0xffffffffu, v[b][e], 8); v[b][e] += __shfl_xor_sync(0xffffffffu, v[b][e], 16);
      if (WS) { u[b][e] += __shfl_xor_sync(0xffffffffu, u[b][e], 8); u[b][e] += __shfl_xor_sync(0xffffffffu, u[b][e], 16); }
    }
  if (lane < 8) {
#pragma unroll
    for (int b = 0; b < 4; b++) {
      const uint32_t a = stg + warp * 2048 + b * 256 + lane * 32;
      sts128(a, __float_as_uint(v[b][0]), __float_as_uint(v[b][1]), __float_as_uint(v[b][2]), __float_as_uint(v[b][3]));
      sts128(a + 16, __float_as_uint(v[b][4]), __float_as_uint(v[b][5]), __float_as_uint(v[b][6]), __float_as_uint(v[b][7]));
      if (WS) {
        sts128(a + 1024, __float_as_uint(u[b][0]), __float_as_uint(u[b][1]), __float_as_uint(u[b][2]), __float_as_uint(u[b][3]));
        sts128(a + 1040, __float_as_uint(u[b][4]), __float_as_uint(u[b][5]), __float_as_uint(u[b][6]), __float_as_uint(u[b][7]));
      }
    }
  }
  bar_sync<1, 256>();
  float sv = 0.f, su = 0.f;
#pragma unroll
  for (int i = 0; i < 8; i++) {
    sv += lds32f(stg + i * 2048 + tid * 4);
    su += WS ? lds32f(stg + i * 2048 + 1024 + tid * 4) : lds32f(stg + i * 2048 + (tid ^ 128) * 4);
  }
  if (WS) {
    const __nv_bfloat16 uh = __float2bfloat16(su), ul = __float2bfloat16(su - __bfloat162float(uh));
    const __nv_bfloat16 vh = __float2bfloat16(sv), vl = __float2bfloat16(sv - __bfloat162float(vh)), z = __float2bfloat16(0.f);
    uint8_t* p = bext + idx * 4096 + (tid >> 6) * 1024 + (tid & 7) * 2;
#pragma unroll
    for (int r = 0; r < 8; r++)
      *reinterpret_cast<__nv_bfloat16*>(p + r * 128 + ((((tid & 63) >> 3) ^ r) << 4)) = r == 0 || r == 2 ? uh : r == 1 ? ul : r == 3 || r == 5 ? vh : r == 4 ? vl : z;
  } else if (tid < 128) {
    const int n = idx * 128 + tid, vec = n >> 10, col = n & 1023;
    const __nv_bfloat16 r = __float2bfloat16(sv + su);
    mod[2048 + n] = r;
    if (vec == 0 || vec == 3) gate[(vec ? D_ : 0) + (col & ~31) + ((col >> 1) & 3) * 8 + ((col >> 3) & 3) * 2 + (col & 1)] = r;
  }
}

__global__ void __launch_bounds__(384, 1)
kernel_H(const __grid_constant__ CUtensorMap tmo, const __grid_constant__ CUtensorMap tm1, const __grid_constant__ CUtensorMap tm3,
         const __grid_constant__ CUtensorMap tm2, const __grid_constant__ CUtensorMap tmm, const __grid_constant__ CUtensorMap tmx,
         const __grid_constant__ CUtensorMap tmy, const __nv_bfloat16* __restrict__ x, const __nv_bfloat16* __restrict__ cvec, __nv_bfloat16* out, const __grid_constant__ HList list) {
  extern __shared__ __align__(1024) uint8_t smem[];
  uint32_t rank, pair;
  asm("mov.u32 %0, %%cluster_ctarank;" : "=r"(rank)); asm("mov.u32 %0, %%cluster_nctarank;" : "=r"(pair));
  rank = __shfl_sync(0xffffffffu, rank, 0); pair = __shfl_sync(0xffffffffu, pair, 0) - 1;
  const uint32_t sb = H_SB + (rank << 24), bars = sb + H_BAR, pm = pair << 24;
  const int tid = threadIdx.x, lane = tid & 31;
  const int warp = __shfl_sync(0xffffffffu, tid >> 5, 0);
  if (tid == 0) {
    if ((smem_u32(smem) & 0xffffff) != H_SB) __trap();
    for (int i = 0; i < H_NST; i++) { mbar_init(bars + HB_FULL + i * 8, 1); mbar_init(bars + HB_EMPTY + i * 8, 4); }
    for (int i = 0; i < 2; i++) { mbar_init(bars + HB_IFULL + i * 8, 1); mbar_init(bars + HB_IEMPTY + i * 8, 1); mbar_init(bars + HB_VFULL + i * 8, 1);
      mbar_init(bars + HB_MFULL + i * 8, 1); mbar_init(bars + HB_MEMPTY + i * 8, 1); }
    for (int i = 0; i < 3; i++) { mbar_init(bars + HB_SRDY + i * 8, 4); mbar_init(bars + HB_SFREE + i * 8, 1); }
    mbar_init(bars + HB_STGF, 1);
    asm volatile("fence.mbarrier_init.release.cluster;" ::: "memory");
    fence_async_smem();
  }
  __syncthreads();
  cluster_sync();
  asm volatile("griddepcontrol.launch_dependents;");
  if (warp >= 8) {
    asm volatile("setmaxnreg.dec.sync.aligned.u32 56;");
    if (warp == 8) {
      uint32_t st = 0, ph = 1, nv = 0, q = 0;
      uint32_t* const head = &g_flags[list.head];
      const bool claimer = lane == 0 && rank == 0;
      if (claimer) q = atomicAdd(head, 1);
#pragma unroll 1
      for (uint32_t n = 0;; n++) {
        if (pair) {
          const uint32_t o = (n & 1) * 8, p = (n >> 1) & 1;
          if (rank == 0) {
            mbar_wait(bars + HB_MEMPTY + o, p ^ 1);
            if (lane == 0) st_async1((bars + HB_MAIL + o) ^ pm, q, (bars + HB_MFULL + o) ^ pm);
          } else {
            if (lane == 0) mbar_expect(bars + HB_MFULL + o, 4);
            mbar_wait(bars + HB_MFULL + o, p);
            q = lds32(bars + HB_MAIL + o);
            __syncwarp();
            if (lane == 0) mbar_arrive_cl((bars + HB_MEMPTY + o) ^ pm);
          }
        }
        q = __shfl_sync(0xffffffffu, q, 0);
        uint32_t it = q < list.n ? list.it[q] : 0;
        const bool shA = pair && !(it >> 28 & 1), shB = pair && (it >> 28 & 1);
        if (rank && it) it += shA ? 1 << 7 : (it >> 29) << 3;
        const int type = it & 7, mt = (it >> 3) & 15, idx = (it >> 7) & 63, sz = (it >> 13) & 3, kb0 = (it >> 15) & 63, nkb = (it >> 21) & 127;
        {
          int f = FL_GO; uint32_t target = 0;
          if (type == IT_OUT) { f = lane == 0 ? FL_ATT + 8 * mt : lane == 1 ? FL_XT + 8 * mt : FL_MOD; target = lane == 0 ? 64 : lane == 1 ? N_XT : N_MOD; }
          else if (type == IT_F1) { f = lane == 0 ? FL_OUT + 8 * mt : FL_WS; target = lane == 0 ? 1024 : N_WS; }
          else if (type == IT_F2) { f = FL_F1 + 8 * mt; target = 56; }
          else if (type == IT_STAT) { f = FL_OUT + 8 * mt; target = 1024; }
          else if (type == IT_WS) { f = FL_MOD; target = N_MOD; }
          else if (type != IT_END) target = 1;
          if (lane < 3) wait_flag(&g_flags[f], target);
          __syncwarp();
          asm volatile("fence.proxy.async.global;" ::: "memory");
        }
        mbar_wait(bars + HB_IEMPTY + (n & 1) * 8, ((n >> 1) & 1) ^ 1);
        if (elect_one()) {
          sts32(bars + HB_ITEM + (n & 1) * 4, it);
          mbar_arrive(bars + HB_IFULL + (n & 1) * 8);
        }
        if (type == IT_END) break;
        const bool gemm = type == IT_OUT || type == IT_F1 || type == IT_F2;
        const int nst = gemm ? nkb : type == IT_WS ? 16 : type == IT_MOD ? 8 : 0;
        const int bn = 256 >> sz;
        const uint8_t* ap = type == IT_OUT ? g_att + (size_t)mt * 64 * 16384 : g_act + (size_t)mt * 56 * 16384;
        const uint8_t* wp = g_w13s + (size_t)(idx >> sz) * 16 * 32768 + (sz ? (idx & 1) * 8192 : 0);
        const CUtensorMap* tb = type == IT_OUT ? &tmo : type == IT_F2 ? &tm2 : type == IT_WS ? &tm1 : &tmm;
        const CUtensorMap* tc = type == IT_WS ? &tm3 : tb;
        const int c0 = gemm ? idx * bn : type == IT_WS ? idx * 128 : 2048 + idx * 128, dcol = gemm ? 128 : 0, kmul = type == IT_MOD ? 128 : 64, drow = type == IT_MOD ? 64 : 0;
        const uint32_t bytes = gemm ? 16384 + bn * 128 : 32768;
        const uint64_t pa = type == IT_OUT ? POL_ATT : POL_ACT, pb = type == IT_OUT ? POL_WO : type == IT_F2 ? POL_W2 : POL_PRE;
        if (nst < 2 && claimer) q = atomicAdd(head, 1);
#pragma unroll 1
        for (int i = 0; i < nst; i++) {
          const int kb = kb0 + i;
          const uint32_t d = sb + st * H_STAGE, fb = bars + HB_FULL + st * 8;
          if (i == nst - 2 && claimer) q = atomicAdd(head, 1);
          mbar_wait(bars + HB_EMPTY + st * 8, ph);
          if (elect_one()) {
            mbar_expect(fb, bytes);
            if (type == IT_F1) {
              if (shA) tma2d_mc(d + rank * 8192, &tmy, kb * 64, mt * 128 + rank * 64, fb, L2_NORMAL); else tma2d(d, &tmx, kb * 64, mt * 128, fb);
              if (shB) bulk_mc(d + 16384 + rank * (16384 >> sz), wp + (size_t)kb * 32768 + rank * 16384, 16384 >> sz, fb, L2_NORMAL);
              else if (sz == 0) bulk_g2s(d + 16384, wp + (size_t)kb * 32768, 32768, fb);
              else { bulk_g2s(d + 16384, wp + (size_t)kb * 32768, 8192, fb); bulk_g2s(d + 24576, wp + (size_t)kb * 32768 + 16384, 8192, fb); }
            } else {
              if (shA) bulk_mc(d + rank * 8192, ap + (size_t)kb * 16384 + rank * 8192, 8192, fb, pa);
              else if (gemm) bulk_g2s_p(d, ap + (size_t)kb * 16384, 16384, fb, pa);
              if (shB) {
                if (sz == 0) {
                  tma2d_mc(d + 16384 + rank * 16384, tb, c0 + rank * 128, kb * 64, fb, pb);
                  tma2d_mc(d + 24576 + rank * 16384, tb, c0 + rank * 128 + 64, kb * 64, fb, pb);
                } else tma2d_mc(d + 16384 + rank * 8192, tb, c0 + rank * 64, kb * 64, fb, pb);
              } else {
                tma2d_p(d + 16384, tb, c0, kb * kmul, fb, pb);
                tma2d_p(d + 24576, tb, c0 + 64, kb * kmul, fb, pb);
                if (sz == 0) { tma2d_p(d + 32768, tc, c0 + dcol, kb * kmul + drow, fb, pb); tma2d_p(d + 40960, tc, c0 + dcol + 64, kb * kmul + drow, fb, pb); }
              }
            }
          }
          if (++st == H_NST) { st = 0; ph ^= 1; }
        }
        if (gemm) {
          if (type == IT_F1) {
            if (lane == 0) wait_flag(&g_flags[FL_STAT + 8 * mt], N_STAT);
            __syncwarp();
            asm volatile("fence.proxy.async.global;" ::: "memory");
          }
          if (elect_one()) {
            const uint32_t v = sb + H_VEC, fb = bars + HB_VFULL + (nv & 1) * 8;
            if (type == IT_F1) {
              mbar_expect(fb, (4096 >> sz) + 2560);
              if (sz == 0) bulk_g2s(v, g_bext + idx * 4096, 4096, fb);
              else { const uint8_t* p = g_bext + (idx >> 1) * 4096 + (idx & 1) * 1024; bulk_g2s(v, p, 1024, fb); bulk_g2s(v + 1024, p + 2048, 1024, fb); }
              bulk_g2s(v + 4096, g_ext + mt * 2560, 2560, fb);
            } else {
              mbar_expect(fb, bn * 2);
              bulk_g2s(sb + H_GATE + (nv & 1) * 512, g_gate + (type == IT_F2 ? D_ : 0) + c0, bn * 2, fb);
            }
          }
          nv++;
        }
      }
    } else if (warp == 9) {
      uint32_t g = 0;
#pragma unroll 1
      for (uint32_t n = 0;; n++) {
        mbar_wait(bars + HB_IFULL + (n & 1) * 8, (n >> 1) & 1);
        const uint32_t it = lds32(bars + HB_ITEM + (n & 1) * 4);
        const int type = it & 7, mt = (it >> 3) & 15, idx = (it >> 7) & 63, sz = (it >> 13) & 3, nkb = (it >> 21) & 127;
        if (type == IT_END) break;
        const bool gated = type == IT_OUT || type == IT_F2, gemm = gated || type == IT_F1;
        if (!gemm) { if (n & 1) bar_sync<3, 288>(); else bar_sync<2, 288>(); }
        if (lane == 0) {
          if (gemm) {
            const int nu = (gated ? 4 : 2) >> sz;
            uint32_t pb = 0;
#pragma unroll 1
            for (int u = 0; u < 2 * nu; u++, g++) {
              const uint32_t r = (g * 43691u) >> 17, b = g - 3 * r, src = sb + H_STG + b * 8192;
              const int w = u >= nu, uu = u - w * nu;
              mbar_wait(bars + HB_SRDY + b * 8, r & 1);
              if (u == 2 * nu - 1) mbar_arrive(bars + HB_IEMPTY + (n & 1) * 8);
              fence_async_smem();
              if (gated) tma2d_add(&tmy, idx * (256 >> sz) + uu * 64, mt * 128 + w * 64, src);
              else bulk_s2g(g_act + (size_t)(mt * 56 + idx * nu + uu) * 16384 + w * 8192, src, 8192);
              bulk_commit();
              if (u > 0) { bulk_wait_read<1>(); mbar_arrive(bars + HB_SFREE + pb * 8); }
              pb = b;
            }
            bulk_wait_read<0>();
            mbar_arrive(bars + HB_SFREE + pb * 8);
            mbar_arrive(bars + HB_STGF);
            bulk_wait_all(); fence_async_all();
          } else {
            mbar_arrive(bars + HB_STGF);
            mbar_arrive(bars + HB_IEMPTY + (n & 1) * 8);
          }
          if (type != IT_F2) {
            const uint32_t inc = type == IT_OUT ? (4 >> sz) * nkb : type == IT_F1 ? 2 >> sz : 1;
            fence_gpu();
            red_add_u32(&g_flags[type == IT_MOD ? FL_MOD : type == IT_WS ? FL_WS :
                                 (type == IT_XT ? FL_XT : type == IT_OUT ? FL_OUT : type == IT_STAT ? FL_STAT : FL_F1) + 8 * mt], inc);
          }
        }
        __syncwarp();
      }
      if (!pair) asm volatile("griddepcontrol.wait;" ::: "memory");
      uint32_t k = 0;
      if (lane == 0) { fence_gpu(); k = atomicAdd(&g_flags[FL_EXIT], 1); }
      k = __shfl_sync(0xffffffffu, k, 0);
      if (k == NH1 + NH2 - 1) {
        fence_gpu();
        for (int i = lane; i < 1024; i += 32) g_flags[i] = 0;
      }
    }
  } else {
    asm volatile("setmaxnreg.inc.sync.aligned.u32 224;");
    const int wg = warp >> 2;
    const bool leader = (tid & 127) == 0;
    uint32_t st = 0, ph = 0, nv = 0, g = 0;
#pragma unroll 1
    for (uint32_t n = 0;; n++) {
      mbar_wait(bars + HB_IFULL + (n & 1) * 8, (n >> 1) & 1);
      const uint32_t it = __shfl_sync(0xffffffffu, lds32(bars + HB_ITEM + (n & 1) * 4), 0);
      const int type = it & 7, mt = (it >> 3) & 15, idx = (it >> 7) & 63, sz = (it >> 13) & 3, nkb = (it >> 21) & 127;
      if (type == IT_END) break;
      constexpr uint32_t clk_q = 0;
      if (type == IT_OUT || type == IT_F1 || type == IT_F2) {
        const uint32_t va = sb + H_GATE + (nv & 1) * 512, vb = bars + HB_VFULL + (nv & 1) * 8, vp = (nv >> 1) & 1;
        const uint32_t nu = (type == IT_F1 ? 2 : 4) >> sz, g0 = g + wg * nu;
        nv++; g += 2 * nu;
        if (sz == 0) {
          float acc[128];
          if (type == IT_OUT) h_mainloop<256, 1>(acc, sb, pm, nkb, st, ph, wg, leader, clk_q);
          else h_mainloop<256, 0>(acc, sb, pm, nkb, st, ph, wg, leader, clk_q);
          if (type == IT_F1) h_swiglu<256>(acc, vb, vp, sb, pm, st, ph, g0, wg, leader, warp, lane, clk_q);
          else h_gated<256>(acc, va, vb, vp, sb, pm, st, ph, g0, wg, leader, warp, lane, clk_q);
        } else {
          float acc[64];
          if (type == IT_OUT) h_mainloop<128, 1>(acc, sb, pm, nkb, st, ph, wg, leader, clk_q);
          else h_mainloop<128, 0>(acc, sb, pm, nkb, st, ph, wg, leader, clk_q);
          if (type == IT_F1) h_swiglu<128>(acc, vb, vp, sb, pm, st, ph, g0, wg, leader, warp, lane, clk_q);
          else h_gated<128>(acc, va, vb, vp, sb, pm, st, ph, g0, wg, leader, warp, lane, clk_q);
        }
        HT(3);
        continue;
      } else if (type == IT_XT) {
        const uint4* xp = reinterpret_cast<const uint4*>(x + (size_t)(mt * 128 + idx * 64) * D_) + tid;
        uint4* op = reinterpret_cast<uint4*>(out + (size_t)(mt * 128 + idx * 64) * D_) + tid;
#pragma unroll 1
        for (int b = 0; b < 2; b++) {
          uint4 v[16];
#pragma unroll
          for (int i = 0; i < 16; i++) v[i] = __ldcs(xp + (b * 16 + i) * 256);
#pragma unroll
          for (int i = 0; i < 16; i++) op[(b * 16 + i) * 256] = v[i];
        }
      } else if (type == IT_STAT) {
        const int row0 = mt * 128 + idx * 32 + warp * 4;
        const uint4* xp = reinterpret_cast<const uint4*>(out + (size_t)row0 * D_) + lane;
        uint4 v[16];
#pragma unroll
        for (int i = 0; i < 16; i++) v[i] = __ldcg(xp + (i >> 2) * 128 + (i & 3) * 32);
        float s[4], m[4];
#pragma unroll
        for (int r = 0; r < 4; r++) {
          s[r] = 0.f;
#pragma unroll
          for (int i = 0; i < 4; i++) {
            const uint4 w = v[4 * r + i];
            s[r] += ((bf_lo(w.x) + bf_hi(w.x)) + (bf_lo(w.y) + bf_hi(w.y))) + ((bf_lo(w.z) + bf_hi(w.z)) + (bf_lo(w.w) + bf_hi(w.w)));
          }
        }
#pragma unroll
        for (int o = 1; o < 32; o <<= 1)
#pragma unroll
          for (int r = 0; r < 4; r++) s[r] += __shfl_xor_sync(0xffffffffu, s[r], o);
#pragma unroll
        for (int r = 0; r < 4; r++) {
          m[r] = s[r] * (1.f / D_);
          float a = 0.f, b = 0.f;
#pragma unroll
          for (int i = 0; i < 4; i++) {
            const uint4 w = v[4 * r + i];
            const uint32_t ww[4] = {w.x, w.y, w.z, w.w};
#pragma unroll
            for (int e = 0; e < 4; e++) { const float p = bf_lo(ww[e]) - m[r], t = bf_hi(ww[e]) - m[r]; a = fmaf(p, p, a); b = fmaf(t, t, b); }
          }
          s[r] = a + b;
        }
#pragma unroll
        for (int o = 1; o < 32; o <<= 1)
#pragma unroll
          for (int r = 0; r < 4; r++) s[r] += __shfl_xor_sync(0xffffffffu, s[r], o);
        if (lane < 4) {
          const float sr = lane == 0 ? s[0] : lane == 1 ? s[1] : lane == 2 ? s[2] : s[3], mr = lane == 0 ? m[0] : lane == 1 ? m[1] : lane == 2 ? m[2] : m[3];
          const float var = sr * (1.f / D_) + 1e-5f, rs = rsqrtf(var);
          const float a = -0.5f * mr, b = 0.5f * var * rs;
          const float ah = __bfloat162float(__float2bfloat16(a)), bh = __bfloat162float(__float2bfloat16(b));
          const int r = (row0 & 127) + lane;
          *reinterpret_cast<uint4*>(g_ext + mt * 2560 + r * 16) = make_uint4(pack2(ah, ah), pack2(a - ah, bh), pack2(bh, b - bh), 0u);
          *reinterpret_cast<float*>(g_ext + mt * 2560 + 2048 + r * 4) = rs;
        }
      } else {
        mbar_wait(bars + HB_STGF, (n & 1) ^ 1);
        if (type == IT_WS) h_vecmat<true>(sb, idx, st, ph, tid, cvec, g_w13s, g_bext, g_mod, g_gate);
        else h_vecmat<false>(sb, idx, st, ph, tid, cvec, g_w13s, g_bext, g_mod, g_gate);
      }
      HT(3);
      if (n & 1) bar_arrive<3, 288>(); else bar_arrive<2, 288>();
    }
  }
  cluster_sync();
}

const uint32_t h_items1[] = {
  0x1, 0x81, 0x101, 0x181, 0x201, 0x281, 0x301, 0x381, 0x401, 0x481, 0x501, 0x581, 0x601, 0x681,
  0x701, 0x781, 0x801, 0x881, 0x901, 0x981, 0xa01, 0xa81, 0xb01, 0xb81, 0xc01, 0xc81, 0xd01, 0xd81,
  0xe01, 0xe81, 0xf01, 0xf81, 0x2, 0x82, 0xa, 0x8a, 0x12, 0x92, 0x1a, 0x9a, 0x22, 0xa2,
  0x2a, 0xaa, 0x4, 0x84, 0x104, 0x184, 0x32, 0xb2, 0x3a, 0xba, 0x42, 0xc2, 0x4a, 0xca,
  0x52, 0xd2, 0x5a, 0xda, 0x62, 0xe2, 0x6a, 0xea, 0x72, 0xf2, 0x7a, 0xfa, 0x204, 0x284,
  0x304, 0x384, 0x404, 0x484, 0x504, 0x584, 0x604, 0x684, 0x704, 0x784, 0x804, 0x884, 0x904, 0x984,
  0xa04, 0xa84, 0xb04, 0xb84, 0xc04, 0xc84, 0xd04, 0xd84, 0x1000003, 0x1000083, 0x1000103, 0x1000183, 0x1040003, 0x1040083,
  0x1040103, 0x1040183, 0x1080003, 0x1080083, 0x1080103, 0x1080183, 0x10c0003, 0x10c0083, 0x10c0103, 0x10c0183, 0x1100003, 0x1100083, 0x1100103, 0x1100183,
  0x1140003, 0x1140083, 0x1140103, 0x1140183, 0x1180003, 0x1180083, 0x1180103, 0x1180183, 0x11c0003, 0x11c0083, 0x11c0103, 0x11c0183, 0x200000b, 0x200008b,
  0x200010b, 0x200018b, 0x208000b, 0x208008b, 0x208010b, 0x208018b, 0x210000b, 0x210008b, 0x210010b, 0x210018b, 0x218000b, 0x218008b, 0x218010b, 0x218018b,
  0x7, 0x87, 0x107, 0x187, 0x2000005, 0x2000085, 0x2000105, 0x2000185, 0x2000205, 0x2000285, 0x2000305, 0x2000385, 0x2000405, 0x2000485,
  0x2000505, 0x2000585, 0x2000605, 0x2000685, 0x2000705, 0x2000785, 0x2000805, 0x2000885, 0x2000905, 0x2000985, 0x2000a05, 0x2000a85, 0x2000b05, 0x2000b85,
  0x2000c05, 0x2000c85, 0x2000d05, 0x2000d85, 0x4000013, 0x4000093, 0x4000113, 0x4000193, 0x4100013, 0x4100093, 0x4100113, 0x4100193, 0xf, 0x8f,
  0x10f, 0x18f, 0x200000d, 0x200008d, 0x200010d, 0x200018d, 0x200020d, 0x200028d, 0x200030d, 0x200038d, 0x200040d, 0x200048d, 0x200050d, 0x200058d,
  0x200060d, 0x200068d, 0x200070d, 0x200078d, 0x200080d, 0x200088d, 0x200090d, 0x200098d, 0x2000a0d, 0x2000a8d, 0x2000b0d, 0x2000b8d, 0x2000c0d, 0x2000c8d,
  0x2000d0d, 0x2000d8d, 0x3800006, 0x3800086, 0x3800106, 0x3800186, 0x38e0006, 0x38e0086, 0x38e0106, 0x38e0186, 0x400001b, 0x400009b, 0x400011b, 0x400019b,
  0x410001b, 0x410009b, 0x410011b, 0x410019b, 0x380000e, 0x380008e, 0x380010e, 0x380018e, 0x38e000e, 0x38e008e, 0x38e010e, 0x38e018e, 0x17, 0x97,
  0x117, 0x197, 0x2000015, 0x2000095, 0x2000115, 0x2000195, 0x2000215, 0x2000295, 0x2000315, 0x2000395, 0x2000415, 0x2000495, 0x2000515, 0x2000595,
  0x4000023, 0x40000a3, 0x4000123, 0x40001a3, 0x4100023, 0x41000a3, 0x4100123, 0x41001a3, 0x2000615, 0x2000695, 0x2000715, 0x2000795, 0x2000815, 0x2000895,
  0x2000915, 0x2000995, 0x2000a15, 0x2000a95, 0x2000b15, 0x2000b95, 0x2000c15, 0x2000c95, 0x2000d15, 0x2000d95, 0x1f, 0x9f, 0x11f, 0x19f,
  0x200001d, 0x200009d, 0x200011d, 0x200019d, 0x200021d, 0x200029d, 0x200031d, 0x200039d, 0x200041d, 0x200049d, 0x200051d, 0x200059d, 0x400002b, 0x40000ab,
  0x400012b, 0x40001ab, 0x410002b, 0x41000ab, 0x410012b, 0x41001ab, 0x200061d, 0x200069d, 0x200071d, 0x200079d, 0x200081d, 0x200089d, 0x200091d, 0x200099d,
  0x2000a1d, 0x2000a9d, 0x2000b1d, 0x2000b9d, 0x2000c1d, 0x2000c9d, 0x2000d1d, 0x2000d9d, 0x27, 0xa7, 0x127, 0x1a7, 0x2000025, 0x20000a5,
  0x2000125, 0x20001a5, 0x2000225, 0x20002a5, 0x2000325, 0x20003a5, 0x4000033, 0x40000b3, 0x4000133, 0x40001b3, 0x4100033, 0x41000b3, 0x4100133, 0x41001b3,
  0x2000425, 0x20004a5, 0x2000525, 0x20005a5, 0x2000625, 0x20006a5, 0x2000725, 0x20007a5, 0x2000825, 0x20008a5, 0x2000925, 0x20009a5, 0x2000a25, 0x2000aa5,
  0x2000b25, 0x2000ba5, 0x2000c25, 0x2000ca5, 0x2000d25, 0x2000da5, 0x2f, 0xaf, 0x12f, 0x1af, 0x200002d, 0x20000ad, 0x200012d, 0x20001ad,
  0x200022d, 0x20002ad, 0x200032d, 0x20003ad, 0x400003b, 0x40000bb, 0x400013b, 0x40001bb, 0x410003b, 0x41000bb, 0x410013b, 0x41001bb, 0x200042d, 0x20004ad,
  0x200052d, 0x20005ad, 0x200062d, 0x20006ad, 0x200072d, 0x20007ad, 0x200082d, 0x20008ad, 0x200092d, 0x20009ad, 0x2000a2d, 0x2000aad, 0x2000b2d, 0x2000bad,
  0x2000c2d, 0x2000cad, 0x2000d2d, 0x2000dad, 0x37, 0xb7, 0x137, 0x1b7, 0x2000035, 0x20000b5, 0x2000135, 0x20001b5, 0x2000235, 0x20002b5,
  0x2000335, 0x20003b5, 0x2000435, 0x20004b5, 0x2000535, 0x20005b5, 0x4000043, 0x40000c3, 0x4000143, 0x40001c3, 0x4100043, 0x41000c3, 0x4100143, 0x41001c3,
  0x2000635, 0x20006b5, 0x2000735, 0x20007b5, 0x2000835, 0x20008b5, 0x2000935, 0x20009b5, 0x2000a35, 0x2000ab5, 0x2000b35, 0x2000bb5, 0x2000c35, 0x2000cb5,
  0x2000d35, 0x2000db5, 0x3f, 0xbf, 0x13f, 0x1bf, 0x200003d, 0x20000bd, 0x200013d, 0x20001bd, 0x200023d, 0x20002bd, 0x200033d, 0x20003bd,
  0x400004b, 0x40000cb, 0x400014b, 0x40001cb, 0x410004b, 0x41000cb, 0x410014b, 0x41001cb, 0x200043d, 0x20004bd, 0x200053d, 0x20005bd, 0x200063d, 0x20006bd,
  0x200073d, 0x20007bd, 0x200083d, 0x20008bd, 0x200093d, 0x20009bd, 0x2000a3d, 0x2000abd, 0x2000b3d, 0x2000bbd, 0x2000c3d, 0x2000cbd, 0x2000d3d, 0x2000dbd,
  0x47, 0xc7, 0x147, 0x1c7, 0x2000045, 0x20000c5, 0x2000145, 0x20001c5, 0x2000245, 0x20002c5, 0x2000345, 0x20003c5, 0x4000053, 0x40000d3,
  0x4000153, 0x40001d3, 0x4100053, 0x41000d3, 0x4100153, 0x41001d3, 0x2000445, 0x20004c5, 0x2000545, 0x20005c5, 0x2000645, 0x20006c5, 0x2000745, 0x20007c5,
  0x2000845, 0x20008c5, 0x2000945, 0x20009c5, 0x2000a45, 0x2000ac5, 0x2000b45, 0x2000bc5, 0x2000c45, 0x2000cc5, 0x2000d45, 0x2000dc5, 0x4f, 0xcf,
  0x14f, 0x1cf, 0x200004d, 0x20000cd, 0x200014d, 0x20001cd, 0x200024d, 0x20002cd, 0x200034d, 0x20003cd, 0x200044d, 0x20004cd, 0x200054d, 0x20005cd,
  0x400005b, 0x40000db, 0x400015b, 0x40001db, 0x410005b, 0x41000db, 0x410015b, 0x41001db, 0x200064d, 0x20006cd, 0x200074d, 0x20007cd, 0x200084d, 0x20008cd,
  0x200094d, 0x20009cd, 0x2000a4d, 0x2000acd, 0x2000b4d, 0x2000bcd, 0x2000c4d, 0x2000ccd, 0x2000d4d, 0x2000dcd, 0x57, 0xd7, 0x157, 0x1d7,
  0x2000055, 0x20000d5, 0x2000155, 0x20001d5, 0x2000255, 0x20002d5, 0x2000355, 0x20003d5, 0x4000063, 0x40000e3, 0x4000163, 0x40001e3, 0x4100063, 0x41000e3,
  0x4100163, 0x41001e3, 0x2000455, 0x20004d5, 0x2000555, 0x20005d5, 0x2000655, 0x20006d5, 0x2000755, 0x20007d5, 0x2000855, 0x20008d5, 0x2000955, 0x20009d5,
  0x2000a55, 0x2000ad5, 0x2000b55, 0x2000bd5, 0x2000c55, 0x2000cd5, 0x2000d55, 0x2000dd5, 0x5f, 0xdf, 0x15f, 0x1df, 0x200005d, 0x20000dd,
  0x200015d, 0x20001dd, 0x200025d, 0x20002dd, 0x200035d, 0x20003dd, 0x200006b, 0x20000eb, 0x200016b, 0x20001eb, 0x208006b, 0x20800eb, 0x208016b, 0x20801eb,
  0x210006b, 0x21000eb, 0x210016b, 0x21001eb, 0x218006b, 0x21800eb, 0x218016b, 0x21801eb, 0x200045d, 0x20004dd, 0x200055d, 0x20005dd, 0x200065d, 0x20006dd,
  0x200075d, 0x20007dd, 0x200085d, 0x20008dd, 0x200095d, 0x20009dd, 0x2000a5d, 0x2000add, 0x2000b5d, 0x2000bdd, 0x2000c5d, 0x2000cdd, 0x2000d5d, 0x2000ddd,
  0x67, 0xe7, 0x167, 0x1e7, 0x2000065, 0x20000e5, 0x2000165, 0x20001e5, 0x2000265, 0x20002e5, 0x2000365, 0x20003e5, 0x2000465, 0x20004e5,
  0x2000565, 0x20005e5, 0x2000073, 0x20000f3, 0x2000173, 0x20001f3, 0x2080073, 0x20800f3, 0x2080173, 0x20801f3, 0x2100073, 0x21000f3, 0x2100173, 0x21001f3,
  0x2180073, 0x21800f3, 0x2180173, 0x21801f3, 0x6f, 0xef, 0x16f, 0x1ef, 0x2000665, 0x20006e5, 0x2000765, 0x20007e5, 0x2000865, 0x20008e5,
  0x2000965, 0x20009e5, 0x2000a65, 0x2000ae5, 0x2000b65, 0x2000be5, 0x2000c65, 0x2000ce5, 0x2000d65, 0x2000de5, 0x200006d, 0x20000ed, 0x200016d, 0x20001ed,
  0x200026d, 0x20002ed, 0x200036d, 0x20003ed, 0x200046d, 0x20004ed, 0x200056d, 0x20005ed, 0x200066d, 0x20006ed, 0x200076d, 0x20007ed, 0x200086d, 0x20008ed,
  0x200096d, 0x20009ed, 0x2000a6d, 0x2000aed, 0x2000b6d, 0x2000bed, 0x77, 0xf7, 0x177, 0x1f7, 0x2000c6d, 0x2000ced, 0x2000d6d, 0x2000ded,
  0x2000075, 0x20000f5, 0x2000175, 0x20001f5, 0x2000275, 0x20002f5, 0x2000375, 0x20003f5, 0x2000475, 0x20004f5, 0x2000575, 0x20005f5, 0x2000675, 0x20006f5,
  0x2000775, 0x20007f5, 0x2000875, 0x20008f5, 0x2000975, 0x20009f5, 0x2000a75, 0x2000af5, 0x2000b75, 0x2000bf5, 0x2000c75, 0x2000cf5, 0x2000d75, 0x2000df5,
  0x1c0006e, 0x1c000ee, 0x1c0016e, 0x1c001ee, 0x1c7006e, 0x1c700ee, 0x1c7016e, 0x1c701ee, 0x1ce006e, 0x1ce00ee, 0x1ce016e, 0x1ce01ee, 0x1d5006e, 0x1d500ee,
  0x1d5016e, 0x1d501ee, 0x1c00076, 0x1c000f6, 0x1c00176, 0x1c001f6, 0x1c70076, 0x1c700f6, 0x1c70176, 0x1c701f6, 0x1ce0076, 0x1ce00f6, 0x1ce0176, 0x1ce01f6,
  0x1d50076, 0x1d500f6, 0x1d50176, 0x1d501f6,
};
const uint32_t h_items2[] = {
  0x100207b, 0x100217b, 0x100227b, 0x100237b, 0x104207b, 0x104217b, 0x104227b, 0x104237b, 0x108207b, 0x108217b, 0x108227b, 0x108237b, 0x10c207b, 0x10c217b,
  0x10c227b, 0x10c237b, 0x110207b, 0x110217b, 0x110227b, 0x110237b, 0x114207b, 0x114217b, 0x114227b, 0x114237b, 0x118207b, 0x118217b, 0x118227b, 0x118237b,
  0x11c207b, 0x11c217b, 0x11c227b, 0x11c237b, 0x31c00016, 0x31c00096, 0x31c00116, 0x31c00196, 0x31c70016, 0x31c70096, 0x31c70116, 0x31c70196, 0x31ce0016, 0x31ce0096,
  0x31ce0116, 0x31ce0196, 0x31d50016, 0x31d50096, 0x31d50116, 0x7f, 0x17f, 0x31d50196, 0x31c00026, 0x31c000a6, 0x31c00126, 0x31c001a6, 0x31c70026, 0x31c700a6,
  0x31c70126, 0x31c701a6, 0x31ce0026, 0x31ce00a6, 0x31ce0126, 0x31ce01a6, 0x31d50026, 0x31d500a6, 0x31d50126, 0x31d501a6, 0x31c00036, 0x31c000b6, 0x31c00136, 0x31c001b6,
  0x31c70036, 0x31c700b6, 0x31c70136, 0x31c701b6, 0x31ce0036, 0x31ce00b6, 0x31ce0136, 0x31ce01b6, 0x31d50036, 0x200207d, 0x200217d, 0x200227d, 0x200237d, 0x200247d,
  0x200257d, 0x200267d, 0x200277d, 0x200287d, 0x200297d, 0x2002a7d, 0x2002b7d, 0x2002c7d, 0x2002d7d, 0x2002e7d, 0x2002f7d, 0x200307d, 0x200317d, 0x200327d,
  0x200337d, 0x200347d, 0x200357d, 0x200367d, 0x200377d, 0x200387d, 0x200397d, 0x2003a7d, 0x2003b7d, 0x31d500b6, 0x31d50136, 0x31d501b6, 0x31c00046, 0x31c000c6,
  0x31c00146, 0x31c001c6, 0x31c70046, 0x31c700c6, 0x31c70146, 0x31c701c6, 0x31ce0046, 0x31ce00c6, 0x31ce0146, 0x31ce01c6, 0x31d50046, 0x31d500c6, 0x31d50146, 0x31d501c6,
  0x31c00056, 0x31c000d6, 0x31c00156, 0x31c001d6, 0x31c70056, 0x31c700d6, 0x31c70156, 0x31c701d6, 0x31ce0056, 0x31ce00d6, 0x31ce0156, 0x31ce01d6, 0x31d50056, 0x31d500d6,
  0x31d50156, 0x31d501d6, 0x1c00066, 0x1c00166, 0x1c70066, 0x1c70166, 0x1ce0066, 0x1ce0166, 0x1d50066, 0x1d50166, 0xe0207e, 0xe0217e, 0xe0227e, 0xe0237e,
  0xe3a07e, 0xe3a17e, 0xe3a27e, 0xe3a37e, 0xe7207e, 0xe7217e, 0xe7227e, 0xe7237e, 0xeaa07e, 0xeaa17e, 0xeaa27e, 0xeaa37e, 0xee207e, 0xee217e,
  0xee227e, 0xee237e, 0xf1a07e, 0xf1a17e, 0xf1a27e, 0xf1a37e, 0xf5207e, 0xf5217e, 0xf5227e, 0xf5237e, 0xf8a07e, 0xf8a17e, 0xf8a27e, 0xf8a37e,
};

void build_lists(HList& a, HList& b) {
  a.n = b.n = 0;
  for (uint32_t v : h_items1) a.it[a.n++] = v;
  for (uint32_t v : h_items2) b.it[b.n++] = v;
  a.head = FL_HEAD; a.tbase = 0;
  b.head = FL_HEAD2; b.tbase = a.n;
}

typedef CUresult (*EncodeFn)(CUtensorMap*, CUtensorMapDataType, cuuint32_t, void*, const cuuint64_t*, const cuuint64_t*,
                             const cuuint32_t*, const cuuint32_t*, CUtensorMapInterleave, CUtensorMapSwizzle,
                             CUtensorMapL2promotion, CUtensorMapFloatOOBfill);

void make_map(EncodeFn fn, CUtensorMap* m, const void* p, uint64_t cols, uint64_t rows, uint32_t bc, uint32_t br, CUtensorMapSwizzle sw) {
  cuuint64_t dims[2] = {cols, rows};
  cuuint64_t strides[1] = {cols * 2};
  cuuint32_t box[2] = {bc, br};
  cuuint32_t es[2] = {1, 1};
  fn(m, CU_TENSOR_MAP_DATA_TYPE_BFLOAT16, 2, const_cast<void*>(p), dims, strides, box, es, CU_TENSOR_MAP_INTERLEAVE_NONE, sw,
     CU_TENSOR_MAP_L2_PROMOTION_L2_128B, CU_TENSOR_MAP_FLOAT_OOB_FILL_NONE);
}

}

extern "C" void kernel_launch(void* const* d_in, const int* in_sizes, int n_in, void* d_out, int out_size) {
  const __nv_bfloat16* x = (const __nv_bfloat16*)d_in[0];
  const __nv_bfloat16* mem0 = (const __nv_bfloat16*)d_in[1];
  const __nv_bfloat16* cvec = (const __nv_bfloat16*)d_in[11];
  static EncodeFn enc = nullptr;
  if (!enc) {
    cudaDriverEntryPointQueryResult qr;
    void* fp = nullptr;
    cudaGetDriverEntryPoint("cuTensorMapEncodeTiled", &fp, cudaEnableDefault, &qr);
    enc = (EncodeFn)fp;
    cudaFuncSetAttribute(kernel_R, cudaFuncAttributeMaxDynamicSharedMemorySize, R_SMEM);
    cudaFuncSetAttribute(kernel_H, cudaFuncAttributeMaxDynamicSharedMemorySize, H_SMEM);
  }
  CUtensorMap tmq, tmk, tmv, tmo, tmm;
  make_map(enc, &tmm, d_in[12], 6144, 1024, 64, 64, CU_TENSOR_MAP_SWIZZLE_NONE);
  make_map(enc, &tmq, d_in[2], 4096, 1024, 64, 64, CU_TENSOR_MAP_SWIZZLE_128B);
  make_map(enc, &tmk, d_in[3], 4096, 1024, 64, 64, CU_TENSOR_MAP_SWIZZLE_128B);
  make_map(enc, &tmv, d_in[4], 4096, 1024, 64, 64, CU_TENSOR_MAP_SWIZZLE_128B);
  make_map(enc, &tmo, d_in[5], 1024, 4096, 16, 128, CU_TENSOR_MAP_SWIZZLE_32B);
  RDesc dsc;
  for (int k = 0; k < 32; k++) {
    dsc.tok[k] = mkdesc(0x400 + (k < 16 ? R_GA : R_GB) + ((k & 15) >> 2) * 4096 + (k & 3) * 256, 128, 1024, 0);
    dsc.tail_a[k] = mkdesc(0x400 + R_TAIL + k * 2048, 1024, 1024, 1);
    if (k < 16) dsc.tail_b[k] = mkdesc(0x400 + R_GA + k * 256, 128, 4096, 0);
  }
  kernel_R<<<96, 256, R_SMEM, cudaStreamPerThread>>>(tmq, tmk, tmv, tmo, tmm, x, mem0, cvec, dsc);

  CUtensorMap ho, h1, h3, h2, hm, hx, hy;
  make_map(enc, &ho, d_in[5], 1024, 4096, 64, 64, CU_TENSOR_MAP_SWIZZLE_128B);
  make_map(enc, &h1, d_in[8], F_, 1024, 64, 64, CU_TENSOR_MAP_SWIZZLE_128B);
  make_map(enc, &h3, d_in[9], F_, 1024, 64, 64, CU_TENSOR_MAP_SWIZZLE_128B);
  make_map(enc, &h2, d_in[10], 1024, F_, 64, 64, CU_TENSOR_MAP_SWIZZLE_128B);
  make_map(enc, &hm, d_in[12], 6144, 1024, 64, 64, CU_TENSOR_MAP_SWIZZLE_128B);
  make_map(enc, &hx, d_out, 1024, S_, 64, 128, CU_TENSOR_MAP_SWIZZLE_128B);
  make_map(enc, &hy, d_out, 1024, S_, 64, 64, CU_TENSOR_MAP_SWIZZLE_128B);
  HList list1, list2;
  build_lists(list1, list2);
  cudaLaunchConfig_t cfg = {};
  cfg.gridDim = dim3(NH1); cfg.blockDim = dim3(384); cfg.dynamicSmemBytes = H_SMEM; cfg.stream = cudaStreamPerThread;
  cudaLaunchAttribute at[2];
  at[0].id = cudaLaunchAttributeProgrammaticStreamSerialization;
  at[0].val.programmaticStreamSerializationAllowed = 1;
  at[1].id = cudaLaunchAttributeClusterDimension;
  at[1].val.clusterDim.x = 2; at[1].val.clusterDim.y = 1; at[1].val.clusterDim.z = 1;
  cfg.attrs = at; cfg.numAttrs = 1;
  cudaLaunchKernelEx(&cfg, kernel_H, ho, h1, h3, h2, hm, hx, hy, x, cvec, (__nv_bfloat16*)d_out, list1);
  cfg.numAttrs = 2; cfg.gridDim = dim3(NH2);
  cudaLaunchKernelEx(&cfg, kernel_H, ho, h1, h3, h2, hm, hx, hy, x, cvec, (__nv_bfloat16*)d_out, list2);
}
```

```cpp
#include <cuda_runtime.h>
#include <cuda_bf16.h>
#include <cuda.h>
#include <stdint.h>
#include <type_traits>

namespace {

constexpr int S_ = 2048, D_ = 1024, NSEG = 64, F_ = 3584;

__device__ __align__(1024) uint8_t g_h[S_ * D_ * 2];
__device__ __align__(1024) uint8_t g_att[S_ * 4096 * 2];
__device__ __align__(1024) uint8_t g_act[S_ * F_ * 2];
__device__ __align__(1024) uint8_t g_w13s[28 * 16 * 32768];
__device__ __align__(1024) uint8_t g_ext[16 * 2560];
__device__ __align__(1024) uint8_t g_bext[28 * 4096];
__device__ __align__(1024) __nv_bfloat16 g_gate[2 * D_];
__device__ __align__(1024) float g_slot[4 * 3 * 8 * 4 * 32 * 4];
__device__ __align__(128) __nv_bfloat16 g_mod[6 * D_];
__device__ __align__(128) float g_modp[3 * 2 * D_];
__device__ __align__(128) uint32_t g_flags[1024];
constexpr int FL_S1 = 0, FL_S2 = 32, FL_MOD = 64, FL_HEAD = 96, FL_EXIT = 128, FL_WS = 160, FL_GO = 192, FL_HEAD2 = 224, FL_ATT = 256, FL_XT = 384, FL_OUT = 512, FL_F1 = 640, FL_STAT = 768;

__device__ __forceinline__ uint32_t smem_u32(const void* p) { return (uint32_t)__cvta_generic_to_shared(p); }
__device__ __forceinline__ uint32_t mapa(uint32_t a, uint32_t r) { uint32_t o; asm("mapa.shared::cluster.u32 %0, %1, %2;" : "=r"(o) : "r"(a), "r"(r)); return o; }
__device__ __forceinline__ uint32_t pack2(float a, float b) { uint32_t r; asm("cvt.rn.bf16x2.f32 %0, %1, %2;" : "=r"(r) : "f"(b), "f"(a)); return r; }
__device__ __forceinline__ float bf_lo(uint32_t w) { return __uint_as_float(w << 16); }
__device__ __forceinline__ float bf_hi(uint32_t w) { return __uint_as_float(w & 0xffff0000u); }
__device__ __forceinline__ float ex2(float x) { float y; asm("ex2.approx.ftz.f32 %0, %1;" : "=f"(y) : "f"(x)); return y; }
__device__ __forceinline__ float rcp(float x) { float y; asm("rcp.approx.ftz.f32 %0, %1;" : "=f"(y) : "f"(x)); return y; }
__device__ __forceinline__ uint32_t clk32() { uint64_t c; asm volatile("mov.u64 %0, %%clock64;" : "=l"(c) :: "memory"); return (uint32_t)c; }

__device__ __forceinline__ void mbar_init(uint32_t b, uint32_t n) { asm volatile("mbarrier.init.shared::cta.b64 [%0], %1;" :: "r"(b), "r"(n) : "memory"); }
__device__ __forceinline__ void mbar_arrive(uint32_t b) { asm volatile("mbarrier.arrive.shared::cta.b64 _, [%0];" :: "r"(b) : "memory"); }
__device__ __forceinline__ void mbar_expect(uint32_t b, uint32_t n) { asm volatile("mbarrier.arrive.expect_tx.shared::cta.b64 _, [%0], %1;" :: "r"(b), "r"(n) : "memory"); }
__device__ __forceinline__ uint32_t mbar_try(uint32_t b, uint32_t par) {
  uint32_t ok;
  asm volatile("{\n.reg .pred p;\nmbarrier.try_wait.parity.shared::cta.b64 p, [%1], %2;\nselp.u32 %0, 1, 0, p;\n}" : "=r"(ok) : "r"(b), "r"(par) : "memory");
  return ok;
}
__device__ __forceinline__ void mbar_wait(uint32_t b, uint32_t par) {
  asm volatile("{\n.reg .pred p;\n"
               "LOOP:\n"
               "mbarrier.try_wait.parity.shared::cta.b64 p, [%0], %1;\n"
               "@!p bra.uni LOOP;\n}" :: "r"(b), "r"(par) : "memory");
}
__device__ __forceinline__ void mbar_wait_safe(uint32_t b, uint32_t par) {
  uint32_t c = 0;
  while (!mbar_try(b, par)) { if (++c > 4000000u) __trap(); }
}
__device__ __forceinline__ bool elect_one() {
  uint32_t p;
  asm volatile("{\n.reg .pred p;\nelect.sync _|p, 0xffffffff;\nselp.u32 %0, 1, 0, p;\n}" : "=r"(p));
  return p;
}
__device__ __forceinline__ void sched_fence(uint32_t x, uint32_t y) { asm volatile("{\n.reg .pred p;\nsetp.eq.u32 p, %0, %1;\n@p trap;\n}" :: "r"(x), "r"(y) : "memory"); }
template <class T> __device__ __forceinline__ T opaque32(T x) { asm volatile("" : "+r"(x)); return x; }
template <class T> __device__ __forceinline__ T opaque64(T x) { asm volatile("" : "+l"(x)); return x; }
template <int ID, int N> __device__ __forceinline__ void bar_sync() { asm volatile("bar.sync %0, %1;" :: "n"(ID), "n"(N) : "memory"); }
template <int ID, int N> __device__ __forceinline__ void bar_arrive() { asm volatile("bar.arrive %0, %1;" :: "n"(ID), "n"(N) : "memory"); }
__device__ __forceinline__ void fence_async_smem() { asm volatile("fence.proxy.async.shared::cta;" ::: "memory"); }
__device__ __forceinline__ void fence_async_all() { asm volatile("fence.proxy.async;" ::: "memory"); }
__device__ __forceinline__ void fence_gpu() { asm volatile("fence.acq_rel.gpu;" ::: "memory"); }
__device__ __forceinline__ void red_add_u32(uint32_t* p, uint32_t v) { asm volatile("red.relaxed.gpu.global.add.u32 [%0], %1;" :: "l"(p), "r"(v) : "memory"); }
__device__ __forceinline__ uint32_t ld_acquire(const uint32_t* p) { uint32_t v; asm volatile("ld.acquire.gpu.global.u32 %0, [%1];" : "=r"(v) : "l"(p) : "memory"); return v; }
__device__ __forceinline__ void wait_flag(const uint32_t* p, uint32_t target) {
  uint32_t c = 0;
  while (ld_acquire(p) < target) { if (++c > 20000000u) __trap(); __nanosleep(20); }
}

__device__ __forceinline__ void tma2d(uint32_t dst, const CUtensorMap* m, int c0, int c1, uint32_t bar) {
  asm volatile("cp.async.bulk.tensor.2d.shared::cluster.global.mbarrier::complete_tx::bytes [%0], [%1, {%3, %4}], [%2];"
               :: "r"(dst), "l"(m), "r"(bar), "r"(c0), "r"(c1) : "memory");
}
constexpr uint64_t L2_NORMAL = 0x1000000000000000ull, L2_FIRST = 0x12F0000000000000ull;
__device__ __forceinline__ void tma2d_p(uint32_t dst, const CUtensorMap* m, int c0, int c1, uint32_t bar, uint64_t pol) {
  asm volatile("cp.async.bulk.tensor.2d.shared::cluster.global.mbarrier::complete_tx::bytes.L2::cache_hint [%0], [%1, {%3, %4}], [%2], %5;"
               :: "r"(dst), "l"(m), "r"(bar), "r"(c0), "r"(c1), "l"(pol) : "memory");
}
__device__ __forceinline__ void bulk_g2s_p(uint32_t dst, const void* src, uint32_t bytes, uint32_t bar, uint64_t pol) {
  asm volatile("cp.async.bulk.shared::cluster.global.mbarrier::complete_tx::bytes.L2::cache_hint [%0], [%1], %2, [%3], %4;"
               :: "r"(dst), "l"(src), "r"(bytes), "r"(bar), "l"(pol) : "memory");
}
#define POL_RW L2_FIRST
__device__ __forceinline__ void tma2d_prefetch_p(const CUtensorMap* m, int c0, int c1, uint64_t pol) {
  asm volatile("cp.async.bulk.prefetch.tensor.2d.L2.global.L2::cache_hint [%0, {%1, %2}], %3;" :: "l"(m), "r"(c0), "r"(c1), "l"(pol) : "memory");
}
__device__ __forceinline__ void tma2d_prefetch(const CUtensorMap* m, int c0, int c1) {
  asm volatile("cp.async.bulk.prefetch.tensor.2d.L2.global [%0, {%1, %2}];" :: "l"(m), "r"(c0), "r"(c1) : "memory");
}
__device__ __forceinline__ void bulk_g2s(uint32_t dst, const void* src, uint32_t bytes, uint32_t bar) {
  asm volatile("cp.async.bulk.shared::cluster.global.mbarrier::complete_tx::bytes [%0], [%1], %2, [%3];"
               :: "r"(dst), "l"(src), "r"(bytes), "r"(bar) : "memory");
}
__device__ __forceinline__ void bulk_s2s(uint32_t dst, uint32_t src, uint32_t bytes, uint32_t bar) {
  asm volatile("cp.async.bulk.shared::cluster.shared::cta.mbarrier::complete_tx::bytes [%0], [%1], %2, [%3];"
               :: "r"(dst), "r"(src), "r"(bytes), "r"(bar) : "memory");
}
__device__ __forceinline__ void st_async1(uint32_t dst, uint32_t a, uint32_t bar) {
  asm volatile("st.async.shared::cluster.mbarrier::complete_tx::bytes.b32 [%0], %1, [%2];" :: "r"(dst), "r"(a), "r"(bar) : "memory");
}
__device__ __forceinline__ void st_async2(uint32_t dst, uint32_t a, uint32_t b, uint32_t bar) {
  asm volatile("st.async.shared::cluster.mbarrier::complete_tx::bytes.v2.b32 [%0], {%1, %2}, [%3];" :: "r"(dst), "r"(a), "r"(b), "r"(bar) : "memory");
}
__device__ __forceinline__ void st_async4(uint32_t dst, const uint32_t* r, uint32_t bar) {
  asm volatile("st.async.shared::cluster.mbarrier::complete_tx::bytes.v4.b32 [%0], {%1, %2, %3, %4}, [%5];"
               :: "r"(dst), "r"(r[0]), "r"(r[1]), "r"(r[2]), "r"(r[3]), "r"(bar) : "memory");
}
__device__ __forceinline__ void sts32(uint32_t a, uint32_t v) { asm volatile("st.shared.b32 [%0], %1;" :: "r"(a), "r"(v) : "memory"); }
__device__ __forceinline__ void sts64(uint32_t a, uint32_t x, uint32_t y) { asm volatile("st.shared.v2.b32 [%0], {%1, %2};" :: "r"(a), "r"(x), "r"(y) : "memory"); }
__device__ __forceinline__ void sts128(uint32_t a, uint32_t x, uint32_t y, uint32_t z, uint32_t w) {
  asm volatile("st.shared.v4.b32 [%0], {%1, %2, %3, %4};" :: "r"(a), "r"(x), "r"(y), "r"(z), "r"(w) : "memory");
}
__device__ __forceinline__ void lds128(uint32_t* r, uint32_t a) {
  asm volatile("ld.shared.v4.b32 {%0, %1, %2, %3}, [%4];" : "=r"(r[0]), "=r"(r[1]), "=r"(r[2]), "=r"(r[3]) : "r"(a) : "memory");
}
__device__ __forceinline__ uint32_t lds32(uint32_t a) { uint32_t r; asm volatile("ld.shared.b32 %0, [%1];" : "=r"(r) : "r"(a) : "memory"); return r; }
__device__ __forceinline__ void lds64(uint32_t* r, uint32_t a) {
  asm volatile("ld.shared.v2.b32 {%0, %1}, [%2];" : "=r"(r[0]), "=r"(r[1]) : "r"(a) : "memory");
}
__device__ __forceinline__ void lds128f(float* r, uint32_t a) {
  asm volatile("ld.shared.v4.f32 {%0, %1, %2, %3}, [%4];" : "=f"(r[0]), "=f"(r[1]), "=f"(r[2]), "=f"(r[3]) : "r"(a) : "memory");
}
__device__ __forceinline__ void lds64f(float* r, uint32_t a) {
  asm volatile("ld.shared.v2.f32 {%0, %1}, [%2];" : "=f"(r[0]), "=f"(r[1]) : "r"(a) : "memory");
}
__device__ __forceinline__ void ldsm4(uint32_t* r, uint32_t a) {
  asm volatile("ldmatrix.sync.aligned.m8n8.x4.shared.b16 {%0, %1, %2, %3}, [%4];" : "=r"(r[0]), "=r"(r[1]), "=r"(r[2]), "=r"(r[3]) : "r"(a) : "memory");
}
__device__ __forceinline__ void ldsm4t(uint32_t* r, uint32_t a) {
  asm volatile("ldmatrix.sync.aligned.m8n8.x4.trans.shared.b16 {%0, %1, %2, %3}, [%4];" : "=r"(r[0]), "=r"(r[1]), "=r"(r[2]), "=r"(r[3]) : "r"(a) : "memory");
}
__device__ __forceinline__ void ldsm2(uint32_t* r, uint32_t a) {
  asm volatile("ldmatrix.sync.aligned.m8n8.x2.shared.b16 {%0, %1}, [%2];" : "=r"(r[0]), "=r"(r[1]) : "r"(a) : "memory");
}
__device__ __forceinline__ void stsm4(uint32_t a, const uint32_t* r) {
  asm volatile("stmatrix.sync.aligned.m8n8.x4.shared.b16 [%0], {%1, %2, %3, %4};" :: "r"(a), "r"(r[0]), "r"(r[1]), "r"(r[2]), "r"(r[3]) : "memory");
}
__device__ __forceinline__ uint32_t hadd2(uint32_t a, uint32_t b) { uint32_t t; asm("add.rn.bf16x2 %0, %1, %2;" : "=r"(t) : "r"(a), "r"(b)); return t; }
__device__ __forceinline__ uint32_t hmax2(uint32_t a, uint32_t b) { uint32_t t; asm("max.bf16x2 %0, %1, %2;" : "=r"(t) : "r"(a), "r"(b)); return t; }
__device__ __forceinline__ void ldsm2t(uint32_t* r, uint32_t a) {
  asm volatile("ldmatrix.sync.aligned.m8n8.x2.trans.shared.b16 {%0, %1}, [%2];" : "=r"(r[0]), "=r"(r[1]) : "r"(a) : "memory");
}
__device__ __forceinline__ uint32_t movm(uint32_t x) { uint32_t y; asm volatile("movmatrix.sync.aligned.m8n8.trans.b16 %0, %1;" : "=r"(y) : "r"(x)); return y; }
__device__ __forceinline__ void hmma(float* d, uint32_t a0, uint32_t a1, uint32_t a2, uint32_t a3, uint32_t b0, uint32_t b1) {
  asm volatile("mma.sync.aligned.m16n8k16.row.col.f32.bf16.bf16.f32 {%0,%1,%2,%3}, {%4,%5,%6,%7}, {%8,%9}, {%0,%1,%2,%3};"
               : "+f"(d[0]), "+f"(d[1]), "+f"(d[2]), "+f"(d[3]) : "r"(a0), "r"(a1), "r"(a2), "r"(a3), "r"(b0), "r"(b1));
}
__device__ __forceinline__ void hmma0(float* d, uint32_t a0, uint32_t a1, uint32_t a2, uint32_t a3, uint32_t b0, uint32_t b1) {
  asm volatile("mma.sync.aligned.m16n8k16.row.col.f32.bf16.bf16.f32 {%0,%1,%2,%3}, {%4,%5,%6,%7}, {%8,%9}, {%10,%10,%10,%10};"
               : "=f"(d[0]), "=f"(d[1]), "=f"(d[2]), "=f"(d[3]) : "r"(a0), "r"(a1), "r"(a2), "r"(a3), "r"(b0), "r"(b1), "f"(0.f));
}
__device__ __forceinline__ void hmma_k8(float* d, uint32_t a0, uint32_t a1, uint32_t b0) {
  asm volatile("mma.sync.aligned.m16n8k8.row.col.f32.bf16.bf16.f32 {%0,%1,%2,%3}, {%4,%5}, {%6}, {%0,%1,%2,%3};"
               : "+f"(d[0]), "+f"(d[1]), "+f"(d[2]), "+f"(d[3]) : "r"(a0), "r"(a1), "r"(b0));
}
__host__ __device__ constexpr uint64_t mkdesc(uint32_t addr, uint32_t lbo, uint32_t sbo, uint32_t sw) {
  return (uint64_t)((addr & 0x3FFFF) >> 4) | ((uint64_t)(lbo >> 4) << 16) | ((uint64_t)(sbo >> 4) << 32) | ((uint64_t)sw << 62);
}
#define WG_FENCE() asm volatile("wgmma.fence.sync.aligned;" ::: "memory")
#define WG_COMMIT() asm volatile("wgmma.commit_group.sync.aligned;" ::: "memory")
#define WG_WAIT(n) asm volatile("wgmma.wait_group.sync.aligned " #n ";" ::: "memory")
template <int N> __device__ __forceinline__ void reg_fence(float* d) {
#pragma unroll
  for (int i = 0; i < N; i++) asm volatile("" : "+f"(d[i]) :: "memory");
}
template <int N> __device__ __forceinline__ void zero_regs(float* d) {
#pragma unroll
  for (int i = 0; i < N; i++) asm volatile("mov.b32 %0, 0;" : "=f"(d[i]));
}
template <int SD>
__device__ __forceinline__ void wg_rs32(float* d, uint32_t a0, uint32_t a1, uint32_t a2, uint32_t a3, uint64_t b) {
  asm volatile("wgmma.mma_async.sync.aligned.m64n32k16.f32.bf16.bf16 {%0,%1,%2,%3,%4,%5,%6,%7,%8,%9,%10,%11,%12,%13,%14,%15}, {%16,%17,%18,%19}, %20, %21, 1, 1, 0;"
               : "+f"(d[0]), "+f"(d[1]), "+f"(d[2]), "+f"(d[3]), "+f"(d[4]), "+f"(d[5]), "+f"(d[6]), "+f"(d[7]),
                 "+f"(d[8]), "+f"(d[9]), "+f"(d[10]), "+f"(d[11]), "+f"(d[12]), "+f"(d[13]), "+f"(d[14]), "+f"(d[15])
               : "r"(a0), "r"(a1), "r"(a2), "r"(a3), "l"(b), "n"(SD));
}
template <int TB>
__device__ __forceinline__ void wg_ss40(float* d, uint64_t a, uint64_t b) {
  asm volatile("wgmma.mma_async.sync.aligned.m64n40k16.f32.bf16.bf16 {%0,%1,%2,%3,%4,%5,%6,%7,%8,%9,%10,%11,%12,%13,%14,%15,%16,%17,%18,%19}, %20, %21, 1, 1, 1, 1, %22;"
               : "+f"(d[0]), "+f"(d[1]), "+f"(d[2]), "+f"(d[3]), "+f"(d[4]), "+f"(d[5]), "+f"(d[6]), "+f"(d[7]),
                 "+f"(d[8]), "+f"(d[9]), "+f"(d[10]), "+f"(d[11]), "+f"(d[12]), "+f"(d[13]), "+f"(d[14]), "+f"(d[15]),
                 "+f"(d[16]), "+f"(d[17]), "+f"(d[18]), "+f"(d[19])
               : "l"(a), "l"(b), "n"(TB));
}
template <int T>
__device__ __forceinline__ void wg_ss32(float* d, uint64_t a, uint64_t b) {
  asm volatile("wgmma.mma_async.sync.aligned.m64n32k16.f32.bf16.bf16 {%0,%1,%2,%3,%4,%5,%6,%7,%8,%9,%10,%11,%12,%13,%14,%15}, %16, %17, 1, 1, 1, %18, %18;"
               : "+f"(d[0]), "+f"(d[1]), "+f"(d[2]), "+f"(d[3]), "+f"(d[4]), "+f"(d[5]), "+f"(d[6]), "+f"(d[7]),
                 "+f"(d[8]), "+f"(d[9]), "+f"(d[10]), "+f"(d[11]), "+f"(d[12]), "+f"(d[13]), "+f"(d[14]), "+f"(d[15])
               : "l"(a), "l"(b), "n"(T));
}

constexpr int R_TAIL = 0;
constexpr int R_WO = 65536;
constexpr int R_QK = R_WO + 86016;
constexpr int R_P = R_QK + 10240;
constexpr int R_GA = R_P + 6400;
constexpr int R_M2 = R_GA + 16384;
constexpr int R_M1 = R_M2 + 7168;
constexpr int R_GB = R_M1 + 9216;
constexpr int R_VT = R_GB + 16384;
constexpr int R_VM = R_VT + 8192;
constexpr int R_XS = R_VM + 2048;
constexpr int R_OX = R_XS + 1280;
constexpr int R_BAR = R_OX + 2048;
constexpr int R_TRC = R_BAR + 256;
constexpr int R_SMEM = R_TRC + 1024;
constexpr int B_MB = 0, B_XS = 32, B_VM = 40, B_VT = 48, B_TS = 56, B_FA = 64, B_FB = 72, B_TAIL = 80, B_WO = 88, B_STG = 96, B_WM = 128, B_X = 136;
constexpr int NB_A = 1, NB_B = 2, NB_X = 3, NB_C = 4, NB_D = 5, NB_E = 6, NB_F = 7, NB_G = 8, NB_H = 9, NB_S = 10, NB_E2 = 11, NB_P = 12, NB_W0 = 13;

#define POLL_DELAY 750
#define POLL_DELAY1 700
#define P1K -1
#define P2K -1
#define ZS 2
#define HPF 4
#define PF1 2
#define PF2 2
#define PF3 2
#define PF4 0
#define RF_FIRST 0
#define BX_I 5
#define NCH 4
#define TOP2 0
#define CX_I 13
#define ATT_LATE 0
#define V_FENCE 1
#define SELF_STAS 1
#define Q_FENCE 1
#define ND_K 3
#define TRACE(i)
#define TS(i)

__device__ __forceinline__ int rot_chunk(int c, int rank) {
  int G = c;
  if (c < 9) { G = c + 3 * rank; if (G >= 9) G -= 9; }
  return G;
}
__device__ __forceinline__ int wo_tile(int i, int rank) {
  if (i < 12) return 12 * rank + i;
  const int r = i - 12 + 9 * rank;
  return r < 16 ? 48 + r : 20 + r;
}
__device__ __forceinline__ void load_chunk(uint32_t dst, int seg, int G, uint32_t bar) {
  mbar_expect(bar, 4096);
  bulk_g2s(dst, g_h + (size_t)(seg * 16 + G) * 4096, 4096, bar);
}
__device__ __forceinline__ void load_red(uint32_t* v, const float* p) {
#pragma unroll
  for (int j = 0; j < 2; j++)
    asm volatile("ld.relaxed.gpu.global.v4.u32 {%0, %1, %2, %3}, [%4];"
                 : "=r"(v[4 * j]), "=r"(v[4 * j + 1]), "=r"(v[4 * j + 2]), "=r"(v[4 * j + 3]) : "l"(p + j * 256) : "memory");
}
__device__ __forceinline__ bool red_done(const uint32_t* v) { return __all_sync(0xffffffffu, (v[3] & v[7]) == 0x42000000u); }
__device__ __forceinline__ uint32_t finish_red(uint32_t* v, const float* p) {
  uint32_t tries = 0;
  if (__builtin_expect(!red_done(v), 0)) {
    do { if (++tries > 20000000u) __trap(); load_red(v, p); } while (!red_done(v));
  }
  return tries;
}
__device__ __forceinline__ void exp10(float* sv, const uint32_t* x) {
  constexpr float SC = 0.08838834764831845f * 1.4426950408889634f;
  uint32_t m2 = hmax2(hmax2(hmax2(x[0], x[1]), hmax2(x[2], x[3])), x[4]);
  m2 = hmax2(m2, __shfl_xor_sync(0xffffffffu, m2, 1));
  m2 = hmax2(m2, __shfl_xor_sync(0xffffffffu, m2, 2));
  const float nm = -fmaxf(bf_lo(m2), bf_hi(m2)) * SC;
#pragma unroll
  for (int j = 0; j < 5; j++) { sv[2 * j] = ex2(fmaf(bf_lo(x[j]), SC, nm)); sv[2 * j + 1] = ex2(fmaf(bf_hi(x[j]), SC, nm)); }
}

__device__ __forceinline__ uint32_t arm_size(int w, bool isC) {
  return w == 0 ? (isC ? 1280 : 640) : w == 1 ? (isC ? 0 : 2048) : w == 2 ? (isC ? 0 : 8192) : (isC ? 0 : 1792);
}
struct RDesc { uint64_t tok[32], tail_b[16], tail_a[32]; };

template <int WG>
__device__ __forceinline__ void r_main(const uint32_t (&W)[48][4], const RDesc& dsc, int head, uint32_t rank, int lane_, int w) {
  const uint32_t sb = (rank << 24) + 0x400, bars = sb + R_BAR;
  const uint32_t to1 = rank == 0 ? 2u << 24 : 0u - (1u << 24), to2 = rank == 2 ? 0u - (2u << 24) : 1u << 24;
  const bool isC = rank == 2;
  const int lane = opaque32(lane_), warp = WG * 4 + w;
  const int gl = rot_chunk(4 * (lane & 3) + w, rank);
  const int g0 = __shfl_sync(0xffffffffu, gl, 0), g1 = __shfl_sync(0xffffffffu, gl, 1), g2 = __shfl_sync(0xffffffffu, gl, 2);
  const uint32_t arm_bytes = arm_size(w, isC);

#define L16 opaque32(sb + opaque32(lane) * 16)
#define L8 opaque32(sb + opaque32(lane) * 8)
#define L4 opaque32(sb + opaque32(lane) * 4)
#define LV opaque32(sb + R_VT + ((opaque32(lane) >> 3) & 1) * 512 + (opaque32(lane) >> 4) * 128 + (opaque32(lane) & 7) * 16)
#define SLOT(st) opaque64(slot0 + ((st) & 3) * 12288 + ((st) & 4) * 32)
  float* const slot0 = opaque64(g_slot + (rank * 1024 + warp * 128 + lane) * 4);
  const uint32_t woa = opaque32(sb + R_WO + warp * 12288 + ((lane >> 4) * 8 + (lane & 7)) * 32 + ((((lane >> 3) ^ (lane >> 2)) & 1) << 4));
  const bool has_wo = WG == 0 || isC || w < 3;
  float acc[20];
  uint32_t pk[8] = {0u, 0u, 0u, 0u, 0u, 0u, 0u, 0u};

  auto forward = [&](auto rd, const uint32_t* v, int st, uint32_t tries) {
    constexpr int RD = decltype(rd)::value;
    uint32_t u[6];
#pragma unroll
    for (int j = 0; j < 6; j++) u[j] = movm(v[4 * (j / 3) + j % 3]);
    const bool all3 = RD == 0 || w < 3;
    if (RD == 0) {
      const uint32_t a = L16 + R_M1 + w * 768, a2 = L8 + R_M1 + 512 + w * 768;
      st_async4(a + to1 + 3072, u, bars + to1 + B_MB + 8); st_async2(a2 + to1 + 3072, u[4], u[5], bars + to1 + B_MB + 8);
      sts128(a, u[0], u[1], u[2], u[3]); sts64(a2, u[4], u[5]);
      __syncwarp();
      if (elect_one()) mbar_arrive(bars + B_MB);
      st_async4(a + to2 + 6144, u, bars + to2 + B_MB + 16); st_async2(a2 + to2 + 6144, u[4], u[5], bars + to2 + B_MB + 16);
    } else {
      const uint32_t a = L4 + R_M2 + rank * 2304 + w * 768;
#pragma unroll
      for (int j = 0; j < 6; j++) if (j < 2 || all3) st_async1(a + to1 + j * 128, u[j], bars + to1 + B_MB + 24);
#pragma unroll
      for (int j = 0; j < 6; j++) if (j < 2 || all3) st_async1(a + to2 + j * 128, u[j], bars + to2 + B_MB + 24);
      if (SELF_STAS) {
#pragma unroll
        for (int j = 0; j < 6; j++) if (j < 2 || all3) st_async1(a + j * 128, u[j], bars + B_MB + 24);
      } else {
#pragma unroll
        for (int j = 0; j < 6; j++) if (j < 2 || all3) sts32(a + j * 128, u[j]);
        __syncwarp();
        if (elect_one()) mbar_arrive(bars + B_MB + 24);
      }
    }
  };

  auto send_vt = [&]() {
    if (elect_one()) {
      const uint32_t src = sb + R_VT + warp * 1024;
      bulk_s2s(src + to1, src, 1024, bars + to1 + B_VT);
      bulk_s2s(src + to2, src, 1024, bars + to2 + B_VT);
    }
  };
  auto store_att = [&](int sg) {
    uint32_t* op = reinterpret_cast<uint32_t*>(g_att + (size_t)((sg >> 2) * 64 + head * 2 + rank) * 16384 + (2 * w * 16 + (sg & 3) * 4) * 128) + opaque32(lane);
#pragma unroll
    for (int j = 0; j < 8; j++) op[(j & 1) * 512 + (j >> 1) * 32] = pk[j];
  };

  if (WG == 0) bar_arrive<NB_G, 256>();
#pragma unroll 1
  for (int s = -1; s < NSEG; s++) {
    const uint32_t par = (s + 1) & 1;
    const uint32_t last = s == NSEG - 1;
    TRACE(0);
    {
      float c[NCH][4];
      uint32_t b[3][6];
      const uint32_t ma = L16, m8 = L8;
#pragma unroll
      for (int i = 0; i < 18; i++) {
        if (i < 16) {
          if (i % 4 == 0 && !(i == 4 && TOP2)) mbar_wait(bars + B_MB + (i / 4) * 8, par ^ 1);
          if (i == 0 && TOP2) mbar_wait(bars + B_MB + 8, par ^ 1);
          if (i % 4 == 0) TRACE(1 + i / 4);
          if (i < 12) { lds128(b[i % 3], ma + R_M1 + i * 768); lds64(b[i % 3] + 4, m8 + R_M1 + 512 + i * 768); }
          else { ldsm4(b[i % 3], ma + R_M2 + 4096 + (i - 12) * 768); ldsm2(b[i % 3] + 4, ma + R_M2 + 4096 + 512 + (i - 12) * 768); }
          if (WG == 1 && i == BX_I) {
            bar_sync<NB_G, 256>();
            if (!last && elect_one()) load_chunk(sb + R_GB + w * 4096, s + 1, g0, bars + B_FB);
          }
          if (i == CX_I) {
            if (isC && s >= 0) send_vt();
            if (WG == 1 && ATT_LATE && !isC && s > 0) store_att(s - 1);
          }
          __syncwarp();
        }
        if (i >= 2) {
          const int j = i - 2;
#pragma unroll
          for (int q = 0; q < 3; q++) {
            const uint32_t* f = W[3 * j + q];
            if (3 * j + q < NCH) hmma0(c[3 * j + q], f[0], f[1], f[2], f[3], b[j % 3][2 * q], b[j % 3][2 * q + 1]);
            else hmma(c[(3 * j + q) % NCH], f[0], f[1], f[2], f[3], b[j % 3][2 * q], b[j % 3][2 * q + 1]);
          }
        }
        if (i == 14) zero_regs<16>(acc);
        if (i == 16) mbar_wait(bars + B_FA, last);
      }
#pragma unroll
      for (int j = 0; j < 4; j++) acc[16 + j] = NCH == 3 ? (c[0][j] + c[1][j]) + c[2][j] : (c[0][j] + c[1][j]) + (c[2][j] + c[NCH - 1][j]);
    }
    TRACE(5);
    bar_sync<NB_H, 256>();
    WG_FENCE();
#pragma unroll
    for (int k = 0; k < 16; k++) wg_ss40<0>(acc, dsc.tail_a[WG * 16 + k], dsc.tail_b[k]);
    WG_COMMIT();
    uint32_t vt[4][4];
    {
      const uint32_t a = opaque32(L4 + w * 256 + (isC ? WG * 1024 + R_VM : R_QK + 4096 + WG * 5120));
      const uint32_t qa = L16 + R_QK, xa = opaque32(LV + w * 2048 + (WG == 0 ? 0 : (opaque32(lane) & 8) * 64 + R_QK + 5120 - R_VT));
      const uint32_t d = opaque32(L4 + R_XS + rank * 640 + w * 256);
      if (s == 0) {
        mbar_wait_safe(bars + B_WO, 0);
        TS(10);
        if (WG == 1 && head == 0 && rank == 0 && w == 0 && elect_one()) red_add_u32(&g_flags[FL_GO], 1);
      }
      mbar_wait(bars + B_FB, last);
      if (WG == 0) mbar_wait(bars + B_VT, par);
      WG_WAIT(0);
      reg_fence<20>(acc);
      TRACE(6);
      const uint32_t p0 = pack2(acc[16], acc[17]), p1 = pack2(acc[18], acc[19]);
      sts32(a, p0); sts32(a + 128, p1);
      if (isC) {
        st_async1(a + to1, p0, bars + B_VM + to1); st_async1(a + to1 + 128, p1, bars + B_VM + to1);
        st_async1(a + to2, p0, bars + B_VM + to2); st_async1(a + to2 + 128, p1, bars + B_VM + to2);
      }
      if (WG == 0) {
        bar_arrive<NB_A, 256>();
        if (Q_FENCE && !isC) fence_async_smem();
#pragma unroll
        for (int i = 0; i < 4; i++) ldsm4(vt[i], xa + (i >> 1) * 1024 + (i & 1) * 256);
        bar_sync<NB_S, 256>();
      } else {
        bar_sync<NB_A, 256>();
        if (!isC) {
          if (w < 3) {
            uint32_t q[8], k[4][4];
            ldsm4t(q, qa + 4096); ldsm4t(k[0], xa); ldsm4t(k[1], xa + 256);
            ldsm4t(q + 4, qa + 4096 + 512); ldsm4t(k[2], xa + 512); ldsm4t(k[3], xa + 768);
            float x[4], y[4];
            hmma0(x, k[0][0], k[0][1], k[0][2], k[0][3], q[0], q[1]); hmma0(y, k[1][0], k[1][1], k[1][2], k[1][3], q[2], q[3]);
            hmma(x, k[2][0], k[2][1], k[2][2], k[2][3], q[4], q[5]); hmma(y, k[3][0], k[3][1], k[3][2], k[3][3], q[6], q[7]);
            const uint32_t s0 = pack2(x[0] + y[0], x[1] + y[1]), s1 = pack2(x[2] + y[2], x[3] + y[3]);
            st_async1(d + to1, s0, bars + B_XS + to1);
            st_async1(d + to2, s0, bars + B_XS + to2);
            if (w < 2) { st_async1(d + to1 + 128, s1, bars + B_XS + to1); st_async1(d + to2 + 128, s1, bars + B_XS + to2); sts32(d + 128, s1); }
            sts32(d, s0);
          }
        }
        bar_arrive<NB_S, 256>();
      }
    }
    if (WG == 1) {
      if (!last && elect_one()) load_chunk(sb + R_GA + w * 4096, s + 1, g1, bars + B_FA);
      {
        if (w > 0 && elect_one()) mbar_expect(bars + B_MB + 8 * w, w < 3 ? 3072 : SELF_STAS ? 28 * 256 : isC ? 18 * 256 : 19 * 256);
      }
      fence_async_smem();
      bar_sync<NB_B, 256>();
    }
    TRACE(7);
    WG_FENCE();
#pragma unroll
    for (int k = 0; k < 16; k++) wg_rs32<1>(acc, W[k][0], W[k][1], W[k][2], W[k][3], dsc.tok[16 + k]);
    WG_COMMIT();
    uint32_t wa[3][4];
    const uint32_t oxa = L16 + R_OX;
    if (WG == 0) {
      const uint32_t vma = oxa - (R_OX - R_VM) + w * 512, oa = opaque32(L4 + w * 512 + R_OX);
      TRACE(8);
      mbar_wait(bars + B_XS, par);
      TRACE(9);
      float sv[10];
      {
        uint32_t x[10];
        ldsm4t(x, oxa - (R_OX - R_XS)); ldsm4t(x + 4, oxa - (R_OX - R_XS) + 512); ldsm2t(x + 8, oxa - (R_OX - R_XS) + 1024);
        bar_arrive<NB_B, 256>();
#pragma unroll
        for (int j = 0; j < 5; j++) x[j] = hadd2(x[j], x[j + 5]);
        exp10(sv, x);
      }
      WG_WAIT(0);
      bar_arrive<NB_X, 256>();
      mbar_wait(bars + B_VM, par);
      uint32_t vm[4];
      ldsm4(vm, vma);
      uint32_t pb[5];
#pragma unroll
      for (int j = 0; j < 5; j++) pb[j] = pack2(sv[2 * j], sv[2 * j + 1]);
      TRACE(10);
      float o0[4], o1[4], sm[4];
      const uint32_t ONE = 0x3f803f80u;
      hmma0(o0, vt[0][0], vt[0][1], vt[0][2], vt[0][3], pb[0], pb[1]);
      hmma0(o1, vt[2][0], vt[2][1], vt[2][2], vt[2][3], pb[0], pb[1]);
      hmma0(sm, ONE, ONE, ONE, ONE, pb[0], pb[1]);
      hmma(sm, ONE, ONE, ONE, ONE, pb[2], pb[3]);
      hmma(o0, vt[1][0], vt[1][1], vt[1][2], vt[1][3], pb[2], pb[3]);
      hmma(o1, vt[3][0], vt[3][1], vt[3][2], vt[3][3], pb[2], pb[3]);
      hmma_k8(sm, ONE, ONE, pb[4]);
      hmma_k8(o0, vm[0], vm[1], pb[4]);
      hmma_k8(o1, vm[2], vm[3], pb[4]);
#pragma unroll
      for (int i = 0; i < 3; i++) ldsm4t(wa[i], woa + i * 4096);
      __syncwarp();
      const float i0 = rcp(sm[0]), i1 = rcp(sm[1]);
      sts32(oa, pack2(o0[0] * i0, o0[1] * i1)); sts32(oa + 128, pack2(o0[2] * i0, o0[3] * i1));
      sts32(oa + 256, pack2(o1[0] * i0, o1[1] * i1)); sts32(oa + 384, pack2(o1[2] * i0, o1[3] * i1));
      TRACE(11);
      bar_sync<NB_C, 128>();
    } else {
      if (!isC) {
        constexpr uint64_t dQ = mkdesc(0x400 + R_QK, 128, 1024, 0), dK = mkdesc(0x400 + R_QK + 5120, 128, 1024, 0);
        float sc[16];
        zero_regs<16>(sc);
        WG_FENCE();
#pragma unroll
        for (int k = 0; k < 4; k++) wg_ss32<1>(sc, dK + k * 16, dQ + k * 16);
        WG_COMMIT();
        const uint32_t top = rank == 0 ? to2 : to1, e = L4 + R_P + w * 256;
        WG_WAIT(0);
        bar_sync<NB_X, 256>();
        if (!last && elect_one()) load_chunk(sb + R_GB + w * 4096, s + 1, g2, bars + B_FB);
        reg_fence<16>(sc);
        if (w < 3) {
#pragma unroll
          for (int j = 0; j < 8; j++) {
            if ((j & 1) ? (j > 1 && (w == 0 || (w == 1 && j == 7))) : (j >= 4 || w != 1)) {
              const uint32_t t = pack2(sc[2 * j], sc[2 * j + 1]), o = (j >> 1) * 768 + (j & 1) * 128;
              st_async1(e + top + 3072 + o, t, bars + top + B_TS);
              sts32(e + o, t);
            }
          }
          __syncwarp();
          if (elect_one()) mbar_arrive(bars + B_TS);
        }
      } else {
        WG_WAIT(0);
        bar_sync<NB_X, 256>();
        if (!last && elect_one()) load_chunk(sb + R_GB + w * 4096, s + 1, g2, bars + B_FB);
      }
      TRACE(8);
      mbar_wait(bars + B_FA, 1);
      TRACE(11);
    }
    if (has_wo) {
      float* rslot = SLOT(s);
      uint32_t ob[4][4];
      float c[3][4];
      if (WG == 1) {
#pragma unroll
        for (int i = 0; i < 3; i++) ldsm4t(wa[i], woa + i * 4096);
        bar_sync<NB_D, 256>();
      }
      ldsm4t(ob[0], oxa);
      __syncwarp();
#pragma unroll
      for (int k = 0; k < 8; k++) {
        uint32_t nx[3][4];
        if ((k & 1) == 0 && k < 6) { ldsm4t(ob[(k >> 1) + 1], oxa + ((k >> 1) + 1) * 512); __syncwarp(); }
#pragma unroll
        for (int i = 0; i < 3; i++) {
          const uint32_t* o = ob[k >> 1] + (k & 1) * 2;
          if (k < 7) { ldsm4t(nx[i], woa + i * 4096 + (k + 1) * 512); if (i == 2) __syncwarp(); }
          if (k == 0) hmma0(c[i], wa[i][0], wa[i][1], wa[i][2], wa[i][3], o[0], o[1]);
          else hmma(c[i], wa[i][0], wa[i][1], wa[i][2], wa[i][3], o[0], o[1]);
#pragma unroll
          for (int q = 0; q < 4; q++) if (k < 7) wa[i][q] = nx[i][q];
        }
        if (k == ND_K && WG == 0) bar_arrive<NB_D, 256>();
      }
      const float* cv = &c[0][0];
      uint32_t r[6];
#pragma unroll
      for (int j = 0; j < 6; j++) r[j] = pack2(cv[2 * j], cv[2 * j + 1]);
      asm volatile("{\n.reg .pred p;\nsetp.lt.s32 p, %8, 0;\n@p bra.uni SKIP;\n"
                   "red.relaxed.gpu.global.add.noftz.v4.bf16x2 [%0], {%1, %2, %3, %7};\n"
                   "red.relaxed.gpu.global.add.noftz.v4.bf16x2 [%0+1024], {%4, %5, %6, %7};\nSKIP:\n}"
                   :: "l"(rslot), "r"(r[0]), "r"(r[1]), "r"(r[2]), "r"(r[3]), "r"(r[4]), "r"(r[5]), "r"(0x3f800000), "r"(s) : "memory");
    } else {
      bar_arrive<NB_D, 256>();
      if ((s & 3) == 0) {
        fence_gpu();
        if (s > 0 && elect_one()) red_add_u32(&g_flags[FL_ATT + 2 * (s - 4)], 1);
      }
      if (rank == 0 || head < 16)
        reinterpret_cast<uint4*>(g_slot)[((s + ZS) & 3) * 3072 + ((s + ZS) & 4) * 8 + rank * 2048 + head * 64 + opaque32(lane)] = make_uint4(0, 0, 0, 0);
      if (HPF && head < 16 && rank == 0 && s + HPF < NSEG && elect_one())
        asm volatile("cp.async.bulk.prefetch.L2.global [%0], 4096;" :: "l"(g_h + (size_t)((s + HPF) * 16 + head) * 4096) : "memory");
    }
    const uint32_t t_red = clk32();
    uint32_t v[8];
    const float* slot = SLOT(s);
    TRACE(13);
    if (WG == 0) {
      if (!isC) {
        const int ln = opaque32(lane), kg = w - (ln >> 3);
        const uint32_t r16 = sb + R_P + w * 768 + (ln & 7) * 16;
        const uint32_t ta = r16 + (kg >= 0 ? kg * 128 : 640);
        const int dg = (ln >> 2) - 2 * (ln & 3);
        const uint32_t keep = dg > 0 ? 0xffffffffu : dg == 0 ? 0x0000ffffu : 0u;
        mbar_wait(bars + B_TS, par);
        uint32_t x[6], y[4];
        ldsm4t(x, ta); ldsm4t(y, ta + 3072); ldsm2t(x + 4, r16 + 512 + ((ln >> 3) & 1) * 3072);
#pragma unroll
        for (int j = 0; j < 5; j++) x[j] = hadd2(x[j], j < 4 ? y[j] : x[5]);
        x[0] = (x[0] & keep) | (0xff80ff80u & ~keep);
        float sv[10];
        exp10(sv, x);
        float sum = (((sv[0] + sv[1]) + (sv[2] + sv[3])) + ((sv[4] + sv[5]) + (sv[6] + sv[7]))) + (sv[8] + sv[9]);
        sum += __shfl_xor_sync(0xffffffffu, sum, 1);
        sum += __shfl_xor_sync(0xffffffffu, sum, 2);
        const float inv = rcp(sum);
#pragma unroll
        for (int j = 0; j < 5; j++) x[j] = pack2(sv[2 * j] * inv, sv[2 * j + 1] * inv);
        stsm4(r16 + (kg & 3) * 128, x);
        sts32(sb + ln * 4 + w * 768 + R_P + 512, x[4]);
        fence_async_smem();
        bar_arrive<NB_P, 256>();
      }
      if (P1K < 0) { while (clk32() - t_red < POLL_DELAY) {} load_red(v, slot); }
      bar_sync<NB_E, 256>();
    } else {
      mbar_wait(bars + B_FB, 1);
    }
    TRACE(14);
    float ao[16];
    uint32_t v2[8];
    if (WG == 1) zero_regs<16>(ao);
    WG_FENCE();
#pragma unroll
    for (int k = 0; k < 32; k++) {
      if (WG == 0 && k == P1K) { sched_fence(head, 101); load_red(v, slot); }
      if (WG == 0 && k == P2K) { sched_fence(head, 102); load_red(v2, slot); }
      if (WG == 0 && k == 16) WG_COMMIT();
      wg_rs32<1>(acc, W[16 + k][0], W[16 + k][1], W[16 + k][2], W[16 + k][3], dsc.tok[k]);
    }
    WG_COMMIT();
    TRACE(12);
    if (WG == 1) {
      if (!isC) {
        constexpr uint64_t dP = mkdesc(0x400 + R_P, 128, 768, 0);
        const uint64_t dV = mkdesc(0x400 + R_VT, 128, 512, 0) + rank * 256, dM = mkdesc(0x400 + R_VM, 0, 128, 0) + rank * 64;
        bar_sync<NB_P, 256>();
        WG_FENCE();
        wg_ss32<0>(ao, dV, dP); wg_ss32<0>(ao, dV + 16, dP + 16); wg_ss32<0>(ao, dM, dP + 32);
        WG_COMMIT();
      }
      bar_arrive<NB_E, 256>();
      if (elect_one()) mbar_expect(bars + B_XS + 8 * w, arm_bytes);
      while (clk32() - t_red < POLL_DELAY1) {}
      load_red(v, slot);
      bar_arrive<NB_W0, 128>();
    } else {
      WG_WAIT(1);
      bar_arrive<NB_F, 256>();
      sched_fence(head, 100);
      v[3] = opaque32(v[3]);
      uint32_t tries = 0;
      if (P2K < 0) tries = finish_red(v, slot);
      else if (__builtin_expect(!red_done(v), 0)) {
#pragma unroll
        for (int j = 0; j < 8; j++) v[j] = v2[j];
        tries = 1;
        while (!red_done(v)) { if (++tries > 20000000u) __trap(); load_red(v, slot); }
      }
      forward(std::integral_constant<int, 0>(), v, s, tries);
      if (P2K >= 0) asm volatile("" :: "r"(v2[0]), "r"(v2[1]), "r"(v2[2]), "r"(v2[3]), "r"(v2[4]), "r"(v2[5]), "r"(v2[6]), "r"(v2[7]));
      TRACE(16);
    }
    WG_WAIT(0);
    reg_fence<16>(acc);
    if (WG == 0) bar_arrive<NB_G, 256>();
    TRACE(15);
    {
      uint32_t pq[8];
#pragma unroll
      for (int j = 0; j < 8; j++) pq[j] = pack2(acc[2 * j], acc[2 * j + 1]);
      if (WG == 1) {
        reg_fence<16>(ao);
#pragma unroll
        for (int j = 0; j < 8; j++) pk[j] = pack2(ao[2 * j], ao[2 * j + 1]);
      }
      if (!isC) {
        const uint32_t q = L4 + w * 256 + R_QK + WG * 5120;
#pragma unroll
        for (int j = 0; j < 8; j++) sts32(q + (j >> 1) * 1024 + (j & 1) * 128, pq[j]);
        if (WG == 1 && !ATT_LATE && s >= 0) store_att(s);
      } else {
        const uint32_t a = LV + warp * 1024;
        stsm4(a, pq); stsm4(a + 256, pq + 4);
      }
    }
    TRACE(17);
    if (WG == 1) {
      auto refill = [&]() {
        bar_sync<NB_F, 256>();
        if (s < NSEG - 2 && elect_one()) load_chunk(sb + R_GA + w * 4096, s + 2, 12 + w, bars + B_FA);
      };
      if (RF_FIRST) refill();
      if (has_wo) { v[3] = opaque32(v[3]); const uint32_t tries = finish_red(v, slot); forward(std::integral_constant<int, 1>(), v, s, tries); }
      if (!RF_FIRST) refill();
      TRACE(16);
    }
    if (isC && V_FENCE) { fence_async_smem(); __syncwarp(); }
    TRACE(18);
  }
  if (WG == 1 && ATT_LATE && !isC) store_att(NSEG - 1);
  if (WG == 1) bar_sync<NB_G, 256>();
  mbar_wait_safe(bars + B_MB + 8, 0); mbar_wait_safe(bars + B_MB + 16, 0); mbar_wait_safe(bars + B_MB + 24, 0);
#undef L16
#undef L8
#undef L4
#undef SLOT
#undef LV
}

__global__ void __cluster_dims__(3, 1, 1) __launch_bounds__(256, 1)
kernel_R(const __grid_constant__ CUtensorMap tmq, const __grid_constant__ CUtensorMap tmk, const __grid_constant__ CUtensorMap tmv,
         const __grid_constant__ CUtensorMap tmo, const __grid_constant__ CUtensorMap tmm, const __nv_bfloat16* __restrict__ x,
         const __nv_bfloat16* __restrict__ mem0, const __nv_bfloat16* __restrict__ cvec, const __grid_constant__ RDesc dsc) {
  extern __shared__ __align__(1024) uint8_t smem[];
  const uint32_t sb = smem_u32(smem);
  uint32_t rank; asm("mov.u32 %0, %%cluster_ctarank;" : "=r"(rank));
  rank = __shfl_sync(0xffffffffu, rank, 0);
  const int cta = blockIdx.x, head = __shfl_sync(0xffffffffu, cta / 3, 0);
  const int tid = threadIdx.x, lane = tid & 31;
  const int warp = __shfl_sync(0xffffffffu, tid >> 5, 0);
  const int wg = warp >> 2, w = warp & 3;
  const uint32_t bars = sb + R_BAR;
  const CUtensorMap* tmw = rank == 2 ? &tmv : (wg == 0 ? &tmq : &tmk);
  const int fcol = head * 128 + (rank == 2 ? wg * 64 : (int)rank * 64);

  asm volatile("griddepcontrol.launch_dependents;");
  uint32_t W[48][4];
  {
    if (sb != (rank << 24) + 0x400) __trap();
    if (tid == 0) {
      sts64(bars + 248, rank, head);
      mbar_init(bars + B_MB, 4); mbar_init(bars + B_MB + 8, 1); mbar_init(bars + B_MB + 16, 1); mbar_init(bars + B_MB + 24, SELF_STAS ? 1 : rank == 2 ? 5 : 4);
      for (int i = B_XS; i <= B_X; i += 8) mbar_init(bars + i, i == B_FA || i == B_FB || (i == B_TS && rank < 2) ? 4 : 1);
      asm volatile("fence.mbarrier_init.release.cluster;" ::: "memory");
      fence_async_smem();
    }
    __syncthreads();
    asm volatile("barrier.cluster.arrive.relaxed.aligned;" ::: "memory");
    TS(0);
    const int nwm = rank == 0 ? 6 : 5, wm0 = rank == 0 ? 0 : 5 * rank + 1, nrg = cta < 64 ? 3 : 2;
    if (elect_one()) {
      if (warp == 0) { mbar_expect(bars + B_WM, nwm * 8192); mbar_expect(bars + B_X, nrg * 16384); }
      if (warp < nwm) tma2d_p(sb + R_GA + warp * 8192, &tmm, head * 64, (wm0 + warp) * 64, bars + B_WM, POL_RW);
#pragma unroll 1
      for (int r = 0; r < nrg; r++) bulk_g2s(sb + R_TAIL + (r * 8 + warp) * 2064, x + (size_t)((cta + 96 * r) * 8 + warp) * D_, 2048, bars + B_X);
      if (w == 0) mbar_expect(bars + B_STG + wg * 16, 49152);
      if (w < 2) tma2d_p(sb + R_WO + wg * 49152 + w * 8192, tmw, fcol, rot_chunk(w, rank) * 64, bars + B_STG + wg * 16, POL_RW);
    }
    float* scr = reinterpret_cast<float*>(smem + R_VT);
#pragma unroll 1
    for (int i = tid; i < nwm * 64; i += 256) {
      const float c = __bfloat162float(cvec[wm0 * 64 + i]);
      scr[i] = __bfloat162float(__float2bfloat16(c / (1.f + __expf(-c))));
    }
    if (tid < 128) {
      uint32_t e[4] = {0u, 0u, 0u, 0u};
      if (cta >= 72 && (tid & 32)) {
        const uint16_t* mp = reinterpret_cast<const uint16_t*>(mem0) + 2 * (lane & 3) * D_ + (lane >> 2);
#pragma unroll
        for (int q = 0; q < 3; q++) {
          const int n = 3 * (tid >> 6) + q, col = wo_tile(3 * (cta & 7) + (n >> 1), (cta - 72) >> 3) * 16 + 8 * (n & 1);
          e[q] = mp[col] | (uint32_t)mp[col + D_] << 16;
        }
        e[3] = 0x42000000u;
      }
      reinterpret_cast<uint4*>(g_slot)[cta * 128 + tid] = make_uint4(e[0], e[1], e[2], e[3]);
    }
    __syncthreads();
    TS(1);
    mbar_wait_safe(bars + B_WM, 0);
    if (elect_one()) tma2d_p(sb + R_WO + wg * 49152 + (2 + w) * 8192, tmw, fcol, rot_chunk(2 + w, rank) * 64, bars + B_STG + wg * 16, POL_RW);
    {
      float a[8];
#pragma unroll
      for (int j = 0; j < 8; j++) a[j] = 0.f;
#pragma unroll 2
      for (int i = 0; i < 2 * nwm; i++) {
        uint32_t u[4];
        lds128(u, sb + R_GA + i * 4096 + tid * 16);
        const float sc = scr[i * 32 + (tid >> 3)];
#pragma unroll
        for (int j = 0; j < 4; j++) { a[2 * j] += sc * bf_lo(u[j]); a[2 * j + 1] += sc * bf_hi(u[j]); }
      }
#pragma unroll
      for (int j = 0; j < 8; j++) { a[j] += __shfl_xor_sync(0xffffffffu, a[j], 8); a[j] += __shfl_xor_sync(0xffffffffu, a[j], 16); }
      if (lane < 8) {
        sts128(sb + R_VT + 1536 + warp * 256 + lane * 32, __float_as_uint(a[0]), __float_as_uint(a[1]), __float_as_uint(a[2]), __float_as_uint(a[3]));
        sts128(sb + R_VT + 1552 + warp * 256 + lane * 32, __float_as_uint(a[4]), __float_as_uint(a[5]), __float_as_uint(a[6]), __float_as_uint(a[7]));
      }
    }
    __syncthreads();
    TS(2);
    if (warp == 7) {
      float t0 = 0.f, t1 = 0.f;
#pragma unroll
      for (int i = 0; i < 8; i++) { float t[2]; lds64f(t, sb + R_VT + 1536 + i * 256 + lane * 8); t0 += t[0]; t1 += t[1]; }
      reinterpret_cast<float2*>(g_modp + rank * 2048 + head * 64)[lane] = make_float2(t0, t1);
      fence_gpu();
      __syncwarp();
      if (lane == 0) red_add_u32(&g_flags[FL_S1], 1);
      __syncwarp();
    }
    mbar_wait_safe(bars + B_X, 0);
#pragma unroll 1
    for (int r = 0; r < nrg; r++) {
      float f[32];
#pragma unroll
      for (int i = 0; i < 4; i++) {
        uint32_t u[4];
        lds128(u, sb + R_TAIL + (r * 8 + warp) * 2064 + i * 512 + lane * 16);
#pragma unroll
        for (int j = 0; j < 4; j++) { f[8 * i + 2 * j] = bf_lo(u[j]); f[8 * i + 2 * j + 1] = bf_hi(u[j]); }
      }
      float t = 0.f;
#pragma unroll
      for (int i = 0; i < 32; i++) t += f[i];
#pragma unroll
      for (int o = 1; o < 32; o <<= 1) t += __shfl_xor_sync(0xffffffffu, t, o);
      const float mean = t * (1.f / D_);
      t = 0.f;
#pragma unroll
      for (int i = 0; i < 32; i++) t = fmaf(f[i] - mean, f[i] - mean, t);
#pragma unroll
      for (int o = 1; o < 32; o <<= 1) t += __shfl_xor_sync(0xffffffffu, t, o);
      const float rstd = rsqrtf(t * (1.f / D_) + 1e-5f);
      if (lane == 0) sts64(sb + R_VT + 3584 + (r * 8 + warp) * 8, __float_as_uint(rstd), __float_as_uint(-mean * rstd));
    }
    TS(3);
    if (w < PF1 && elect_one()) tma2d_prefetch_p(tmw, fcol, rot_chunk(6 + w, rank) * 64, POL_RW);
    if (tid == 0) wait_flag(&g_flags[FL_S1], 96);
    __syncthreads();
    TS(4);
    {
      float4 p[6];
#pragma unroll
      for (int i = 0; i < 6; i++) p[i] = __ldcg(reinterpret_cast<const float4*>(g_modp + (i >> 1) * 2048) + 2 * tid + (i & 1));
      if (w < PF2 && elect_one()) tma2d_prefetch_p(tmw, fcol, (9 + w) * 64, POL_RW);
      sts128(sb + R_VT + 5120 + tid * 16, pack2(p[0].x + p[2].x + p[4].x, p[0].y + p[2].y + p[4].y), pack2(p[0].z + p[2].z + p[4].z, p[0].w + p[2].w + p[4].w),
             pack2(p[1].x + p[3].x + p[5].x, p[1].y + p[3].y + p[5].y), pack2(p[1].z + p[3].z + p[5].z, p[1].w + p[3].w + p[5].w));
    }
    __syncthreads();
#pragma unroll 2
    for (int it = 0; it < 4 * nrg; it++) {
      const int r = it >> 2, rg = cta + 96 * r, c = 16 * warp + (lane >> 3) + 4 * (it & 3);
      uint32_t a[4], b[4], u[4], o[4];
      float t[2];
      lds128(u, sb + R_TAIL + (r * 8 + (lane & 7)) * 2064 + c * 16);
      lds128(a, sb + R_VT + 5120 + c * 16); lds128(b, sb + R_VT + 7168 + c * 16);
      lds64f(t, sb + R_VT + 3584 + (r * 8 + (lane & 7)) * 8);
#pragma unroll
      for (int j = 0; j < 4; j++)
        o[j] = pack2(fmaf(fmaf(bf_lo(u[j]), t[0], t[1]), 1.f + bf_lo(b[j]), bf_lo(a[j])), fmaf(fmaf(bf_hi(u[j]), t[0], t[1]), 1.f + bf_hi(b[j]), bf_hi(a[j])));
      *reinterpret_cast<uint4*>(g_h + (size_t)(rg >> 2) * 65536 + (lane & 7) * 16 + (c & 7) * 128 +
                                (c < 96 ? (c >> 3) * 4096 + (rg & 3) * 1024 : 49152 + (rg & 3) * 4096 + ((c >> 3) - 12) * 1024)) =
          make_uint4(o[0], o[1], o[2], o[3]);
    }
    TS(5);
    __syncthreads();
    TS(6);
    if (w < PF3 && elect_one()) tma2d_p(sb + R_TAIL + warp * 8192, tmw, fcol, 768 + w * 64, bars + B_TAIL, POL_RW);
    if (warp == 3 && lane == 0) { fence_gpu(); red_add_u32(&g_flags[FL_S2], 1); }
    __syncwarp();

    const uint32_t a0 = opaque32(sb + R_WO + wg * 49152 + ((lane >> 4) * 8 + (lane & 7)) * 128 + (((2 * w + ((lane >> 3) & 1)) ^ (lane & 7)) << 4));
    mbar_wait_safe(bars + B_STG + wg * 16, 0);
    TS(7);
#pragma unroll
    for (int i = 0; i < 24; i++) ldsm4t(W[i], a0 + i * 2048);
    if (tid == 0) wait_flag(&g_flags[FL_S2], 96);
    __syncthreads();
    asm volatile("fence.proxy.async.global;" ::: "memory");
    if (elect_one()) {
      if (wg == 0) load_chunk(sb + R_GA + w * 4096, 0, 12 + w, bars + B_FA);
      if (w == 0) mbar_expect(bars + B_STG + wg * 16 + 8, 49152);
#pragma unroll 1
      for (int c = w; c < 6; c += 4) tma2d_p(sb + R_WO + wg * 49152 + c * 8192, tmw, fcol, rot_chunk(6 + c, rank) * 64, bars + B_STG + wg * 16 + 8, POL_RW);
      if (warp == 0) mbar_expect(bars + B_TAIL, 65536);
      if (w >= PF3) tma2d_p(sb + R_TAIL + warp * 8192, tmw, fcol, 768 + w * 64, bars + B_TAIL, POL_RW);
      if (wg == 1) mbar_expect(bars + B_XS + 8 * w, w == 2 ? 0 : arm_size(w, rank == 2));
#pragma unroll 1
      for (int i = warp; i < PF4; i += 8) tma2d_prefetch(&tmo, 16 * wo_tile(i, rank), head * 128);
    }
    TS(8);
    mbar_wait_safe(bars + B_STG + wg * 16 + 8, 0);
    TS(9);
#pragma unroll
    for (int i = 0; i < 24; i++) ldsm4t(W[24 + i], a0 + i * 2048);
    __syncthreads();
    if (elect_one()) {
      const int n = rank == 2 ? 22 : 21;
      if (warp == 0) mbar_expect(bars + B_WO, n * 4096);
#pragma unroll 1
      for (int i = warp; i < n; i += 8) tma2d(sb + R_WO + i * 4096, &tmo, 16 * wo_tile(i, rank), head * 128, bars + B_WO);
    }
    sts32(sb + R_P + warp * 768 + 640 + lane * 4, wg == 0 ? 0u : 0xff80ff80u);
    mbar_wait_safe(bars + B_TAIL, 0);
    asm volatile("barrier.cluster.wait.aligned;\nbarrier.cluster.arrive.relaxed.aligned;\nbarrier.cluster.wait.aligned;" ::: "memory");
  }
  uint32_t rh[2];
  lds64(rh, bars + 248);
  rh[0] = __shfl_sync(0xffffffffu, rh[0], 0); rh[1] = __shfl_sync(0xffffffffu, rh[1], 0);
  if (wg == 0) r_main<0>(W, dsc, rh[1], rh[0], lane, w);
  else r_main<1>(W, dsc, rh[1], rh[0], lane, w);
  __syncthreads();
  if (rank < 2 && threadIdx.x == 0) { fence_gpu(); red_add_u32(&g_flags[FL_ATT + 8 * 15], 1); }
  asm volatile("barrier.cluster.arrive.release.aligned;\nbarrier.cluster.wait.acquire.aligned;" ::: "memory");
}

template <int TA> __device__ __forceinline__ void wg_ss256(float* d, uint64_t a, uint64_t b) {
  asm volatile("wgmma.mma_async.sync.aligned.m64n256k16.f32.bf16.bf16 {%0,%1,%2,%3,%4,%5,%6,%7,%8,%9,%10,%11,%12,%13,%14,%15,%16,%17,%18,%19,%20,%21,%22,%23,%24,%25,%26,%27,%28,%29,%30,%31,%32,%33,%34,%35,%36,%37,%38,%39,%40,%41,%42,%43,%44,%45,%46,%47,%48,%49,%50,%51,%52,%53,%54,%55,%56,%57,%58,%59,%60,%61,%62,%63,%64,%65,%66,%67,%68,%69,%70,%71,%72,%73,%74,%75,%76,%77,%78,%79,%80,%81,%82,%83,%84,%85,%86,%87,%88,%89,%90,%91,%92,%93,%94,%95,%96,%97,%98,%99,%100,%101,%102,%103,%104,%105,%106,%107,%108,%109,%110,%111,%112,%113,%114,%115,%116,%117,%118,%119,%120,%121,%122,%123,%124,%125,%126,%127}, %128, %129, 1, 1, 1, %130, 1;"
               : "+f"(d[0]), "+f"(d[1]), "+f"(d[2]), "+f"(d[3]), "+f"(d[4]), "+f"(d[5]), "+f"(d[6]), "+f"(d[7]),
                 "+f"(d[8]), "+f"(d[9]), "+f"(d[10]), "+f"(d[11]), "+f"(d[12]), "+f"(d[13]), "+f"(d[14]), "+f"(d[15]),
                 "+f"(d[16]), "+f"(d[17]), "+f"(d[18]), "+f"(d[19]), "+f"(d[20]), "+f"(d[21]), "+f"(d[22]), "+f"(d[23]),
                 "+f"(d[24]), "+f"(d[25]), "+f"(d[26]), "+f"(d[27]), "+f"(d[28]), "+f"(d[29]), "+f"(d[30]), "+f"(d[31]),
                 "+f"(d[32]), "+f"(d[33]), "+f"(d[34]), "+f"(d[35]), "+f"(d[36]), "+f"(d[37]), "+f"(d[38]), "+f"(d[39]),
                 "+f"(d[40]), "+f"(d[41]), "+f"(d[42]), "+f"(d[43]), "+f"(d[44]), "+f"(d[45]), "+f"(d[46]), "+f"(d[47]),
                 "+f"(d[48]), "+f"(d[49]), "+f"(d[50]), "+f"(d[51]), "+f"(d[52]), "+f"(d[53]), "+f"(d[54]), "+f"(d[55]),
                 "+f"(d[56]), "+f"(d[57]), "+f"(d[58]), "+f"(d[59]), "+f"(d[60]), "+f"(d[61]), "+f"(d[62]), "+f"(d[63]),
                 "+f"(d[64]), "+f"(d[65]), "+f"(d[66]), "+f"(d[67]), "+f"(d[68]), "+f"(d[69]), "+f"(d[70]), "+f"(d[71]),
                 "+f"(d[72]), "+f"(d[73]), "+f"(d[74]), "+f"(d[75]), "+f"(d[76]), "+f"(d[77]), "+f"(d[78]), "+f"(d[79]),
                 "+f"(d[80]), "+f"(d[81]), "+f"(d[82]), "+f"(d[83]), "+f"(d[84]), "+f"(d[85]), "+f"(d[86]), "+f"(d[87]),
                 "+f"(d[88]), "+f"(d[89]), "+f"(d[90]), "+f"(d[91]), "+f"(d[92]), "+f"(d[93]), "+f"(d[94]), "+f"(d[95]),
                 "+f"(d[96]), "+f"(d[97]), "+f"(d[98]), "+f"(d[99]), "+f"(d[100]), "+f"(d[101]), "+f"(d[102]), "+f"(d[103]),
                 "+f"(d[104]), "+f"(d[105]), "+f"(d[106]), "+f"(d[107]), "+f"(d[108]), "+f"(d[109]), "+f"(d[110]), "+f"(d[111]),
                 "+f"(d[112]), "+f"(d[113]), "+f"(d[114]), "+f"(d[115]), "+f"(d[116]), "+f"(d[117]), "+f"(d[118]), "+f"(d[119]),
                 "+f"(d[120]), "+f"(d[121]), "+f"(d[122]), "+f"(d[123]), "+f"(d[124]), "+f"(d[125]), "+f"(d[126]), "+f"(d[127])
               : "l"(a), "l"(b), "n"(TA));
}
template <int TA> __device__ __forceinline__ void wg_ss128(float* d, uint64_t a, uint64_t b) {
  asm volatile("wgmma.mma_async.sync.aligned.m64n128k16.f32.bf16.bf16 {%0,%1,%2,%3,%4,%5,%6,%7,%8,%9,%10,%11,%12,%13,%14,%15,%16,%17,%18,%19,%20,%21,%22,%23,%24,%25,%26,%27,%28,%29,%30,%31,%32,%33,%34,%35,%36,%37,%38,%39,%40,%41,%42,%43,%44,%45,%46,%47,%48,%49,%50,%51,%52,%53,%54,%55,%56,%57,%58,%59,%60,%61,%62,%63}, %64, %65, 1, 1, 1, %66, 1;"
               : "+f"(d[0]), "+f"(d[1]), "+f"(d[2]), "+f"(d[3]), "+f"(d[4]), "+f"(d[5]), "+f"(d[6]), "+f"(d[7]),
                 "+f"(d[8]), "+f"(d[9]), "+f"(d[10]), "+f"(d[11]), "+f"(d[12]), "+f"(d[13]), "+f"(d[14]), "+f"(d[15]),
                 "+f"(d[16]), "+f"(d[17]), "+f"(d[18]), "+f"(d[19]), "+f"(d[20]), "+f"(d[21]), "+f"(d[22]), "+f"(d[23]),
                 "+f"(d[24]), "+f"(d[25]), "+f"(d[26]), "+f"(d[27]), "+f"(d[28]), "+f"(d[29]), "+f"(d[30]), "+f"(d[31]),
                 "+f"(d[32]), "+f"(d[33]), "+f"(d[34]), "+f"(d[35]), "+f"(d[36]), "+f"(d[37]), "+f"(d[38]), "+f"(d[39]),
                 "+f"(d[40]), "+f"(d[41]), "+f"(d[42]), "+f"(d[43]), "+f"(d[44]), "+f"(d[45]), "+f"(d[46]), "+f"(d[47]),
                 "+f"(d[48]), "+f"(d[49]), "+f"(d[50]), "+f"(d[51]), "+f"(d[52]), "+f"(d[53]), "+f"(d[54]), "+f"(d[55]),
                 "+f"(d[56]), "+f"(d[57]), "+f"(d[58]), "+f"(d[59]), "+f"(d[60]), "+f"(d[61]), "+f"(d[62]), "+f"(d[63])
               : "l"(a), "l"(b), "n"(TA));
}
template <int TA> __device__ __forceinline__ void wg_ss256_first(float* d, uint64_t a, uint64_t b) {
  asm volatile("wgmma.mma_async.sync.aligned.m64n256k16.f32.bf16.bf16 {%0,%1,%2,%3,%4,%5,%6,%7,%8,%9,%10,%11,%12,%13,%14,%15,%16,%17,%18,%19,%20,%21,%22,%23,%24,%25,%26,%27,%28,%29,%30,%31,%32,%33,%34,%35,%36,%37,%38,%39,%40,%41,%42,%43,%44,%45,%46,%47,%48,%49,%50,%51,%52,%53,%54,%55,%56,%57,%58,%59,%60,%61,%62,%63,%64,%65,%66,%67,%68,%69,%70,%71,%72,%73,%74,%75,%76,%77,%78,%79,%80,%81,%82,%83,%84,%85,%86,%87,%88,%89,%90,%91,%92,%93,%94,%95,%96,%97,%98,%99,%100,%101,%102,%103,%104,%105,%106,%107,%108,%109,%110,%111,%112,%113,%114,%115,%116,%117,%118,%119,%120,%121,%122,%123,%124,%125,%126,%127}, %128, %129, 0, 1, 1, %130, 1;"
               : "=f"(d[0]), "=f"(d[1]), "=f"(d[2]), "=f"(d[3]), "=f"(d[4]), "=f"(d[5]), "=f"(d[6]), "=f"(d[7]),
                 "=f"(d[8]), "=f"(d[9]), "=f"(d[10]), "=f"(d[11]), "=f"(d[12]), "=f"(d[13]), "=f"(d[14]), "=f"(d[15]),
                 "=f"(d[16]), "=f"(d[17]), "=f"(d[18]), "=f"(d[19]), "=f"(d[20]), "=f"(d[21]), "=f"(d[22]), "=f"(d[23]),
                 "=f"(d[24]), "=f"(d[25]), "=f"(d[26]), "=f"(d[27]), "=f"(d[28]), "=f"(d[29]), "=f"(d[30]), "=f"(d[31]),
                 "=f"(d[32]), "=f"(d[33]), "=f"(d[34]), "=f"(d[35]), "=f"(d[36]), "=f"(d[37]), "=f"(d[38]), "=f"(d[39]),
                 "=f"(d[40]), "=f"(d[41]), "=f"(d[42]), "=f"(d[43]), "=f"(d[44]), "=f"(d[45]), "=f"(d[46]), "=f"(d[47]),
                 "=f"(d[48]), "=f"(d[49]), "=f"(d[50]), "=f"(d[51]), "=f"(d[52]), "=f"(d[53]), "=f"(d[54]), "=f"(d[55]),
                 "=f"(d[56]), "=f"(d[57]), "=f"(d[58]), "=f"(d[59]), "=f"(d[60]), "=f"(d[61]), "=f"(d[62]), "=f"(d[63]),
                 "=f"(d[64]), "=f"(d[65]), "=f"(d[66]), "=f"(d[67]), "=f"(d[68]), "=f"(d[69]), "=f"(d[70]), "=f"(d[71]),
                 "=f"(d[72]), "=f"(d[73]), "=f"(d[74]), "=f"(d[75]), "=f"(d[76]), "=f"(d[77]), "=f"(d[78]), "=f"(d[79]),
                 "=f"(d[80]), "=f"(d[81]), "=f"(d[82]), "=f"(d[83]), "=f"(d[84]), "=f"(d[85]), "=f"(d[86]), "=f"(d[87]),
                 "=f"(d[88]), "=f"(d[89]), "=f"(d[90]), "=f"(d[91]), "=f"(d[92]), "=f"(d[93]), "=f"(d[94]), "=f"(d[95]),
                 "=f"(d[96]), "=f"(d[97]), "=f"(d[98]), "=f"(d[99]), "=f"(d[100]), "=f"(d[101]), "=f"(d[102]), "=f"(d[103]),
                 "=f"(d[104]), "=f"(d[105]), "=f"(d[106]), "=f"(d[107]), "=f"(d[108]), "=f"(d[109]), "=f"(d[110]), "=f"(d[111]),
                 "=f"(d[112]), "=f"(d[113]), "=f"(d[114]), "=f"(d[115]), "=f"(d[116]), "=f"(d[117]), "=f"(d[118]), "=f"(d[119]),
                 "=f"(d[120]), "=f"(d[121]), "=f"(d[122]), "=f"(d[123]), "=f"(d[124]), "=f"(d[125]), "=f"(d[126]), "=f"(d[127])
               : "l"(a), "l"(b), "n"(TA));
}
template <int TA> __device__ __forceinline__ void wg_ss128_first(float* d, uint64_t a, uint64_t b) {
  asm volatile("wgmma.mma_async.sync.aligned.m64n128k16.f32.bf16.bf16 {%0,%1,%2,%3,%4,%5,%6,%7,%8,%9,%10,%11,%12,%13,%14,%15,%16,%17,%18,%19,%20,%21,%22,%23,%24,%25,%26,%27,%28,%29,%30,%31,%32,%33,%34,%35,%36,%37,%38,%39,%40,%41,%42,%43,%44,%45,%46,%47,%48,%49,%50,%51,%52,%53,%54,%55,%56,%57,%58,%59,%60,%61,%62,%63}, %64, %65, 0, 1, 1, %66, 1;"
               : "=f"(d[0]), "=f"(d[1]), "=f"(d[2]), "=f"(d[3]), "=f"(d[4]), "=f"(d[5]), "=f"(d[6]), "=f"(d[7]),
                 "=f"(d[8]), "=f"(d[9]), "=f"(d[10]), "=f"(d[11]), "=f"(d[12]), "=f"(d[13]), "=f"(d[14]), "=f"(d[15]),
                 "=f"(d[16]), "=f"(d[17]), "=f"(d[18]), "=f"(d[19]), "=f"(d[20]), "=f"(d[21]), "=f"(d[22]), "=f"(d[23]),
                 "=f"(d[24]), "=f"(d[25]), "=f"(d[26]), "=f"(d[27]), "=f"(d[28]), "=f"(d[29]), "=f"(d[30]), "=f"(d[31]),
                 "=f"(d[32]), "=f"(d[33]), "=f"(d[34]), "=f"(d[35]), "=f"(d[36]), "=f"(d[37]), "=f"(d[38]), "=f"(d[39]),
                 "=f"(d[40]), "=f"(d[41]), "=f"(d[42]), "=f"(d[43]), "=f"(d[44]), "=f"(d[45]), "=f"(d[46]), "=f"(d[47]),
                 "=f"(d[48]), "=f"(d[49]), "=f"(d[50]), "=f"(d[51]), "=f"(d[52]), "=f"(d[53]), "=f"(d[54]), "=f"(d[55]),
                 "=f"(d[56]), "=f"(d[57]), "=f"(d[58]), "=f"(d[59]), "=f"(d[60]), "=f"(d[61]), "=f"(d[62]), "=f"(d[63])
               : "l"(a), "l"(b), "n"(TA));
}

constexpr uint32_t H_SB = 0x400;
constexpr int H_STAGE = 49152, H_NST = 4;
constexpr int H_STG = H_NST * H_STAGE;
constexpr int H_VEC = H_STG + 3 * 8192;
constexpr int H_GATE = H_VEC + 6656;
constexpr int H_BAR = H_GATE + 1024;
constexpr int H_SMEM = H_BAR + 256;
constexpr int HB_FULL = 0, HB_EMPTY = 32, HB_IFULL = 64, HB_IEMPTY = 80, HB_VFULL = 96, HB_STGF = 112, HB_ITEM = 120, HB_Q = 128, HB_SRDY = 160, HB_SFREE = 184,
              HB_MFULL = 208, HB_MEMPTY = 224, HB_MAIL = 240;
constexpr int NB_HX = 4, NB_HY = 5, NB_HZ = 6;
enum { IT_END = 0, IT_MOD = 1, IT_XT = 2, IT_OUT = 3, IT_WS = 4, IT_F1 = 5, IT_F2 = 6, IT_STAT = 7 };
constexpr int N_MOD = 32, N_WS = 28, N_XT = 2, N_STAT = 4;
constexpr int MAX_ITEMS = 1400;
#define NH2 94
constexpr int NH1 = 36;
struct HList { uint32_t n, head, tbase; uint32_t it[MAX_ITEMS]; };
#define HT(i)

#define POL_WO L2_NORMAL
#define POL_W2 L2_NORMAL
#define POL_ATT L2_FIRST
#define POL_ACT L2_FIRST
#define POL_PRE L2_FIRST
__device__ __forceinline__ void mbar_arrive_n(uint32_t b, uint32_t n) { asm volatile("mbarrier.arrive.shared::cta.b64 _, [%0], %1;" :: "r"(b), "r"(n) : "memory"); }
__device__ __forceinline__ void mbar_arrive_cl(uint32_t b) { asm volatile("mbarrier.arrive.shared::cluster.b64 _, [%0];" :: "r"(b) : "memory"); }
__device__ __forceinline__ void h_free(uint32_t b, uint32_t pm) { mbar_arrive(b); mbar_arrive_cl(b ^ pm); }
__device__ __forceinline__ void tma2d_mc(uint32_t dst, const CUtensorMap* m, int c0, int c1, uint32_t bar, uint64_t pol) {
  asm volatile("cp.async.bulk.tensor.2d.shared::cluster.global.mbarrier::complete_tx::bytes.multicast::cluster.L2::cache_hint [%0], [%1, {%3, %4}], [%2], %5, %6;"
               :: "r"(dst), "l"(m), "r"(bar), "r"(c0), "r"(c1), "h"((uint16_t)3), "l"(pol) : "memory");
}
__device__ __forceinline__ void bulk_mc(uint32_t dst, const void* src, uint32_t bytes, uint32_t bar, uint64_t pol) {
  asm volatile("cp.async.bulk.shared::cluster.global.mbarrier::complete_tx::bytes.multicast::cluster.L2::cache_hint [%0], [%1], %2, [%3], %4, %5;"
               :: "r"(dst), "l"(src), "r"(bytes), "r"(bar), "h"((uint16_t)3), "l"(pol) : "memory");
}
__device__ __forceinline__ void cluster_sync() {
  asm volatile("barrier.cluster.arrive.release.aligned;\nbarrier.cluster.wait.acquire.aligned;" ::: "memory");
}
__device__ __forceinline__ void bulk_s2g(void* dst, uint32_t src, uint32_t bytes) {
  asm volatile("cp.async.bulk.global.shared::cta.bulk_group [%0], [%1], %2;" :: "l"(dst), "r"(src), "r"(bytes) : "memory");
}
__device__ __forceinline__ void tma2d_add(const CUtensorMap* m, int c0, int c1, uint32_t src) {
  asm volatile("cp.reduce.async.bulk.tensor.2d.global.shared::cta.add.tile.bulk_group [%0, {%2, %3}], [%1];" :: "l"(m), "r"(src), "r"(c0), "r"(c1) : "memory");
}
__device__ __forceinline__ void bulk_commit() { asm volatile("cp.async.bulk.commit_group;" ::: "memory"); }
template <int N> __device__ __forceinline__ void bulk_wait_read() { asm volatile("cp.async.bulk.wait_group.read %0;" :: "n"(N) : "memory"); }
__device__ __forceinline__ void bulk_wait_all() { asm volatile("cp.async.bulk.wait_group 0;" ::: "memory"); }
__device__ __forceinline__ uint32_t hfma2(uint32_t a, uint32_t b, uint32_t c) { uint32_t t; asm("fma.rn.bf16x2 %0, %1, %2, %3;" : "=r"(t) : "r"(a), "r"(b), "r"(c)); return t; }
__device__ __forceinline__ float lds32f(uint32_t a) { return __uint_as_float(lds32(a)); }

template <int BN, int TA, int K0, int K1>
__device__ __forceinline__ void h_mma(float* acc, uint64_t da, uint64_t db) {
#pragma unroll
  for (int k = K0; k < K1; k++) {
    const uint64_t a = da + k * (TA ? 256 : 2), b = db + k * 128;
    if (BN == 256) wg_ss256<TA>(acc, a, b); else wg_ss128<TA>(acc, a, b);
  }
}
template <int BN, int TA>
__device__ __forceinline__ void h_mainloop(float* acc, uint32_t sb, uint32_t pm, int nst, uint32_t& st, uint32_t& ph, int wg, bool leader, uint32_t clk_q) {
  const uint64_t da0 = TA ? mkdesc(H_SB + wg * 1024, 2048, 128, 0) : mkdesc(H_SB + wg * 8192, 16, 1024, 1);
  const uint64_t db0 = mkdesc(H_SB + 16384, 8192, 1024, 1);
  const uint32_t full = sb + H_BAR + HB_FULL, empty = sb + H_BAR + HB_EMPTY;
  uint32_t prev = st;
  {
    mbar_wait(full + st * 8, ph);
    HT(1);
    const uint64_t da = da0 + st * (H_STAGE >> 4), db = db0 + st * (H_STAGE >> 4);
    WG_FENCE();
    if (BN == 256) wg_ss256_first<TA>(acc, da, db); else wg_ss128_first<TA>(acc, da, db);
    h_mma<BN, TA, 1, 4>(acc, da, db);
    WG_COMMIT();
    if (++st == H_NST) { st = 0; ph ^= 1; }
  }
  {
    mbar_wait(full + st * 8, ph);
    const uint64_t da = da0 + st * (H_STAGE >> 4), db = db0 + st * (H_STAGE >> 4);
    WG_FENCE();
    h_mma<BN, TA, 0, 3>(acc, da, db);
    WG_COMMIT();
    h_mma<BN, TA, 3, 4>(acc, da, db);
    WG_COMMIT();
    WG_WAIT(1);
    if (leader) h_free(empty + prev * 8, pm);
    if (wg) bar_arrive<NB_HY, 256>(); else bar_sync<NB_HY, 256>();
    prev = st;
    if (++st == H_NST) { st = 0; ph ^= 1; }
  }
#pragma unroll 1
  for (int i = 4; i < nst; i++) {
    mbar_wait(full + st * 8, ph);
    const uint64_t da = da0 + st * (H_STAGE >> 4), db = db0 + st * (H_STAGE >> 4);
    WG_FENCE();
    h_mma<BN, TA, 0, 4>(acc, da, db);
    WG_COMMIT();
    WG_WAIT(1);
    if (leader) h_free(empty + prev * 8, pm);
    prev = st;
    if (++st == H_NST) { st = 0; ph ^= 1; }
  }
  if (wg) {
    WG_WAIT(0);
    if (leader) h_free(empty + prev * 8, pm);
    bar_sync<NB_HX, 256>();
  }
  {
    mbar_wait(full + st * 8, ph);
    const uint64_t da = da0 + st * (H_STAGE >> 4), db = db0 + st * (H_STAGE >> 4);
    WG_FENCE();
    h_mma<BN, TA, 0, 4>(acc, da, db);
    WG_COMMIT();
    WG_WAIT(1);
    if (leader && !wg) h_free(empty + prev * 8, pm);
    prev = st;
    if (++st == H_NST) { st = 0; ph ^= 1; }
  }
  {
    mbar_wait(full + st * 8, ph);
    const uint64_t da = da0 + st * (H_STAGE >> 4), db = db0 + st * (H_STAGE >> 4);
    WG_FENCE();
    h_mma<BN, TA, 0, 3>(acc, da, db);
    WG_COMMIT();
    h_mma<BN, TA, 3, 4>(acc, da, db);
    WG_COMMIT();
    WG_WAIT(1);
    if (leader) h_free(empty + prev * 8, pm);
    if (!wg) bar_arrive<NB_HX, 256>();
  }
}
__device__ __forceinline__ void h_release(uint32_t sb, uint32_t pm, uint32_t& st, uint32_t& ph, bool leader) {
  if (leader) h_free(sb + H_BAR + HB_EMPTY + st * 8, pm);
  if (++st == H_NST) { st = 0; ph ^= 1; }
}

__device__ __forceinline__ uint32_t stg_acquire(uint32_t sb, uint32_t g, uint32_t& b) {
  const uint32_t q = (g * 43691u) >> 17;
  b = g - 3 * q;
  mbar_wait(sb + H_BAR + HB_SFREE + b * 8, (q & 1) ^ 1);
  return sb + H_STG + b * 8192;
}
__device__ __forceinline__ void stg_release(uint32_t sb, uint32_t b, int lane) {
  __syncwarp();
  if (lane == 0) mbar_arrive(sb + H_BAR + HB_SRDY + b * 8);
}
__device__ __forceinline__ uint32_t hmul2(uint32_t a, uint32_t b) { uint32_t t; asm("mul.rn.bf16x2 %0, %1, %2;" : "=r"(t) : "r"(a), "r"(b)); return t; }
template <int BN>
__device__ __forceinline__ void h_gated(float* acc, uint32_t va, uint32_t vb, uint32_t vp, uint32_t sb, uint32_t pm, uint32_t& st, uint32_t& ph, uint32_t g0, int wg, bool leader,
                                        int warp, int lane, uint32_t clk_q) {
  uint32_t gt[BN / 8];
  mbar_wait(vb, vp);
#pragma unroll
  for (int i = 0; i < BN / 32; i++) lds128(gt + 4 * i, va + i * 64 + (lane & 3) * 16);
  WG_WAIT(0);
  reg_fence<BN / 2>(acc);
  h_release(sb, pm, st, ph, leader);
  HT(2);
  const uint32_t ro = ((warp & 3) * 16 + (lane & 7)) * 128, x0 = ((lane >> 3) ^ (lane & 7)) << 4;
  if (BN == 256 && wg) bar_sync<NB_HZ, 256>();
#pragma unroll
  for (int u = 0; u < BN / 64; u++) {
    uint32_t b;
    const uint32_t base = stg_acquire(sb, g0 + u, b) + ro;
    if (BN == 256 && u == 1 && !wg) bar_arrive<NB_HZ, 256>();
#pragma unroll
    for (int c2 = 0; c2 < 2; c2++) {
      const int c = 2 * u + c2;
#pragma unroll
      for (int h = 0; h < 2; h++) {
        uint32_t y[4];
#pragma unroll
        for (int j = 0; j < 4; j++) { const float* a = acc + c * 16 + j * 4 + h * 2; y[j] = hmul2(pack2(a[0], a[1]), gt[4 * c + j]); }
        stsm4(base + h * 1024 + (x0 ^ (c2 << 6)), y);
      }
    }
    stg_release(sb, b, lane);
  }
}

template <int BN>
__device__ __forceinline__ void h_swiglu(float* acc, uint32_t vb, uint32_t vp, uint32_t sb, uint32_t pm, uint32_t& st, uint32_t& ph, uint32_t g0, int wg, bool leader,
                                         int warp, int lane, uint32_t clk_q) {
  float rs[2], rh[2];
  mbar_wait(vb, vp);
  {
    const uint64_t da = mkdesc(H_SB + H_VEC + 4096 + wg * 1024, 0, 128, 0), db = mkdesc(H_SB + H_VEC, 1024, 0, 1);
    WG_FENCE();
    if (BN == 256) wg_ss256<0>(acc, da, db); else wg_ss128<0>(acc, da, db);
    WG_COMMIT();
  }
#pragma unroll
  for (int h = 0; h < 2; h++) { rs[h] = lds32f(sb + H_VEC + 6144 + (warp * 16 + h * 8 + (lane >> 2)) * 4); rh[h] = 0.5f * rs[h]; }
  WG_WAIT(1);
  h_release(sb, pm, st, ph, leader);
  WG_WAIT(0);
  reg_fence<BN / 2>(acc);
  HT(2);
  const uint32_t ro = ((warp & 3) * 16 + (lane & 7)) * 128, x0 = ((lane >> 3) ^ (lane & 7)) << 4;
#pragma unroll
  for (int uu = 0; uu < BN / 128; uu++) {
    uint32_t b;
    const uint32_t base = stg_acquire(sb, g0 + uu, b) + ro;
#pragma unroll
    for (int c2 = 0; c2 < 2; c2++) {
      const int c = 2 * uu + c2;
      uint32_t y[2][4];
#pragma unroll
      for (int j = 0; j < 4; j++) {
        const float* g = acc + 16 * c + 4 * j; const float* u = g + BN / 4;
        float o[4];
#pragma unroll
        for (int e = 0; e < 4; e++) {
          const float g2 = rh[e >> 1] * g[e];
          const float h = g2 * (rs[e >> 1] * u[e]);
          float t; asm("tanh.approx.f32 %0, %1;" : "=f"(t) : "f"(g2));
          o[e] = fmaf(h, t, h);
        }
        y[0][j] = pack2(o[0], o[1]); y[1][j] = pack2(o[2], o[3]);
      }
      stsm4(base + (x0 ^ (c2 << 6)), y[0]); stsm4(base + 1024 + (x0 ^ (c2 << 6)), y[1]);
    }
    stg_release(sb, b, lane);
  }
}

template <bool WS>
__device__ __forceinline__ void h_vecmat(uint32_t sb, int idx, uint32_t& st, uint32_t& ph, int tid, const __nv_bfloat16* cvec, uint8_t* w13s, uint8_t* bext,
                                         __nv_bfloat16* mod, __nv_bfloat16* gate) {
  const uint32_t stg = sb + H_STG, bars = sb + H_BAR;
  const int lane = tid & 31, warp = tid >> 5;
#pragma unroll
  for (int i = 0; i < 4; i++) {
    const int k = tid + 256 * i;
    if (WS) {
      const uint32_t s = __ldcg(reinterpret_cast<const uint16_t*>(mod) + 3 * D_ + k), c = __ldcg(reinterpret_cast<const uint16_t*>(mod) + 4 * D_ + k);
      sts32(stg + k * 4, s << 16); sts32(stg + 4096 + k * 4, c | c << 16);
    } else {
      const float c = __bfloat162float(cvec[k]);
      sts32(stg + k * 4, __float_as_uint(__bfloat162float(__float2bfloat16(c / (1.f + __expf(-c))))));
    }
  }
  bar_sync<1, 256>();
  float v[4][8], u[4][8];
#pragma unroll
  for (int b = 0; b < 4; b++)
#pragma unroll
    for (int e = 0; e < 8; e++) { v[b][e] = 0.f; u[b][e] = 0.f; }
  const int r0 = tid >> 3;
  const uint32_t off = 16384 + r0 * 128 + (((tid & 7) ^ (r0 & 7)) << 4);
  uint32_t prev = 0;
#pragma unroll 1
  for (int i = 0; i < (WS ? 16 : 8); i++) {
    mbar_wait(bars + HB_FULL + st * 8, ph);
    const uint32_t base = sb + st * H_STAGE + off;
#pragma unroll
    for (int ri = 0; ri < 2; ri++) {
      const uint32_t ka = stg + ((WS ? i * 64 : i * 128) + r0 + 32 * ri) * 4;
      const float m0 = lds32f(ka), m1 = WS ? m0 : lds32f(ka + 256);
      const uint32_t c2 = WS ? lds32(ka + 4096) : 0;
#pragma unroll
      for (int b = 0; b < 4; b++) {
        uint32_t w[4];
        lds128(w, base + b * 8192 + ri * 4096);
        const float m = b < 2 ? m0 : m1;
#pragma unroll
        for (int e = 0; e < 4; e++) {
          v[b][2 * e] = fmaf(m, bf_lo(w[e]), v[b][2 * e]); v[b][2 * e + 1] = fmaf(m, bf_hi(w[e]), v[b][2 * e + 1]);
          if (WS) { w[e] = hfma2(w[e], c2, w[e]); u[b][2 * e] += bf_lo(w[e]); u[b][2 * e + 1] += bf_hi(w[e]); }
        }
        if (WS) sts128(base + b * 8192 + ri * 4096, w[0], w[1], w[2], w[3]);
      }
    }
    if (WS) fence_async_smem();
    bar_sync<1, 256>();
    if (tid == 0) {
      if (WS) {
        bulk_s2g(w13s + (size_t)(idx * 16 + i) * 32768, sb + st * H_STAGE + 16384, 32768);
        bulk_commit();
        if (i > 0) { bulk_wait_read<1>(); mbar_arrive_n(bars + HB_EMPTY + prev * 8, 4); }
      } else mbar_arrive_n(bars + HB_EMPTY + st * 8, 4);
    }
    prev = st;
    if (++st == H_NST) { st = 0; ph ^= 1; }
  }
  if (WS && tid == 0) {
    bulk_wait_read<0>(); mbar_arrive_n(bars + HB_EMPTY + prev * 8, 4);
    bulk_wait_all(); fence_async_all(); fence_gpu();
  }
#pragma unroll
  for (int b = 0; b < 4; b++)
#pragma unroll
    for (int e = 0; e < 8; e++) {
      v[b][e] += __shfl_xor_sync(0xffffffffu, v[b][e], 8); v[b][e] += __shfl_xor_sync(0xffffffffu, v[b][e], 16);
      if (WS) { u[b][e] += __shfl_xor_sync(0xffffffffu, u[b][e], 8); u[b][e] += __shfl_xor_sync(0xffffffffu, u[b][e], 16); }
    }
  if (lane < 8) {
#pragma unroll
    for (int b = 0; b < 4; b++) {
      const uint32_t a = stg + warp * 2048 + b * 256 + lane * 32;
      sts128(a, __float_as_uint(v[b][0]), __float_as_uint(v[b][1]), __float_as_uint(v[b][2]), __float_as_uint(v[b][3]));
      sts128(a + 16, __float_as_uint(v[b][4]), __float_as_uint(v[b][5]), __float_as_uint(v[b][6]), __float_as_uint(v[b][7]));
      if (WS) {
        sts128(a + 1024, __float_as_uint(u[b][0]), __float_as_uint(u[b][1]), __float_as_uint(u[b][2]), __float_as_uint(u[b][3]));
        sts128(a + 1040, __float_as_uint(u[b][4]), __float_as_uint(u[b][5]), __float_as_uint(u[b][6]), __float_as_uint(u[b][7]));
      }
    }
  }
  bar_sync<1, 256>();
  float sv = 0.f, su = 0.f;
#pragma unroll
  for (int i = 0; i < 8; i++) {
    sv += lds32f(stg + i * 2048 + tid * 4);
    su += WS ? lds32f(stg + i * 2048 + 1024 + tid * 4) : lds32f(stg + i * 2048 + (tid ^ 128) * 4);
  }
  if (WS) {
    const __nv_bfloat16 uh = __float2bfloat16(su), ul = __float2bfloat16(su - __bfloat162float(uh));
    const __nv_bfloat16 vh = __float2bfloat16(sv), vl = __float2bfloat16(sv - __bfloat162float(vh)), z = __float2bfloat16(0.f);
    uint8_t* p = bext + idx * 4096 + (tid >> 6) * 1024 + (tid & 7) * 2;
#pragma unroll
    for (int r = 0; r < 8; r++)
      *reinterpret_cast<__nv_bfloat16*>(p + r * 128 + ((((tid & 63) >> 3) ^ r) << 4)) = r == 0 || r == 2 ? uh : r == 1 ? ul : r == 3 || r == 5 ? vh : r == 4 ? vl : z;
  } else if (tid < 128) {
    const int n = idx * 128 + tid, vec = n >> 10, col = n & 1023;
    const __nv_bfloat16 r = __float2bfloat16(sv + su);
    mod[2048 + n] = r;
    if (vec == 0 || vec == 3) gate[(vec ? D_ : 0) + (col & ~31) + ((col >> 1) & 3) * 8 + ((col >> 3) & 3) * 2 + (col & 1)] = r;
  }
}

__global__ void __launch_bounds__(384, 1)
kernel_H(const __grid_constant__ CUtensorMap tmo, const __grid_constant__ CUtensorMap tm1, const __grid_constant__ CUtensorMap tm3,
         const __grid_constant__ CUtensorMap tm2, const __grid_constant__ CUtensorMap tmm, const __grid_constant__ CUtensorMap tmx,
         const __grid_constant__ CUtensorMap tmy, const __nv_bfloat16* __restrict__ x, const __nv_bfloat16* __restrict__ cvec, __nv_bfloat16* out, const __grid_constant__ HList list) {
  extern __shared__ __align__(1024) uint8_t smem[];
  uint32_t rank, pair;
  asm("mov.u32 %0, %%cluster_ctarank;" : "=r"(rank)); asm("mov.u32 %0, %%cluster_nctarank;" : "=r"(pair));
  rank = __shfl_sync(0xffffffffu, rank, 0); pair = __shfl_sync(0xffffffffu, pair, 0) - 1;
  const uint32_t sb = H_SB + (rank << 24), bars = sb + H_BAR, pm = pair << 24;
  const int tid = threadIdx.x, lane = tid & 31;
  const int warp = __shfl_sync(0xffffffffu, tid >> 5, 0);
  if (tid == 0) {
    if ((smem_u32(smem) & 0xffffff) != H_SB) __trap();
    for (int i = 0; i < H_NST; i++) { mbar_init(bars + HB_FULL + i * 8, 1); mbar_init(bars + HB_EMPTY + i * 8, 4); }
    for (int i = 0; i < 2; i++) { mbar_init(bars + HB_IFULL + i * 8, 1); mbar_init(bars + HB_IEMPTY + i * 8, 1); mbar_init(bars + HB_VFULL + i * 8, 1);
      mbar_init(bars + HB_MFULL + i * 8, 1); mbar_init(bars + HB_MEMPTY + i * 8, 1); }
    for (int i = 0; i < 3; i++) { mbar_init(bars + HB_SRDY + i * 8, 4); mbar_init(bars + HB_SFREE + i * 8, 1); }
    mbar_init(bars + HB_STGF, 1);
    asm volatile("fence.mbarrier_init.release.cluster;" ::: "memory");
    fence_async_smem();
  }
  __syncthreads();
  cluster_sync();
  asm volatile("griddepcontrol.launch_dependents;");
  if (warp >= 8) {
    asm volatile("setmaxnreg.dec.sync.aligned.u32 56;");
    if (warp == 8) {
      uint32_t st = 0, ph = 1, nv = 0, q = 0;
      uint32_t* const head = &g_flags[list.head];
      const bool claimer = lane == 0 && rank == 0;
      if (claimer) q = atomicAdd(head, 1);
#pragma unroll 1
      for (uint32_t n = 0;; n++) {
        if (pair) {
          const uint32_t o = (n & 1) * 8, p = (n >> 1) & 1;
          if (rank == 0) {
            mbar_wait(bars + HB_MEMPTY + o, p ^ 1);
            if (lane == 0) st_async1((bars + HB_MAIL + o) ^ pm, q, (bars + HB_MFULL + o) ^ pm);
          } else {
            if (lane == 0) mbar_expect(bars + HB_MFULL + o, 4);
            mbar_wait(bars + HB_MFULL + o, p);
            q = lds32(bars + HB_MAIL + o);
            __syncwarp();
            if (lane == 0) mbar_arrive_cl((bars + HB_MEMPTY + o) ^ pm);
          }
        }
        q = __shfl_sync(0xffffffffu, q, 0);
        uint32_t it = q < list.n ? list.it[q] : 0;
        const bool shA = pair && !(it >> 28 & 1), shB = pair && (it >> 28 & 1);
        if (rank && it) it += shA ? 1 << 7 : (it >> 29) << 3;
        const int type = it & 7, mt = (it >> 3) & 15, idx = (it >> 7) & 63, sz = (it >> 13) & 3, kb0 = (it >> 15) & 63, nkb = (it >> 21) & 127;
        {
          int f = FL_GO; uint32_t target = 0;
          if (type == IT_OUT) { f = lane == 0 ? FL_ATT + 8 * mt : lane == 1 ? FL_XT + 8 * mt : FL_MOD; target = lane == 0 ? 64 : lane == 1 ? N_XT : N_MOD; }
          else if (type == IT_F1) { f = lane == 0 ? FL_OUT + 8 * mt : FL_WS; target = lane == 0 ? 1024 : N_WS; }
          else if (type == IT_F2) { f = FL_F1 + 8 * mt; target = 56; }
          else if (type == IT_STAT) { f = FL_OUT + 8 * mt; target = 1024; }
          else if (type == IT_WS) { f = FL_MOD; target = N_MOD; }
          else if (type != IT_END) target = 1;
          if (lane < 3) wait_flag(&g_flags[f], target);
          __syncwarp();
          asm volatile("fence.proxy.async.global;" ::: "memory");
        }
        mbar_wait(bars + HB_IEMPTY + (n & 1) * 8, ((n >> 1) & 1) ^ 1);
        if (elect_one()) {
          sts32(bars + HB_ITEM + (n & 1) * 4, it);
          mbar_arrive(bars + HB_IFULL + (n & 1) * 8);
        }
        if (type == IT_END) break;
        const bool gemm = type == IT_OUT || type == IT_F1 || type == IT_F2;
        const int nst = gemm ? nkb : type == IT_WS ? 16 : type == IT_MOD ? 8 : 0;
        const int bn = 256 >> sz;
        const uint8_t* ap = type == IT_OUT ? g_att + (size_t)mt * 64 * 16384 : g_act + (size_t)mt * 56 * 16384;
        const uint8_t* wp = g_w13s + (size_t)(idx >> sz) * 16 * 32768 + (sz ? (idx & 1) * 8192 : 0);
        const CUtensorMap* tb = type == IT_OUT ? &tmo : type == IT_F2 ? &tm2 : type == IT_WS ? &tm1 : &tmm;
        const CUtensorMap* tc = type == IT_WS ? &tm3 : tb;
        const int c0 = gemm ? idx * bn : type == IT_WS ? idx * 128 : 2048 + idx * 128, dcol = gemm ? 128 : 0, kmul = type == IT_MOD ? 128 : 64, drow = type == IT_MOD ? 64 : 0;
        const uint32_t bytes = gemm ? 16384 + bn * 128 : 32768;
        const uint64_t pa = type == IT_OUT ? POL_ATT : POL_ACT, pb = type == IT_OUT ? POL_WO : type == IT_F2 ? POL_W2 : POL_PRE;
        if (nst < 2 && claimer) q = atomicAdd(head, 1);
#pragma unroll 1
        for (int i = 0; i < nst; i++) {
          const int kb = kb0 + i;
          const uint32_t d = sb + st * H_STAGE, fb = bars + HB_FULL + st * 8;
          if (i == nst - 2 && claimer) q = atomicAdd(head, 1);
          mbar_wait(bars + HB_EMPTY + st * 8, ph);
          if (elect_one()) {
            mbar_expect(fb, bytes);
            if (type == IT_F1) {
              if (shA) tma2d_mc(d + rank * 8192, &tmy, kb * 64, mt * 128 + rank * 64, fb, L2_NORMAL); else tma2d(d, &tmx, kb * 64, mt * 128, fb);
              if (shB) bulk_mc(d + 16384 + rank * (16384 >> sz), wp + (size_t)kb * 32768 + rank * 16384, 16384 >> sz, fb, L2_NORMAL);
              else if (sz == 0) bulk_g2s(d + 16384, wp + (size_t)kb * 32768, 32768, fb);
              else { bulk_g2s(d + 16384, wp + (size_t)kb * 32768, 8192, fb); bulk_g2s(d + 24576, wp + (size_t)kb * 32768 + 16384, 8192, fb); }
            } else {
              if (shA) bulk_mc(d + rank * 8192, ap + (size_t)kb * 16384 + rank * 8192, 8192, fb, pa);
              else if (gemm) bulk_g2s_p(d, ap + (size_t)kb * 16384, 16384, fb, pa);
              if (shB) {
                if (sz == 0) {
                  tma2d_mc(d + 16384 + rank * 16384, tb, c0 + rank * 128, kb * 64, fb, pb);
                  tma2d_mc(d + 24576 + rank * 16384, tb, c0 + rank * 128 + 64, kb * 64, fb, pb);
                } else tma2d_mc(d + 16384 + rank * 8192, tb, c0 + rank * 64, kb * 64, fb, pb);
              } else {
                tma2d_p(d + 16384, tb, c0, kb * kmul, fb, pb);
                tma2d_p(d + 24576, tb, c0 + 64, kb * kmul, fb, pb);
                if (sz == 0) { tma2d_p(d + 32768, tc, c0 + dcol, kb * kmul + drow, fb, pb); tma2d_p(d + 40960, tc, c0 + dcol + 64, kb * kmul + drow, fb, pb); }
              }
            }
          }
          if (++st == H_NST) { st = 0; ph ^= 1; }
        }
        if (gemm) {
          if (type == IT_F1) {
            if (lane == 0) wait_flag(&g_flags[FL_STAT + 8 * mt], N_STAT);
            __syncwarp();
            asm volatile("fence.proxy.async.global;" ::: "memory");
          }
          if (elect_one()) {
            const uint32_t v = sb + H_VEC, fb = bars + HB_VFULL + (nv & 1) * 8;
            if (type == IT_F1) {
              mbar_expect(fb, (4096 >> sz) + 2560);
              if (sz == 0) bulk_g2s(v, g_bext + idx * 4096, 4096, fb);
              else { const uint8_t* p = g_bext + (idx >> 1) * 4096 + (idx & 1) * 1024; bulk_g2s(v, p, 1024, fb); bulk_g2s(v + 1024, p + 2048, 1024, fb); }
              bulk_g2s(v + 4096, g_ext + mt * 2560, 2560, fb);
            } else {
              mbar_expect(fb, bn * 2);
              bulk_g2s(sb + H_GATE + (nv & 1) * 512, g_gate + (type == IT_F2 ? D_ : 0) + c0, bn * 2, fb);
            }
          }
          nv++;
        }
      }
    } else if (warp == 9) {
      uint32_t g = 0;
#pragma unroll 1
      for (uint32_t n = 0;; n++) {
        mbar_wait(bars + HB_IFULL + (n & 1) * 8, (n >> 1) & 1);
        const uint32_t it = lds32(bars + HB_ITEM + (n & 1) * 4);
        const int type = it & 7, mt = (it >> 3) & 15, idx = (it >> 7) & 63, sz = (it >> 13) & 3, nkb = (it >> 21) & 127;
        if (type == IT_END) break;
        const bool gated = type == IT_OUT || type == IT_F2, gemm = gated || type == IT_F1;
        if (!gemm) { if (n & 1) bar_sync<3, 288>(); else bar_sync<2, 288>(); }
        if (lane == 0) {
          if (gemm) {
            const int nu = (gated ? 4 : 2) >> sz;
            uint32_t pb = 0;
#pragma unroll 1
            for (int u = 0; u < 2 * nu; u++, g++) {
              const uint32_t r = (g * 43691u) >> 17, b = g - 3 * r, src = sb + H_STG + b * 8192;
              const int w = u >= nu, uu = u - w * nu;
              mbar_wait(bars + HB_SRDY + b * 8, r & 1);
              if (u == 2 * nu - 1) mbar_arrive(bars + HB_IEMPTY + (n & 1) * 8);
              fence_async_smem();
              if (gated) tma2d_add(&tmy, idx * (256 >> sz) + uu * 64, mt * 128 + w * 64, src);
              else bulk_s2g(g_act + (size_t)(mt * 56 + idx * nu + uu) * 16384 + w * 8192, src, 8192);
              bulk_commit();
              if (u > 0) { bulk_wait_read<1>(); mbar_arrive(bars + HB_SFREE + pb * 8); }
              pb = b;
            }
            bulk_wait_read<0>();
            mbar_arrive(bars + HB_SFREE + pb * 8);
            mbar_arrive(bars + HB_STGF);
            bulk_wait_all(); fence_async_all();
          } else {
            mbar_arrive(bars + HB_STGF);
            mbar_arrive(bars + HB_IEMPTY + (n & 1) * 8);
          }
          if (type != IT_F2) {
            const uint32_t inc = type == IT_OUT ? (4 >> sz) * nkb : type == IT_F1 ? 2 >> sz : 1;
            fence_gpu();
            red_add_u32(&g_flags[type == IT_MOD ? FL_MOD : type == IT_WS ? FL_WS :
                                 (type == IT_XT ? FL_XT : type == IT_OUT ? FL_OUT : type == IT_STAT ? FL_STAT : FL_F1) + 8 * mt], inc);
          }
        }
        __syncwarp();
      }
      if (!pair) asm volatile("griddepcontrol.wait;" ::: "memory");
      uint32_t k = 0;
      if (lane == 0) { fence_gpu(); k = atomicAdd(&g_flags[FL_EXIT], 1); }
      k = __shfl_sync(0xffffffffu, k, 0);
      if (k == NH1 + NH2 - 1) {
        fence_gpu();
        for (int i = lane; i < 1024; i += 32) g_flags[i] = 0;
      }
    }
  } else {
    asm volatile("setmaxnreg.inc.sync.aligned.u32 224;");
    const int wg = warp >> 2;
    const bool leader = (tid & 127) == 0;
    uint32_t st = 0, ph = 0, nv = 0, g = 0;
#pragma unroll 1
    for (uint32_t n = 0;; n++) {
      mbar_wait(bars + HB_IFULL + (n & 1) * 8, (n >> 1) & 1);
      const uint32_t it = __shfl_sync(0xffffffffu, lds32(bars + HB_ITEM + (n & 1) * 4), 0);
      const int type = it & 7, mt = (it >> 3) & 15, idx = (it >> 7) & 63, sz = (it >> 13) & 3, nkb = (it >> 21) & 127;
      if (type == IT_END) break;
      constexpr uint32_t clk_q = 0;
      if (type == IT_OUT || type == IT_F1 || type == IT_F2) {
        const uint32_t va = sb + H_GATE + (nv & 1) * 512, vb = bars + HB_VFULL + (nv & 1) * 8, vp = (nv >> 1) & 1;
        const uint32_t nu = (type == IT_F1 ? 2 : 4) >> sz, g0 = g + wg * nu;
        nv++; g += 2 * nu;
        if (sz == 0) {
          float acc[128];
          if (type == IT_OUT) h_mainloop<256, 1>(acc, sb, pm, nkb, st, ph, wg, leader, clk_q);
          else h_mainloop<256, 0>(acc, sb, pm, nkb, st, ph, wg, leader, clk_q);
          if (type == IT_F1) h_swiglu<256>(acc, vb, vp, sb, pm, st, ph, g0, wg, leader, warp, lane, clk_q);
          else h_gated<256>(acc, va, vb, vp, sb, pm, st, ph, g0, wg, leader, warp, lane, clk_q);
        } else {
          float acc[64];
          if (type == IT_OUT) h_mainloop<128, 1>(acc, sb, pm, nkb, st, ph, wg, leader, clk_q);
          else h_mainloop<128, 0>(acc, sb, pm, nkb, st, ph, wg, leader, clk_q);
          if (type == IT_F1) h_swiglu<128>(acc, vb, vp, sb, pm, st, ph, g0, wg, leader, warp, lane, clk_q);
          else h_gated<128>(acc, va, vb, vp, sb, pm, st, ph, g0, wg, leader, warp, lane, clk_q);
        }
        HT(3);
        continue;
      } else if (type == IT_XT) {
        const uint4* xp = reinterpret_cast<const uint4*>(x + (size_t)(mt * 128 + idx * 64) * D_) + tid;
        uint4* op = reinterpret_cast<uint4*>(out + (size_t)(mt * 128 + idx * 64) * D_) + tid;
#pragma unroll 1
        for (int b = 0; b < 2; b++) {
          uint4 v[16];
#pragma unroll
          for (int i = 0; i < 16; i++) v[i] = __ldcs(xp + (b * 16 + i) * 256);
#pragma unroll
          for (int i = 0; i < 16; i++) op[(b * 16 + i) * 256] = v[i];
        }
      } else if (type == IT_STAT) {
        const int row0 = mt * 128 + idx * 32 + warp * 4;
        const uint4* xp = reinterpret_cast<const uint4*>(out + (size_t)row0 * D_) + lane;
        uint4 v[16];
#pragma unroll
        for (int i = 0; i < 16; i++) v[i] = __ldcg(xp + (i >> 2) * 128 + (i & 3) * 32);
        float s[4], m[4];
#pragma unroll
        for (int r = 0; r < 4; r++) {
          s[r] = 0.f;
#pragma unroll
          for (int i = 0; i < 4; i++) {
            const uint4 w = v[4 * r + i];
            s[r] += ((bf_lo(w.x) + bf_hi(w.x)) + (bf_lo(w.y) + bf_hi(w.y))) + ((bf_lo(w.z) + bf_hi(w.z)) + (bf_lo(w.w) + bf_hi(w.w)));
          }
        }
#pragma unroll
        for (int o = 1; o < 32; o <<= 1)
#pragma unroll
          for (int r = 0; r < 4; r++) s[r] += __shfl_xor_sync(0xffffffffu, s[r], o);
#pragma unroll
        for (int r = 0; r < 4; r++) {
          m[r] = s[r] * (1.f / D_);
          float a = 0.f, b = 0.f;
#pragma unroll
          for (int i = 0; i < 4; i++) {
            const uint4 w = v[4 * r + i];
            const uint32_t ww[4] = {w.x, w.y, w.z, w.w};
#pragma unroll
            for (int e = 0; e < 4; e++) { const float p = bf_lo(ww[e]) - m[r], t = bf_hi(ww[e]) - m[r]; a = fmaf(p, p, a); b = fmaf(t, t, b); }
          }
          s[r] = a + b;
        }
#pragma unroll
        for (int o = 1; o < 32; o <<= 1)
#pragma unroll
          for (int r = 0; r < 4; r++) s[r] += __shfl_xor_sync(0xffffffffu, s[r], o);
        if (lane < 4) {
          const float sr = lane == 0 ? s[0] : lane == 1 ? s[1] : lane == 2 ? s[2] : s[3], mr = lane == 0 ? m[0] : lane == 1 ? m[1] : lane == 2 ? m[2] : m[3];
          const float var = sr * (1.f / D_) + 1e-5f, rs = rsqrtf(var);
          const float a = -0.5f * mr, b = 0.5f * var * rs;
          const float ah = __bfloat162float(__float2bfloat16(a)), bh = __bfloat162float(__float2bfloat16(b));
          const int r = (row0 & 127) + lane;
          *reinterpret_cast<uint4*>(g_ext + mt * 2560 + r * 16) = make_uint4(pack2(ah, ah), pack2(a - ah, bh), pack2(bh, b - bh), 0u);
          *reinterpret_cast<float*>(g_ext + mt * 2560 + 2048 + r * 4) = rs;
        }
      } else {
        mbar_wait(bars + HB_STGF, (n & 1) ^ 1);
        if (type == IT_WS) h_vecmat<true>(sb, idx, st, ph, tid, cvec, g_w13s, g_bext, g_mod, g_gate);
        else h_vecmat<false>(sb, idx, st, ph, tid, cvec, g_w13s, g_bext, g_mod, g_gate);
      }
      HT(3);
      if (n & 1) bar_arrive<3, 288>(); else bar_arrive<2, 288>();
    }
  }
  cluster_sync();
}

const uint32_t h_items1[] = {
  0x1, 0x81, 0x101, 0x181, 0x201, 0x281, 0x301, 0x381, 0x401, 0x481, 0x501, 0x581, 0x601, 0x681,
  0x701, 0x781, 0x801, 0x881, 0x901, 0x981, 0xa01, 0xa81, 0xb01, 0xb81, 0xc01, 0xc81, 0xd01, 0xd81,
  0xe01, 0xe81, 0xf01, 0xf81, 0x2, 0x82, 0xa, 0x8a, 0x12, 0x92, 0x1a, 0x9a, 0x22, 0xa2,
  0x2a, 0xaa, 0x4, 0x84, 0x104, 0x184, 0x32, 0xb2, 0x3a, 0xba, 0x42, 0xc2, 0x4a, 0xca,
  0x52, 0xd2, 0x5a, 0xda, 0x62, 0xe2, 0x6a, 0xea, 0x72, 0xf2, 0x7a, 0xfa, 0x204, 0x284,
  0x304, 0x384, 0x404, 0x484, 0x504, 0x584, 0x604, 0x684, 0x704, 0x784, 0x804, 0x884, 0x904, 0x984,
  0xa04, 0xa84, 0xb04, 0xb84, 0xc04, 0xc84, 0xd04, 0xd84, 0x1000003, 0x1000083, 0x1000103, 0x1000183, 0x1040003, 0x1040083,
  0x1040103, 0x1040183, 0x1080003, 0x1080083, 0x1080103, 0x1080183, 0x10c0003, 0x10c0083, 0x10c0103, 0x10c0183, 0x1100003, 0x1100083, 0x1100103, 0x1100183,
  0x1140003, 0x1140083, 0x1140103, 0x1140183, 0x1180003, 0x1180083, 0x1180103, 0x1180183, 0x11c0003, 0x11c0083, 0x11c0103, 0x11c0183, 0x200000b, 0x200008b,
  0x200010b, 0x200018b, 0x208000b, 0x208008b, 0x208010b, 0x208018b, 0x210000b, 0x210008b, 0x210010b, 0x210018b, 0x218000b, 0x218008b, 0x218010b, 0x218018b,
  0x7, 0x87, 0x107, 0x187, 0x2000005, 0x2000085, 0x2000105, 0x2000185, 0x2000205, 0x2000285, 0x2000305, 0x2000385, 0x2000405, 0x2000485,
  0x2000505, 0x2000585, 0x2000605, 0x2000685, 0x2000705, 0x2000785, 0x2000805, 0x2000885, 0x2000905, 0x2000985, 0x2000a05, 0x2000a85, 0x2000b05, 0x2000b85,
  0x2000c05, 0x2000c85, 0x2000d05, 0x2000d85, 0x4000013, 0x4000093, 0x4000113, 0x4000193, 0x4100013, 0x4100093, 0x4100113, 0x4100193, 0xf, 0x8f,
  0x10f, 0x18f, 0x200000d, 0x200008d, 0x200010d, 0x200018d, 0x200020d, 0x200028d, 0x200030d, 0x200038d, 0x200040d, 0x200048d, 0x200050d, 0x200058d,
  0x200060d, 0x200068d, 0x200070d, 0x200078d, 0x200080d, 0x200088d, 0x200090d, 0x200098d, 0x2000a0d, 0x2000a8d, 0x2000b0d, 0x2000b8d, 0x2000c0d, 0x2000c8d,
  0x2000d0d, 0x2000d8d, 0x3800006, 0x3800086, 0x3800106, 0x3800186, 0x38e0006, 0x38e0086, 0x38e0106, 0x38e0186, 0x400001b, 0x400009b, 0x400011b, 0x400019b,
  0x410001b, 0x410009b, 0x410011b, 0x410019b, 0x380000e, 0x380008e, 0x380010e, 0x380018e, 0x38e000e, 0x38e008e, 0x38e010e, 0x38e018e, 0x17, 0x97,
  0x117, 0x197, 0x2000015, 0x2000095, 0x2000115, 0x2000195, 0x2000215, 0x2000295, 0x2000315, 0x2000395, 0x2000415, 0x2000495, 0x2000515, 0x2000595,
  0x4000023, 0x40000a3, 0x4000123, 0x40001a3, 0x4100023, 0x41000a3, 0x4100123, 0x41001a3, 0x2000615, 0x2000695, 0x2000715, 0x2000795, 0x2000815, 0x2000895,
  0x2000915, 0x2000995, 0x2000a15, 0x2000a95, 0x2000b15, 0x2000b95, 0x2000c15, 0x2000c95, 0x2000d15, 0x2000d95, 0x1f, 0x9f, 0x11f, 0x19f,
  0x200001d, 0x200009d, 0x200011d, 0x200019d, 0x200021d, 0x200029d, 0x200031d, 0x200039d, 0x200041d, 0x200049d, 0x200051d, 0x200059d, 0x400002b, 0x40000ab,
  0x400012b, 0x40001ab, 0x410002b, 0x41000ab, 0x410012b, 0x41001ab, 0x200061d, 0x200069d, 0x200071d, 0x200079d, 0x200081d, 0x200089d, 0x200091d, 0x200099d,
  0x2000a1d, 0x2000a9d, 0x2000b1d, 0x2000b9d, 0x2000c1d, 0x2000c9d, 0x2000d1d, 0x2000d9d, 0x27, 0xa7, 0x127, 0x1a7, 0x2000025, 0x20000a5,
  0x2000125, 0x20001a5, 0x2000225, 0x20002a5, 0x2000325, 0x20003a5, 0x4000033, 0x40000b3, 0x4000133, 0x40001b3, 0x4100033, 0x41000b3, 0x4100133, 0x41001b3,
  0x2000425, 0x20004a5, 0x2000525, 0x20005a5, 0x2000625, 0x20006a5, 0x2000725, 0x20007a5, 0x2000825, 0x20008a5, 0x2000925, 0x20009a5, 0x2000a25, 0x2000aa5,
  0x2000b25, 0x2000ba5, 0x2000c25, 0x2000ca5, 0x2000d25, 0x2000da5, 0x2f, 0xaf, 0x12f, 0x1af, 0x200002d, 0x20000ad, 0x200012d, 0x20001ad,
  0x200022d, 0x20002ad, 0x200032d, 0x20003ad, 0x400003b, 0x40000bb, 0x400013b, 0x40001bb, 0x410003b, 0x41000bb, 0x410013b, 0x41001bb, 0x200042d, 0x20004ad,
  0x200052d, 0x20005ad, 0x200062d, 0x20006ad, 0x200072d, 0x20007ad, 0x200082d, 0x20008ad, 0x200092d, 0x20009ad, 0x2000a2d, 0x2000aad, 0x2000b2d, 0x2000bad,
  0x2000c2d, 0x2000cad, 0x2000d2d, 0x2000dad, 0x37, 0xb7, 0x137, 0x1b7, 0x2000035, 0x20000b5, 0x2000135, 0x20001b5, 0x2000235, 0x20002b5,
  0x2000335, 0x20003b5, 0x2000435, 0x20004b5, 0x2000535, 0x20005b5, 0x4000043, 0x40000c3, 0x4000143, 0x40001c3, 0x4100043, 0x41000c3, 0x4100143, 0x41001c3,
  0x2000635, 0x20006b5, 0x2000735, 0x20007b5, 0x2000835, 0x20008b5, 0x2000935, 0x20009b5, 0x2000a35, 0x2000ab5, 0x2000b35, 0x2000bb5, 0x2000c35, 0x2000cb5,
  0x2000d35, 0x2000db5, 0x3f, 0xbf, 0x13f, 0x1bf, 0x200003d, 0x20000bd, 0x200013d, 0x20001bd, 0x200023d, 0x20002bd, 0x200033d, 0x20003bd,
  0x400004b, 0x40000cb, 0x400014b, 0x40001cb, 0x410004b, 0x41000cb, 0x410014b, 0x41001cb, 0x200043d, 0x20004bd, 0x200053d, 0x20005bd, 0x200063d, 0x20006bd,
  0x200073d, 0x20007bd, 0x200083d, 0x20008bd, 0x200093d, 0x20009bd, 0x2000a3d, 0x2000abd, 0x2000b3d, 0x2000bbd, 0x2000c3d, 0x2000cbd, 0x2000d3d, 0x2000dbd,
  0x47, 0xc7, 0x147, 0x1c7, 0x2000045, 0x20000c5, 0x2000145, 0x20001c5, 0x2000245, 0x20002c5, 0x2000345, 0x20003c5, 0x4000053, 0x40000d3,
  0x4000153, 0x40001d3, 0x4100053, 0x41000d3, 0x4100153, 0x41001d3, 0x2000445, 0x20004c5, 0x2000545, 0x20005c5, 0x2000645, 0x20006c5, 0x2000745, 0x20007c5,
  0x2000845, 0x20008c5, 0x2000945, 0x20009c5, 0x2000a45, 0x2000ac5, 0x2000b45, 0x2000bc5, 0x2000c45, 0x2000cc5, 0x2000d45, 0x2000dc5, 0x4f, 0xcf,
  0x14f, 0x1cf, 0x200004d, 0x20000cd, 0x200014d, 0x20001cd, 0x200024d, 0x20002cd, 0x200034d, 0x20003cd, 0x200044d, 0x20004cd, 0x200054d, 0x20005cd,
  0x400005b, 0x40000db, 0x400015b, 0x40001db, 0x410005b, 0x41000db, 0x410015b, 0x41001db, 0x200064d, 0x20006cd, 0x200074d, 0x20007cd, 0x200084d, 0x20008cd,
  0x200094d, 0x20009cd, 0x2000a4d, 0x2000acd, 0x2000b4d, 0x2000bcd, 0x2000c4d, 0x2000ccd, 0x2000d4d, 0x2000dcd, 0x57, 0xd7, 0x157, 0x1d7,
  0x2000055, 0x20000d5, 0x2000155, 0x20001d5, 0x2000255, 0x20002d5, 0x2000355, 0x20003d5, 0x4000063, 0x40000e3, 0x4000163, 0x40001e3, 0x4100063, 0x41000e3,
  0x4100163, 0x41001e3, 0x2000455, 0x20004d5, 0x2000555, 0x20005d5, 0x2000655, 0x20006d5, 0x2000755, 0x20007d5, 0x2000855, 0x20008d5, 0x2000955, 0x20009d5,
  0x2000a55, 0x2000ad5, 0x2000b55, 0x2000bd5, 0x2000c55, 0x2000cd5, 0x2000d55, 0x2000dd5, 0x5f, 0xdf, 0x15f, 0x1df, 0x200005d, 0x20000dd,
  0x200015d, 0x20001dd, 0x200025d, 0x20002dd, 0x200035d, 0x20003dd, 0x200006b, 0x20000eb, 0x200016b, 0x20001eb, 0x208006b, 0x20800eb, 0x208016b, 0x20801eb,
  0x210006b, 0x21000eb, 0x210016b, 0x21001eb, 0x218006b, 0x21800eb, 0x218016b, 0x21801eb, 0x200045d, 0x20004dd, 0x200055d, 0x20005dd, 0x200065d, 0x20006dd,
  0x200075d, 0x20007dd, 0x200085d, 0x20008dd, 0x200095d, 0x20009dd, 0x2000a5d, 0x2000add, 0x2000b5d, 0x2000bdd, 0x2000c5d, 0x2000cdd, 0x2000d5d, 0x2000ddd,
  0x67, 0xe7, 0x167, 0x1e7, 0x2000065, 0x20000e5, 0x2000165, 0x20001e5, 0x2000265, 0x20002e5, 0x2000365, 0x20003e5, 0x2000465, 0x20004e5,
  0x2000565, 0x20005e5, 0x2000073, 0x20000f3, 0x2000173, 0x20001f3, 0x2080073, 0x20800f3, 0x2080173, 0x20801f3, 0x2100073, 0x21000f3, 0x2100173, 0x21001f3,
  0x2180073, 0x21800f3, 0x2180173, 0x21801f3, 0x6f, 0xef, 0x16f, 0x1ef, 0x2000665, 0x20006e5, 0x2000765, 0x20007e5, 0x2000865, 0x20008e5,
  0x2000965, 0x20009e5, 0x2000a65, 0x2000ae5, 0x2000b65, 0x2000be5, 0x2000c65, 0x2000ce5, 0x2000d65, 0x2000de5, 0x200006d, 0x20000ed, 0x200016d, 0x20001ed,
  0x200026d, 0x20002ed, 0x200036d, 0x20003ed, 0x200046d, 0x20004ed, 0x200056d, 0x20005ed, 0x200066d, 0x20006ed, 0x200076d, 0x20007ed, 0x200086d, 0x20008ed,
  0x200096d, 0x20009ed, 0x2000a6d, 0x2000aed, 0x2000b6d, 0x2000bed, 0x77, 0xf7, 0x177, 0x1f7, 0x2000c6d, 0x2000ced, 0x2000d6d, 0x2000ded,
  0x2000075, 0x20000f5, 0x2000175, 0x20001f5, 0x2000275, 0x20002f5, 0x2000375, 0x20003f5, 0x2000475, 0x20004f5, 0x2000575, 0x20005f5, 0x2000675, 0x20006f5,
  0x2000775, 0x20007f5, 0x2000875, 0x20008f5, 0x2000975, 0x20009f5, 0x2000a75, 0x2000af5, 0x2000b75, 0x2000bf5, 0x2000c75, 0x2000cf5, 0x2000d75, 0x2000df5,
  0x1c0006e, 0x1c000ee, 0x1c0016e, 0x1c001ee, 0x1c7006e, 0x1c700ee, 0x1c7016e, 0x1c701ee, 0x1ce006e, 0x1ce00ee, 0x1ce016e, 0x1ce01ee, 0x1d5006e, 0x1d500ee,
  0x1d5016e, 0x1d501ee, 0x1c00076, 0x1c000f6, 0x1c00176, 0x1c001f6, 0x1c70076, 0x1c700f6, 0x1c70176, 0x1c701f6, 0x1ce0076, 0x1ce00f6, 0x1ce0176, 0x1ce01f6,
  0x1d50076, 0x1d500f6, 0x1d50176, 0x1d501f6,
};
const uint32_t h_items2[] = {
  0x100207b, 0x100217b, 0x100227b, 0x100237b, 0x104207b, 0x104217b, 0x104227b, 0x104237b, 0x108207b, 0x108217b, 0x108227b, 0x108237b, 0x10c207b, 0x10c217b,
  0x10c227b, 0x10c237b, 0x110207b, 0x110217b, 0x110227b, 0x110237b, 0x114207b, 0x114217b, 0x114227b, 0x114237b, 0x118207b, 0x118217b, 0x118227b, 0x118237b,
  0x11c207b, 0x11c217b, 0x11c227b, 0x11c237b, 0x31c00016, 0x31c00096, 0x31c00116, 0x31c00196, 0x31c70016, 0x31c70096, 0x31c70116, 0x31c70196, 0x31ce0016, 0x31ce0096,
  0x31ce0116, 0x31ce0196, 0x31d50016, 0x31d50096, 0x31d50116, 0x7f, 0x17f, 0x31d50196, 0x31c00026, 0x31c000a6, 0x31c00126, 0x31c001a6, 0x31c70026, 0x31c700a6,
  0x31c70126, 0x31c701a6, 0x31ce0026, 0x31ce00a6, 0x31ce0126, 0x31ce01a6, 0x31d50026, 0x31d500a6, 0x31d50126, 0x31d501a6, 0x31c00036, 0x31c000b6, 0x31c00136, 0x31c001b6,
  0x31c70036, 0x31c700b6, 0x31c70136, 0x31c701b6, 0x31ce0036, 0x31ce00b6, 0x31ce0136, 0x31ce01b6, 0x31d50036, 0x200207d, 0x200217d, 0x200227d, 0x200237d, 0x200247d,
  0x200257d, 0x200267d, 0x200277d, 0x200287d, 0x200297d, 0x2002a7d, 0x2002b7d, 0x2002c7d, 0x2002d7d, 0x2002e7d, 0x2002f7d, 0x200307d, 0x200317d, 0x200327d,
  0x200337d, 0x200347d, 0x200357d, 0x200367d, 0x200377d, 0x200387d, 0x200397d, 0x2003a7d, 0x2003b7d, 0x31d500b6, 0x31d50136, 0x31d501b6, 0x31c00046, 0x31c000c6,
  0x31c00146, 0x31c001c6, 0x31c70046, 0x31c700c6, 0x31c70146, 0x31c701c6, 0x31ce0046, 0x31ce00c6, 0x31ce0146, 0x31ce01c6, 0x31d50046, 0x31d500c6, 0x31d50146, 0x31d501c6,
  0x31c00056, 0x31c000d6, 0x31c00156, 0x31c001d6, 0x31c70056, 0x31c700d6, 0x31c70156, 0x31c701d6, 0x31ce0056, 0x31ce00d6, 0x31ce0156, 0x31ce01d6, 0x31d50056, 0x31d500d6,
  0x31d50156, 0x31d501d6, 0x1c00066, 0x1c00166, 0x1c70066, 0x1c70166, 0x1ce0066, 0x1ce0166, 0x1d50066, 0x1d50166, 0xe0207e, 0xe0217e, 0xe0227e, 0xe0237e,
  0xe3a07e, 0xe3a17e, 0xe3a27e, 0xe3a37e, 0xe7207e, 0xe7217e, 0xe7227e, 0xe7237e, 0xeaa07e, 0xeaa17e, 0xeaa27e, 0xeaa37e, 0xee207e, 0xee217e,
  0xee227e, 0xee237e, 0xf1a07e, 0xf1a17e, 0xf1a27e, 0xf1a37e, 0xf5207e, 0xf5217e, 0xf5227e, 0xf5237e, 0xf8a07e, 0xf8a17e, 0xf8a27e, 0xf8a37e,
};

void build_lists(HList& a, HList& b) {
  a.n = b.n = 0;
  for (uint32_t v : h_items1) a.it[a.n++] = v;
  for (uint32_t v : h_items2) b.it[b.n++] = v;
  a.head = FL_HEAD; a.tbase = 0;
  b.head = FL_HEAD2; b.tbase = a.n;
}

typedef CUresult (*EncodeFn)(CUtensorMap*, CUtensorMapDataType, cuuint32_t, void*, const cuuint64_t*, const cuuint64_t*,
                             const cuuint32_t*, const cuuint32_t*, CUtensorMapInterleave, CUtensorMapSwizzle,
                             CUtensorMapL2promotion, CUtensorMapFloatOOBfill);

void make_map(EncodeFn fn, CUtensorMap* m, const void* p, uint64_t cols, uint64_t rows, uint32_t bc, uint32_t br, CUtensorMapSwizzle sw) {
  cuuint64_t dims[2] = {cols, rows};
  cuuint64_t strides[1] = {cols * 2};
  cuuint32_t box[2] = {bc, br};
  cuuint32_t es[2] = {1, 1};
  fn(m, CU_TENSOR_MAP_DATA_TYPE_BFLOAT16, 2, const_cast<void*>(p), dims, strides, box, es, CU_TENSOR_MAP_INTERLEAVE_NONE, sw,
     CU_TENSOR_MAP_L2_PROMOTION_L2_128B, CU_TENSOR_MAP_FLOAT_OOB_FILL_NONE);
}

}

extern "C" void kernel_launch(void* const* d_in, const int* in_sizes, int n_in, void* d_out, int out_size) {
  const __nv_bfloat16* x = (const __nv_bfloat16*)d_in[0];
  const __nv_bfloat16* mem0 = (const __nv_bfloat16*)d_in[1];
  const __nv_bfloat16* cvec = (const __nv_bfloat16*)d_in[11];
  static EncodeFn enc = nullptr;
  if (!enc) {
    cudaDriverEntryPointQueryResult qr;
    void* fp = nullptr;
    cudaGetDriverEntryPoint("cuTensorMapEncodeTiled", &fp, cudaEnableDefault, &qr);
    enc = (EncodeFn)fp;
    cudaFuncSetAttribute(kernel_R, cudaFuncAttributeMaxDynamicSharedMemorySize, R_SMEM);
    cudaFuncSetAttribute(kernel_H, cudaFuncAttributeMaxDynamicSharedMemorySize, H_SMEM);
  }
  CUtensorMap tmq, tmk, tmv, tmo, tmm;
  make_map(enc, &tmm, d_in[12], 6144, 1024, 64, 64, CU_TENSOR_MAP_SWIZZLE_NONE);
  make_map(enc, &tmq, d_in[2], 4096, 1024, 64, 64, CU_TENSOR_MAP_SWIZZLE_128B);
  make_map(enc, &tmk, d_in[3], 4096, 1024, 64, 64, CU_TENSOR_MAP_SWIZZLE_128B);
  make_map(enc, &tmv, d_in[4], 4096, 1024, 64, 64, CU_TENSOR_MAP_SWIZZLE_128B);
  make_map(enc, &tmo, d_in[5], 1024, 4096, 16, 128, CU_TENSOR_MAP_SWIZZLE_32B);
  RDesc dsc;
  for (int k = 0; k < 32; k++) {
    dsc.tok[k] = mkdesc(0x400 + (k < 16 ? R_GA : R_GB) + ((k & 15) >> 2) * 4096 + (k & 3) * 256, 128, 1024, 0);
    dsc.tail_a[k] = mkdesc(0x400 + R_TAIL + k * 2048, 1024, 1024, 1);
    if (k < 16) dsc.tail_b[k] = mkdesc(0x400 + R_GA + k * 256, 128, 4096, 0);
  }
  kernel_R<<<96, 256, R_SMEM, cudaStreamPerThread>>>(tmq, tmk, tmv, tmo, tmm, x, mem0, cvec, dsc);

  CUtensorMap ho, h1, h3, h2, hm, hx, hy;
  make_map(enc, &ho, d_in[5], 1024, 4096, 64, 64, CU_TENSOR_MAP_SWIZZLE_128B);
  make_map(enc, &h1, d_in[8], F_, 1024, 64, 64, CU_TENSOR_MAP_SWIZZLE_128B);
  make_map(enc, &h3, d_in[9], F_, 1024, 64, 64, CU_TENSOR_MAP_SWIZZLE_128B);
  make_map(enc, &h2, d_in[10], 1024, F_, 64, 64, CU_TENSOR_MAP_SWIZZLE_128B);
  make_map(enc, &hm, d_in[12], 6144, 1024, 64, 64, CU_TENSOR_MAP_SWIZZLE_128B);
  make_map(enc, &hx, d_out, 1024, S_, 64, 128, CU_TENSOR_MAP_SWIZZLE_128B);
  make_map(enc, &hy, d_out, 1024, S_, 64, 64, CU_TENSOR_MAP_SWIZZLE_128B);
  HList list1, list2;
  build_lists(list1, list2);
  cudaLaunchConfig_t cfg = {};
  cfg.gridDim = dim3(NH1); cfg.blockDim = dim3(384); cfg.dynamicSmemBytes = H_SMEM; cfg.stream = cudaStreamPerThread;
  cudaLaunchAttribute at[2];
  at[0].id = cudaLaunchAttributeProgrammaticStreamSerialization;
  at[0].val.programmaticStreamSerializationAllowed = 1;
  at[1].id = cudaLaunchAttributeClusterDimension;
  at[1].val.clusterDim.x = 2; at[1].val.clusterDim.y = 1; at[1].val.clusterDim.z = 1;
  cfg.attrs = at; cfg.numAttrs = 1;
  cudaLaunchKernelEx(&cfg, kernel_H, ho, h1, h3, h2, hm, hx, hy, x, cvec, (__nv_bfloat16*)d_out, list1);
  cfg.numAttrs = 2; cfg.gridDim = dim3(NH2);
  cudaLaunchKernelEx(&cfg, kernel_H, ho, h1, h3, h2, hm, hx, hy, x, cvec, (__nv_bfloat16*)d_out, list2);
}
```

```cpp
#include <cuda_runtime.h>
#include <cuda_bf16.h>
#include <cuda.h>
#include <stdint.h>
#include <type_traits>

namespace {

constexpr int S_ = 2048, D_ = 1024, NSEG = 64, F_ = 3584;

__device__ __align__(1024) uint8_t g_h[S_ * D_ * 2];
__device__ __align__(1024) uint8_t g_att[S_ * 4096 * 2];
__device__ __align__(1024) uint8_t g_act[S_ * F_ * 2];
__device__ __align__(1024) uint8_t g_w13s[28 * 16 * 32768];
__device__ __align__(1024) uint8_t g_ext[16 * 2560];
__device__ __align__(1024) uint8_t g_bext[28 * 4096];
__device__ __align__(1024) __nv_bfloat16 g_gate[2 * D_];
__device__ __align__(1024) float g_slot[4 * 3 * 8 * 4 * 32 * 4];
__device__ __align__(128) __nv_bfloat16 g_mod[6 * D_];
__device__ __align__(128) float g_modp[3 * 2 * D_];
__device__ __align__(128) uint32_t g_flags[1024];
constexpr int FL_S1 = 0, FL_S2 = 32, FL_MOD = 64, FL_HEAD = 96, FL_EXIT = 128, FL_WS = 160, FL_GO = 192, FL_HEAD2 = 224, FL_ATT = 256, FL_XT = 384, FL_OUT = 512, FL_F1 = 640, FL_STAT = 768;

__device__ __forceinline__ uint32_t smem_u32(const void* p) { return (uint32_t)__cvta_generic_to_shared(p); }
__device__ __forceinline__ uint32_t mapa(uint32_t a, uint32_t r) { uint32_t o; asm("mapa.shared::cluster.u32 %0, %1, %2;" : "=r"(o) : "r"(a), "r"(r)); return o; }
__device__ __forceinline__ uint32_t pack2(float a, float b) { uint32_t r; asm("cvt.rn.bf16x2.f32 %0, %1, %2;" : "=r"(r) : "f"(b), "f"(a)); return r; }
__device__ __forceinline__ float bf_lo(uint32_t w) { return __uint_as_float(w << 16); }
__device__ __forceinline__ float bf_hi(uint32_t w) { return __uint_as_float(w & 0xffff0000u); }
__device__ __forceinline__ float ex2(float x) { float y; asm("ex2.approx.ftz.f32 %0, %1;" : "=f"(y) : "f"(x)); return y; }
__device__ __forceinline__ float rcp(float x) { float y; asm("rcp.approx.ftz.f32 %0, %1;" : "=f"(y) : "f"(x)); return y; }
__device__ __forceinline__ uint32_t clk32() { uint64_t c; asm volatile("mov.u64 %0, %%clock64;" : "=l"(c) :: "memory"); return (uint32_t)c; }

__device__ __forceinline__ void mbar_init(uint32_t b, uint32_t n) { asm volatile("mbarrier.init.shared::cta.b64 [%0], %1;" :: "r"(b), "r"(n) : "memory"); }
__device__ __forceinline__ void mbar_arrive(uint32_t b) { asm volatile("mbarrier.arrive.shared::cta.b64 _, [%0];" :: "r"(b) : "memory"); }
__device__ __forceinline__ void mbar_expect(uint32_t b, uint32_t n) { asm volatile("mbarrier.arrive.expect_tx.shared::cta.b64 _, [%0], %1;" :: "r"(b), "r"(n) : "memory"); }
__device__ __forceinline__ uint32_t mbar_try(uint32_t b, uint32_t par) {
  uint32_t ok;
  asm volatile("{\n.reg .pred p;\nmbarrier.try_wait.parity.shared::cta.b64 p, [%1], %2;\nselp.u32 %0, 1, 0, p;\n}" : "=r"(ok) : "r"(b), "r"(par) : "memory");
  return ok;
}
__device__ __forceinline__ void mbar_wait(uint32_t b, uint32_t par) {
  asm volatile("{\n.reg .pred p;\n"
               "LOOP:\n"
               "mbarrier.try_wait.parity.shared::cta.b64 p, [%0], %1;\n"
               "@!p bra.uni LOOP;\n}" :: "r"(b), "r"(par) : "memory");
}
__device__ __forceinline__ void mbar_wait_safe(uint32_t b, uint32_t par) {
  uint32_t c = 0;
  while (!mbar_try(b, par)) { if (++c > 4000000u) __trap(); }
}
__device__ __forceinline__ bool elect_one() {
  uint32_t p;
  asm volatile("{\n.reg .pred p;\nelect.sync _|p, 0xffffffff;\nselp.u32 %0, 1, 0, p;\n}" : "=r"(p));
  return p;
}
__device__ __forceinline__ void sched_fence(uint32_t x, uint32_t y) { asm volatile("{\n.reg .pred p;\nsetp.eq.u32 p, %0, %1;\n@p trap;\n}" :: "r"(x), "r"(y) : "memory"); }
template <class T> __device__ __forceinline__ T opaque32(T x) { asm volatile("" : "+r"(x)); return x; }
template <class T> __device__ __forceinline__ T opaque64(T x) { asm volatile("" : "+l"(x)); return x; }
template <int ID, int N> __device__ __forceinline__ void bar_sync() { asm volatile("bar.sync %0, %1;" :: "n"(ID), "n"(N) : "memory"); }
template <int ID, int N> __device__ __forceinline__ void bar_arrive() { asm volatile("bar.arrive %0, %1;" :: "n"(ID), "n"(N) : "memory"); }
__device__ __forceinline__ void fence_async_smem() { asm volatile("fence.proxy.async.shared::cta;" ::: "memory"); }
__device__ __forceinline__ void fence_async_all() { asm volatile("fence.proxy.async;" ::: "memory"); }
__device__ __forceinline__ void fence_gpu() { asm volatile("fence.acq_rel.gpu;" ::: "memory"); }
__device__ __forceinline__ void red_add_u32(uint32_t* p, uint32_t v) { asm volatile("red.relaxed.gpu.global.add.u32 [%0], %1;" :: "l"(p), "r"(v) : "memory"); }
__device__ __forceinline__ uint32_t ld_acquire(const uint32_t* p) { uint32_t v; asm volatile("ld.acquire.gpu.global.u32 %0, [%1];" : "=r"(v) : "l"(p) : "memory"); return v; }
__device__ __forceinline__ void wait_flag(const uint32_t* p, uint32_t target) {
  uint32_t c = 0;
  while (ld_acquire(p) < target) { if (++c > 20000000u) __trap(); __nanosleep(20); }
}

__device__ __forceinline__ void tma2d(uint32_t dst, const CUtensorMap* m, int c0, int c1, uint32_t bar) {
  asm volatile("cp.async.bulk.tensor.2d.shared::cluster.global.mbarrier::complete_tx::bytes [%0], [%1, {%3, %4}], [%2];"
               :: "r"(dst), "l"(m), "r"(bar), "r"(c0), "r"(c1) : "memory");
}
constexpr uint64_t L2_NORMAL = 0x1000000000000000ull, L2_FIRST = 0x12F0000000000000ull;
__device__ __forceinline__ void tma2d_p(uint32_t dst, const CUtensorMap* m, int c0, int c1, uint32_t bar, uint64_t pol) {
  asm volatile("cp.async.bulk.tensor.2d.shared::cluster.global.mbarrier::complete_tx::bytes.L2::cache_hint [%0], [%1, {%3, %4}], [%2], %5;"
               :: "r"(dst), "l"(m), "r"(bar), "r"(c0), "r"(c1), "l"(pol) : "memory");
}
__device__ __forceinline__ void bulk_g2s_p(uint32_t dst, const void* src, uint32_t bytes, uint32_t bar, uint64_t pol) {
  asm volatile("cp.async.bulk.shared::cluster.global.mbarrier::complete_tx::bytes.L2::cache_hint [%0], [%1], %2, [%3], %4;"
               :: "r"(dst), "l"(src), "r"(bytes), "r"(bar), "l"(pol) : "memory");
}
#define POL_RW L2_FIRST
__device__ __forceinline__ void tma2d_prefetch_p(const CUtensorMap* m, int c0, int c1, uint64_t pol) {
  asm volatile("cp.async.bulk.prefetch.tensor.2d.L2.global.L2::cache_hint [%0, {%1, %2}], %3;" :: "l"(m), "r"(c0), "r"(c1), "l"(pol) : "memory");
}
__device__ __forceinline__ void tma2d_prefetch(const CUtensorMap* m, int c0, int c1) {
  asm volatile("cp.async.bulk.prefetch.tensor.2d.L2.global [%0, {%1, %2}];" :: "l"(m), "r"(c0), "r"(c1) : "memory");
}
__device__ __forceinline__ void bulk_g2s(uint32_t dst, const void* src, uint32_t bytes, uint32_t bar) {
  asm volatile("cp.async.bulk.shared::cluster.global.mbarrier::complete_tx::bytes [%0], [%1], %2, [%3];"
               :: "r"(dst), "l"(src), "r"(bytes), "r"(bar) : "memory");
}
__device__ __forceinline__ void bulk_s2s(uint32_t dst, uint32_t src, uint32_t bytes, uint32_t bar) {
  asm volatile("cp.async.bulk.shared::cluster.shared::cta.mbarrier::complete_tx::bytes [%0], [%1], %2, [%3];"
               :: "r"(dst), "r"(src), "r"(bytes), "r"(bar) : "memory");
}
__device__ __forceinline__ void st_async1(uint32_t dst, uint32_t a, uint32_t bar) {
  asm volatile("st.async.shared::cluster.mbarrier::complete_tx::bytes.b32 [%0], %1, [%2];" :: "r"(dst), "r"(a), "r"(bar) : "memory");
}
__device__ __forceinline__ void st_async2(uint32_t dst, uint32_t a, uint32_t b, uint32_t bar) {
  asm volatile("st.async.shared::cluster.mbarrier::complete_tx::bytes.v2.b32 [%0], {%1, %2}, [%3];" :: "r"(dst), "r"(a), "r"(b), "r"(bar) : "memory");
}
__device__ __forceinline__ void st_async4(uint32_t dst, const uint32_t* r, uint32_t bar) {
  asm volatile("st.async.shared::cluster.mbarrier::complete_tx::bytes.v4.b32 [%0], {%1, %2, %3, %4}, [%5];"
               :: "r"(dst), "r"(r[0]), "r"(r[1]), "r"(r[2]), "r"(r[3]), "r"(bar) : "memory");
}
__device__ __forceinline__ void sts32(uint32_t a, uint32_t v) { asm volatile("st.shared.b32 [%0], %1;" :: "r"(a), "r"(v) : "memory"); }
__device__ __forceinline__ void sts64(uint32_t a, uint32_t x, uint32_t y) { asm volatile("st.shared.v2.b32 [%0], {%1, %2};" :: "r"(a), "r"(x), "r"(y) : "memory"); }
__device__ __forceinline__ void sts128(uint32_t a, uint32_t x, uint32_t y, uint32_t z, uint32_t w) {
  asm volatile("st.shared.v4.b32 [%0], {%1, %2, %3, %4};" :: "r"(a), "r"(x), "r"(y), "r"(z), "r"(w) : "memory");
}
__device__ __forceinline__ void lds128(uint32_t* r, uint32_t a) {
  asm volatile("ld.shared.v4.b32 {%0, %1, %2, %3}, [%4];" : "=r"(r[0]), "=r"(r[1]), "=r"(r[2]), "=r"(r[3]) : "r"(a) : "memory");
}
__device__ __forceinline__ uint32_t lds32(uint32_t a) { uint32_t r; asm volatile("ld.shared.b32 %0, [%1];" : "=r"(r) : "r"(a) : "memory"); return r; }
__device__ __forceinline__ void lds64(uint32_t* r, uint32_t a) {
  asm volatile("ld.shared.v2.b32 {%0, %1}, [%2];" : "=r"(r[0]), "=r"(r[1]) : "r"(a) : "memory");
}
__device__ __forceinline__ void lds128f(float* r, uint32_t a) {
  asm volatile("ld.shared.v4.f32 {%0, %1, %2, %3}, [%4];" : "=f"(r[0]), "=f"(r[1]), "=f"(r[2]), "=f"(r[3]) : "r"(a) : "memory");
}
__device__ __forceinline__ void lds64f(float* r, uint32_t a) {
  asm volatile("ld.shared.v2.f32 {%0, %1}, [%2];" : "=f"(r[0]), "=f"(r[1]) : "r"(a) : "memory");
}
__device__ __forceinline__ void ldsm4(uint32_t* r, uint32_t a) {
  asm volatile("ldmatrix.sync.aligned.m8n8.x4.shared.b16 {%0, %1, %2, %3}, [%4];" : "=r"(r[0]), "=r"(r[1]), "=r"(r[2]), "=r"(r[3]) : "r"(a) : "memory");
}
__device__ __forceinline__ void ldsm4t(uint32_t* r, uint32_t a) {
  asm volatile("ldmatrix.sync.aligned.m8n8.x4.trans.shared.b16 {%0, %1, %2, %3}, [%4];" : "=r"(r[0]), "=r"(r[1]), "=r"(r[2]), "=r"(r[3]) : "r"(a) : "memory");
}
__device__ __forceinline__ void ldsm2(uint32_t* r, uint32_t a) {
  asm volatile("ldmatrix.sync.aligned.m8n8.x2.shared.b16 {%0, %1}, [%2];" : "=r"(r[0]), "=r"(r[1]) : "r"(a) : "memory");
}
__device__ __forceinline__ void stsm4(uint32_t a, const uint32_t* r) {
  asm volatile("stmatrix.sync.aligned.m8n8.x4.shared.b16 [%0], {%1, %2, %3, %4};" :: "r"(a), "r"(r[0]), "r"(r[1]), "r"(r[2]), "r"(r[3]) : "memory");
}
__device__ __forceinline__ uint32_t hadd2(uint32_t a, uint32_t b) { uint32_t t; asm("add.rn.bf16x2 %0, %1, %2;" : "=r"(t) : "r"(a), "r"(b)); return t; }
__device__ __forceinline__ uint32_t hmax2(uint32_t a, uint32_t b) { uint32_t t; asm("max.bf16x2 %0, %1, %2;" : "=r"(t) : "r"(a), "r"(b)); return t; }
__device__ __forceinline__ void ldsm2t(uint32_t* r, uint32_t a) {
  asm volatile("ldmatrix.sync.aligned.m8n8.x2.trans.shared.b16 {%0, %1}, [%2];" : "=r"(r[0]), "=r"(r[1]) : "r"(a) : "memory");
}
__device__ __forceinline__ uint32_t movm(uint32_t x) { uint32_t y; asm volatile("movmatrix.sync.aligned.m8n8.trans.b16 %0, %1;" : "=r"(y) : "r"(x)); return y; }
__device__ __forceinline__ void hmma(float* d, uint32_t a0, uint32_t a1, uint32_t a2, uint32_t a3, uint32_t b0, uint32_t b1) {
  asm volatile("mma.sync.aligned.m16n8k16.row.col.f32.bf16.bf16.f32 {%0,%1,%2,%3}, {%4,%5,%6,%7}, {%8,%9}, {%0,%1,%2,%3};"
               : "+f"(d[0]), "+f"(d[1]), "+f"(d[2]), "+f"(d[3]) : "r"(a0), "r"(a1), "r"(a2), "r"(a3), "r"(b0), "r"(b1));
}
__device__ __forceinline__ void hmma0(float* d, uint32_t a0, uint32_t a1, uint32_t a2, uint32_t a3, uint32_t b0, uint32_t b1) {
  asm volatile("mma.sync.aligned.m16n8k16.row.col.f32.bf16.bf16.f32 {%0,%1,%2,%3}, {%4,%5,%6,%7}, {%8,%9}, {%10,%10,%10,%10};"
               : "=f"(d[0]), "=f"(d[1]), "=f"(d[2]), "=f"(d[3]) : "r"(a0), "r"(a1), "r"(a2), "r"(a3), "r"(b0), "r"(b1), "f"(0.f));
}
__device__ __forceinline__ void hmma_k8(float* d, uint32_t a0, uint32_t a1, uint32_t b0) {
  asm volatile("mma.sync.aligned.m16n8k8.row.col.f32.bf16.bf16.f32 {%0,%1,%2,%3}, {%4,%5}, {%6}, {%0,%1,%2,%3};"
               : "+f"(d[0]), "+f"(d[1]), "+f"(d[2]), "+f"(d[3]) : "r"(a0), "r"(a1), "r"(b0));
}
__host__ __device__ constexpr uint64_t mkdesc(uint32_t addr, uint32_t lbo, uint32_t sbo, uint32_t sw) {
  return (uint64_t)((addr & 0x3FFFF) >> 4) | ((uint64_t)(lbo >> 4) << 16) | ((uint64_t)(sbo >> 4) << 32) | ((uint64_t)sw << 62);
}
#define WG_FENCE() asm volatile("wgmma.fence.sync.aligned;" ::: "memory")
#define WG_COMMIT() asm volatile("wgmma.commit_group.sync.aligned;" ::: "memory")
#define WG_WAIT(n) asm volatile("wgmma.wait_group.sync.aligned " #n ";" ::: "memory")
template <int N> __device__ __forceinline__ void reg_fence(float* d) {
#pragma unroll
  for (int i = 0; i < N; i++) asm volatile("" : "+f"(d[i]) :: "memory");
}
template <int N> __device__ __forceinline__ void zero_regs(float* d) {
#pragma unroll
  for (int i = 0; i < N; i++) asm volatile("mov.b32 %0, 0;" : "=f"(d[i]));
}
template <int SD>
__device__ __forceinline__ void wg_rs32(float* d, uint32_t a0, uint32_t a1, uint32_t a2, uint32_t a3, uint64_t b) {
  asm volatile("wgmma.mma_async.sync.aligned.m64n32k16.f32.bf16.bf16 {%0,%1,%2,%3,%4,%5,%6,%7,%8,%9,%10,%11,%12,%13,%14,%15}, {%16,%17,%18,%19}, %20, %21, 1, 1, 0;"
               : "+f"(d[0]), "+f"(d[1]), "+f"(d[2]), "+f"(d[3]), "+f"(d[4]), "+f"(d[5]), "+f"(d[6]), "+f"(d[7]),
                 "+f"(d[8]), "+f"(d[9]), "+f"(d[10]), "+f"(d[11]), "+f"(d[12]), "+f"(d[13]), "+f"(d[14]), "+f"(d[15])
               : "r"(a0), "r"(a1), "r"(a2), "r"(a3), "l"(b), "n"(SD));
}
template <int SD>
__device__ __forceinline__ void wg_rs40(float* d, const uint32_t* a, uint64_t b) {
  asm volatile("wgmma.mma_async.sync.aligned.m64n40k16.f32.bf16.bf16 {%0,%1,%2,%3,%4,%5,%6,%7,%8,%9,%10,%11,%12,%13,%14,%15,%16,%17,%18,%19}, {%20,%21,%22,%23}, %24, %25, 1, 1, 0;"
               : "+f"(d[0]), "+f"(d[1]), "+f"(d[2]), "+f"(d[3]), "+f"(d[4]), "+f"(d[5]), "+f"(d[6]), "+f"(d[7]),
                 "+f"(d[8]), "+f"(d[9]), "+f"(d[10]), "+f"(d[11]), "+f"(d[12]), "+f"(d[13]), "+f"(d[14]), "+f"(d[15]),
                 "+f"(d[16]), "+f"(d[17]), "+f"(d[18]), "+f"(d[19])
               : "r"(a[0]), "r"(a[1]), "r"(a[2]), "r"(a[3]), "l"(b), "n"(SD));
}
template <int TB>
__device__ __forceinline__ void wg_ss40(float* d, uint64_t a, uint64_t b) {
  asm volatile("wgmma.mma_async.sync.aligned.m64n40k16.f32.bf16.bf16 {%0,%1,%2,%3,%4,%5,%6,%7,%8,%9,%10,%11,%12,%13,%14,%15,%16,%17,%18,%19}, %20, %21, 1, 1, 1, 1, %22;"
               : "+f"(d[0]), "+f"(d[1]), "+f"(d[2]), "+f"(d[3]), "+f"(d[4]), "+f"(d[5]), "+f"(d[6]), "+f"(d[7]),
                 "+f"(d[8]), "+f"(d[9]), "+f"(d[10]), "+f"(d[11]), "+f"(d[12]), "+f"(d[13]), "+f"(d[14]), "+f"(d[15]),
                 "+f"(d[16]), "+f"(d[17]), "+f"(d[18]), "+f"(d[19])
               : "l"(a), "l"(b), "n"(TB));
}
template <int T>
__device__ __forceinline__ void wg_ss32(float* d, uint64_t a, uint64_t b) {
  asm volatile("wgmma.mma_async.sync.aligned.m64n32k16.f32.bf16.bf16 {%0,%1,%2,%3,%4,%5,%6,%7,%8,%9,%10,%11,%12,%13,%14,%15}, %16, %17, 1, 1, 1, %18, %18;"
               : "+f"(d[0]), "+f"(d[1]), "+f"(d[2]), "+f"(d[3]), "+f"(d[4]), "+f"(d[5]), "+f"(d[6]), "+f"(d[7]),
                 "+f"(d[8]), "+f"(d[9]), "+f"(d[10]), "+f"(d[11]), "+f"(d[12]), "+f"(d[13]), "+f"(d[14]), "+f"(d[15])
               : "l"(a), "l"(b), "n"(T));
}

constexpr int R_TAIL = 0;
constexpr int R_WO = 65536;
constexpr int R_QK = R_WO + 86016;
constexpr int R_P = R_QK + 10240;
constexpr int R_GA = R_P + 6400;
constexpr int R_M2 = R_GA + 16384;
constexpr int R_M1 = R_M2 + 7168;
constexpr int R_GB = R_M1 + 9216;
constexpr int R_VT = R_GB + 16384;
constexpr int R_VM = R_VT + 8192;
constexpr int R_XS = R_VM + 2048;
constexpr int R_OX = R_XS + 1280;
constexpr int R_BAR = R_OX + 2048;
constexpr int R_TRC = R_BAR + 256;
constexpr int R_SMEM = R_TRC + 1024;
constexpr int B_MB = 0, B_XS = 32, B_VM = 40, B_VT = 48, B_TS = 56, B_FA = 64, B_FB = 72, B_TAIL = 80, B_WO = 88, B_STG = 96, B_WM = 128, B_X = 136;
constexpr int NB_A = 1, NB_B = 2, NB_X = 3, NB_C = 4, NB_D = 5, NB_E = 6, NB_F = 7, NB_G = 8, NB_H = 9, NB_S = 10, NB_E2 = 11, NB_P = 12, NB_W0 = 13;

#define POLL_DELAY 750
#define POLL_DELAY1 700
#define P1K -1
#define P2K -1
#define ZS 2
#define HPF 4
#define PF1 2
#define PF2 2
#define PF3 2
#define PF4 0
#define S2E 0
#define RF_FIRST 0
#define BX_I 5
#define NCH 4
#define TOP2 0
#define CX_I 13
#define ATT_LATE 0
#define V_FENCE 1
#define SELF_STAS 1
#define Q_FENCE 1
#define ND_K 3
#define TRACE(i)
#define TS(i)

__device__ __forceinline__ int rot_chunk(int c, int rank) {
  int G = c;
  if (c < 9) { G = c + 3 * rank; if (G >= 9) G -= 9; }
  return G;
}
__device__ __forceinline__ int wo_tile(int i, int rank) {
  if (i < 12) return 12 * rank + i;
  const int r = i - 12 + 9 * rank;
  return r < 16 ? 48 + r : 20 + r;
}
__device__ __forceinline__ void load_chunk(uint32_t dst, int seg, int G, uint32_t bar) {
  mbar_expect(bar, 4096);
  bulk_g2s(dst, g_h + (size_t)(seg * 16 + G) * 4096, 4096, bar);
}
__device__ __forceinline__ void load_red(uint32_t* v, const float* p) {
#pragma unroll
  for (int j = 0; j < 2; j++)
    asm volatile("ld.relaxed.gpu.global.v4.u32 {%0, %1, %2, %3}, [%4];"
                 : "=r"(v[4 * j]), "=r"(v[4 * j + 1]), "=r"(v[4 * j + 2]), "=r"(v[4 * j + 3]) : "l"(p + j * 256) : "memory");
}
__device__ __forceinline__ bool red_done(const uint32_t* v) { return __all_sync(0xffffffffu, (v[3] & v[7]) == 0x42000000u); }
__device__ __forceinline__ uint32_t finish_red(uint32_t* v, const float* p) {
  uint32_t tries = 0;
  if (__builtin_expect(!red_done(v), 0)) {
    do { if (++tries > 20000000u) __trap(); load_red(v, p); } while (!red_done(v));
  }
  return tries;
}
__device__ __forceinline__ void exp10(float* sv, const uint32_t* x) {
  constexpr float SC = 0.08838834764831845f * 1.4426950408889634f;
  uint32_t m2 = hmax2(hmax2(hmax2(x[0], x[1]), hmax2(x[2], x[3])), x[4]);
  m2 = hmax2(m2, __shfl_xor_sync(0xffffffffu, m2, 1));
  m2 = hmax2(m2, __shfl_xor_sync(0xffffffffu, m2, 2));
  const float nm = -fmaxf(bf_lo(m2), bf_hi(m2)) * SC;
#pragma unroll
  for (int j = 0; j < 5; j++) { sv[2 * j] = ex2(fmaf(bf_lo(x[j]), SC, nm)); sv[2 * j + 1] = ex2(fmaf(bf_hi(x[j]), SC, nm)); }
}

__device__ __forceinline__ uint32_t arm_size(int w, bool isC) {
  return w == 0 ? (isC ? 1280 : 640) : w == 1 ? (isC ? 0 : 2048) : w == 2 ? (isC ? 0 : 8192) : (isC ? 0 : 1792);
}
__device__ __forceinline__ void forward_initial(uint32_t sb, uint32_t rank, int wg, int w, int lane) {
  const uint32_t bars = sb + R_BAR, to1 = rank == 0 ? 2u << 24 : 0u - (1u << 24), to2 = rank == 2 ? 0u - (2u << 24) : 1u << 24;
  if (wg == 1 && w > 0 && elect_one()) mbar_expect(bars + B_MB + 8 * w, w < 3 ? 3072 : SELF_STAS ? 28 * 256 : rank == 2 ? 18 * 256 : 19 * 256);
  if (wg == 1 && w == 3 && rank != 2) return;
  const float* slot = g_slot + (rank * 1024 + (wg * 4 + w) * 128 + lane) * 4 + 3 * 12288 + 4 * 32;
  uint32_t v[8], u[6];
  load_red(v, slot);
  finish_red(v, slot);
#pragma unroll
  for (int j = 0; j < 6; j++) u[j] = movm(v[4 * (j / 3) + j % 3]);
  if (wg == 0) {
    const uint32_t a = sb + lane * 16 + R_M1 + w * 768, a2 = sb + lane * 8 + R_M1 + 512 + w * 768;
    st_async4(a + to1 + 3072, u, bars + to1 + B_MB + 8); st_async2(a2 + to1 + 3072, u[4], u[5], bars + to1 + B_MB + 8);
    sts128(a, u[0], u[1], u[2], u[3]); sts64(a2, u[4], u[5]);
    __syncwarp();
    if (elect_one()) mbar_arrive(bars + B_MB);
    st_async4(a + to2 + 6144, u, bars + to2 + B_MB + 16); st_async2(a2 + to2 + 6144, u[4], u[5], bars + to2 + B_MB + 16);
  } else {
    const uint32_t a = sb + lane * 4 + R_M2 + rank * 2304 + w * 768;
    const int n = w < 3 ? 6 : 2;
#pragma unroll
    for (int j = 0; j < 6; j++) if (j < n) { st_async1(a + to1 + j * 128, u[j], bars + to1 + B_MB + 24); st_async1(a + to2 + j * 128, u[j], bars + to2 + B_MB + 24); }
    if (SELF_STAS) {
#pragma unroll
      for (int j = 0; j < 6; j++) if (j < n) st_async1(a + j * 128, u[j], bars + B_MB + 24);
    } else {
#pragma unroll
      for (int j = 0; j < 6; j++) if (j < n) sts32(a + j * 128, u[j]);
      __syncwarp();
      if (elect_one()) mbar_arrive(bars + B_MB + 24);
    }
  }
}
struct RDesc { uint64_t tok[32], tail_b[16], tail_a[32]; };

template <int WG>
__device__ __forceinline__ void r_main(const uint32_t (&W)[48][4], const RDesc& dsc, int head, uint32_t rank, int lane_, int w) {
  const uint32_t sb = (rank << 24) + 0x400, bars = sb + R_BAR;
  const uint32_t to1 = rank == 0 ? 2u << 24 : 0u - (1u << 24), to2 = rank == 2 ? 0u - (2u << 24) : 1u << 24;
  const bool isC = rank == 2;
  const int lane = opaque32(lane_), warp = WG * 4 + w;
  const int gl = rot_chunk(4 * (lane & 3) + w, rank);
  const int g0 = __shfl_sync(0xffffffffu, gl, 0), g1 = __shfl_sync(0xffffffffu, gl, 1), g2 = __shfl_sync(0xffffffffu, gl, 2);
  const uint32_t arm_bytes = arm_size(w, isC);

#define L16 opaque32(sb + opaque32(lane) * 16)
#define L8 opaque32(sb + opaque32(lane) * 8)
#define L4 opaque32(sb + opaque32(lane) * 4)
#define LV opaque32(sb + R_VT + ((opaque32(lane) >> 3) & 1) * 512 + (opaque32(lane) >> 4) * 128 + (opaque32(lane) & 7) * 16)
#define SLOT(st) opaque64(slot0 + ((st) & 3) * 12288 + ((st) & 4) * 32)
  float* const slot0 = opaque64(g_slot + (rank * 1024 + warp * 128 + lane) * 4);
  const uint32_t woa = opaque32(sb + R_WO + warp * 12288 + ((lane >> 4) * 8 + (lane & 7)) * 32 + ((((lane >> 3) ^ (lane >> 2)) & 1) << 4));
  const bool has_wo = WG == 0 || isC || w < 3;
  float acc[20];
  uint32_t pk[8] = {0u, 0u, 0u, 0u, 0u, 0u, 0u, 0u};

  auto forward = [&](auto rd, const uint32_t* v, int st, uint32_t tries) {
    constexpr int RD = decltype(rd)::value;
    uint32_t u[6];
#pragma unroll
    for (int j = 0; j < 6; j++) u[j] = movm(v[4 * (j / 3) + j % 3]);
    const bool all3 = RD == 0 || w < 3;
    if (RD == 0) {
      const uint32_t a = L16 + R_M1 + w * 768, a2 = L8 + R_M1 + 512 + w * 768;
      st_async4(a + to1 + 3072, u, bars + to1 + B_MB + 8); st_async2(a2 + to1 + 3072, u[4], u[5], bars + to1 + B_MB + 8);
      sts128(a, u[0], u[1], u[2], u[3]); sts64(a2, u[4], u[5]);
      __syncwarp();
      if (elect_one()) mbar_arrive(bars + B_MB);
      st_async4(a + to2 + 6144, u, bars + to2 + B_MB + 16); st_async2(a2 + to2 + 6144, u[4], u[5], bars + to2 + B_MB + 16);
    } else {
      const uint32_t a = L4 + R_M2 + rank * 2304 + w * 768;
#pragma unroll
      for (int j = 0; j < 6; j++) if (j < 2 || all3) st_async1(a + to1 + j * 128, u[j], bars + to1 + B_MB + 24);
#pragma unroll
      for (int j = 0; j < 6; j++) if (j < 2 || all3) st_async1(a + to2 + j * 128, u[j], bars + to2 + B_MB + 24);
      if (SELF_STAS) {
#pragma unroll
        for (int j = 0; j < 6; j++) if (j < 2 || all3) st_async1(a + j * 128, u[j], bars + B_MB + 24);
      } else {
#pragma unroll
        for (int j = 0; j < 6; j++) if (j < 2 || all3) sts32(a + j * 128, u[j]);
        __syncwarp();
        if (elect_one()) mbar_arrive(bars + B_MB + 24);
      }
    }
  };

  auto send_vt = [&]() {
    if (elect_one()) {
      const uint32_t src = sb + R_VT + warp * 1024;
      bulk_s2s(src + to1, src, 1024, bars + to1 + B_VT);
      bulk_s2s(src + to2, src, 1024, bars + to2 + B_VT);
    }
  };
  auto store_att = [&](int sg) {
    uint32_t* op = reinterpret_cast<uint32_t*>(g_att + (size_t)((sg >> 2) * 64 + head * 2 + rank) * 16384 + (2 * w * 16 + (sg & 3) * 4) * 128) + opaque32(lane);
#pragma unroll
    for (int j = 0; j < 8; j++) op[(j & 1) * 512 + (j >> 1) * 32] = pk[j];
  };

  auto token_softmax = [&](uint32_t par) {
    const int ln = opaque32(lane), kg = w - (ln >> 3);
    const uint32_t r16 = sb + R_P + w * 768 + (ln & 7) * 16;
    const uint32_t ta = r16 + (kg >= 0 ? kg * 128 : 640);
    const int dg = (ln >> 2) - 2 * (ln & 3);
    const uint32_t keep = dg > 0 ? 0xffffffffu : dg == 0 ? 0x0000ffffu : 0u;
    mbar_wait(bars + B_TS, par);
    uint32_t x[6], y[4];
    ldsm4t(x, ta); ldsm4t(y, ta + 3072); ldsm2t(x + 4, r16 + 512 + ((ln >> 3) & 1) * 3072);
#pragma unroll
    for (int j = 0; j < 5; j++) x[j] = hadd2(x[j], j < 4 ? y[j] : x[5]);
    x[0] = (x[0] & keep) | (0xff80ff80u & ~keep);
    float sv[10];
    exp10(sv, x);
    float sum = (((sv[0] + sv[1]) + (sv[2] + sv[3])) + ((sv[4] + sv[5]) + (sv[6] + sv[7]))) + (sv[8] + sv[9]);
    sum += __shfl_xor_sync(0xffffffffu, sum, 1);
    sum += __shfl_xor_sync(0xffffffffu, sum, 2);
    const float inv = rcp(sum);
#pragma unroll
    for (int j = 0; j < 5; j++) x[j] = pack2(sv[2 * j] * inv, sv[2 * j + 1] * inv);
    stsm4(r16 + (kg & 3) * 128, x);
    sts32(sb + ln * 4 + w * 768 + R_P + 512, x[4]);
    fence_async_smem();
    bar_arrive<NB_P, 256>();
  };
  auto mem_proj = [&](uint32_t par, auto mid) {
    float c[NCH][4];
    uint32_t b[3][6];
    const uint32_t ma = L16, m8 = L8;
#pragma unroll
    for (int i = 0; i < 18; i++) {
      if (i < 16) {
        if (i % 4 == 0) mbar_wait(bars + B_MB + (i / 4) * 8, par);
        if (i < 12) { lds128(b[i % 3], ma + R_M1 + i * 768); lds64(b[i % 3] + 4, m8 + R_M1 + 512 + i * 768); }
        else { ldsm4(b[i % 3], ma + R_M2 + 4096 + (i - 12) * 768); ldsm2(b[i % 3] + 4, ma + R_M2 + 4096 + 512 + (i - 12) * 768); }
      }
      mid(i);
      if (i < 16) __syncwarp();
      if (i >= 2) {
        const int j = i - 2;
#pragma unroll
        for (int q = 0; q < 3; q++) {
          const uint32_t* f = W[3 * j + q];
          if (3 * j + q < NCH) hmma0(c[3 * j + q], f[0], f[1], f[2], f[3], b[j % 3][2 * q], b[j % 3][2 * q + 1]);
          else hmma(c[(3 * j + q) % NCH], f[0], f[1], f[2], f[3], b[j % 3][2 * q], b[j % 3][2 * q + 1]);
        }
      }
    }
#pragma unroll
    for (int j = 0; j < 4; j++) acc[16 + j] = NCH == 3 ? (c[0][j] + c[1][j]) + c[2][j] : (c[0][j] + c[1][j]) + (c[2][j] + c[NCH - 1][j]);
  };

  if (WG == 0) bar_arrive<NB_G, 256>();
#pragma unroll 1
  for (int s = 0; s < NSEG - 1; s++) {
    const uint32_t par = s & 1;
    TRACE(0);
    {
      float c[NCH][4];
      uint32_t b[3][6];
      const uint32_t ma = L16, m8 = L8;
#pragma unroll
      for (int i = 0; i < 18; i++) {
        if (i < 16) {
          if (i % 4 == 0 && !(i == 4 && TOP2)) mbar_wait(bars + B_MB + (i / 4) * 8, par);
          if (i == 0 && TOP2) mbar_wait(bars + B_MB + 8, par);
          if (i % 4 == 0) TRACE(1 + i / 4);
          if (i < 12) { lds128(b[i % 3], ma + R_M1 + i * 768); lds64(b[i % 3] + 4, m8 + R_M1 + 512 + i * 768); }
          else { ldsm4(b[i % 3], ma + R_M2 + 4096 + (i - 12) * 768); ldsm2(b[i % 3] + 4, ma + R_M2 + 4096 + 512 + (i - 12) * 768); }
          if (WG == 1 && i == BX_I) {
            bar_sync<NB_G, 256>();
            if (elect_one()) load_chunk(sb + R_GB + w * 4096, s + 1, g0, bars + B_FB);
          }
          if (i == CX_I) {
            if (isC) send_vt();
            if (WG == 1 && ATT_LATE && !isC && s > 0) store_att(s - 1);
          }
          __syncwarp();
        }
        if (i >= 2) {
          const int j = i - 2;
#pragma unroll
          for (int q = 0; q < 3; q++) {
            const uint32_t* f = W[3 * j + q];
            if (3 * j + q < NCH) hmma0(c[3 * j + q], f[0], f[1], f[2], f[3], b[j % 3][2 * q], b[j % 3][2 * q + 1]);
            else hmma(c[(3 * j + q) % NCH], f[0], f[1], f[2], f[3], b[j % 3][2 * q], b[j % 3][2 * q + 1]);
          }
        }
        if (i == 14) zero_regs<16>(acc);
        if (i == 16) mbar_wait(bars + B_FA, 0);
      }
#pragma unroll
      for (int j = 0; j < 4; j++) acc[16 + j] = NCH == 3 ? (c[0][j] + c[1][j]) + c[2][j] : (c[0][j] + c[1][j]) + (c[2][j] + c[NCH - 1][j]);
    }
    TRACE(5);
    bar_sync<NB_H, 256>();
    WG_FENCE();
#pragma unroll
    for (int k = 0; k < 16; k++) wg_ss40<0>(acc, dsc.tail_a[WG * 16 + k], dsc.tail_b[k]);
    WG_COMMIT();
    uint32_t vt[4][4];
    {
      const uint32_t a = opaque32(L4 + w * 256 + (isC ? WG * 1024 + R_VM : R_QK + 4096 + WG * 5120));
      const uint32_t qa = L16 + R_QK, xa = opaque32(LV + w * 2048 + (WG == 0 ? 0 : (opaque32(lane) & 8) * 64 + R_QK + 5120 - R_VT));
      const uint32_t d = opaque32(L4 + R_XS + rank * 640 + w * 256);
      if (s == 0) {
        mbar_wait_safe(bars + B_WO, 0);
        TS(10);
        if (WG == 1 && head == 0 && rank == 0 && w == 0 && elect_one()) red_add_u32(&g_flags[FL_GO], 1);
      }
      mbar_wait(bars + B_FB, 0);
      if (WG == 0) mbar_wait(bars + B_VT, par);
      WG_WAIT(0);
      reg_fence<20>(acc);
      TRACE(6);
      const uint32_t p0 = pack2(acc[16], acc[17]), p1 = pack2(acc[18], acc[19]);
      sts32(a, p0); sts32(a + 128, p1);
      if (isC) {
        st_async1(a + to1, p0, bars + B_VM + to1); st_async1(a + to1 + 128, p1, bars + B_VM + to1);
        st_async1(a + to2, p0, bars + B_VM + to2); st_async1(a + to2 + 128, p1, bars + B_VM + to2);
      }
      if (WG == 0) {
        bar_arrive<NB_A, 256>();
        if (Q_FENCE && !isC) fence_async_smem();
#pragma unroll
        for (int i = 0; i < 4; i++) ldsm4(vt[i], xa + (i >> 1) * 1024 + (i & 1) * 256);
        bar_sync<NB_S, 256>();
      } else {
        bar_sync<NB_A, 256>();
        if (!isC) {
          if (w < 3) {
            uint32_t q[8], k[4][4];
            ldsm4t(q, qa + 4096); ldsm4t(k[0], xa); ldsm4t(k[1], xa + 256);
            ldsm4t(q + 4, qa + 4096 + 512); ldsm4t(k[2], xa + 512); ldsm4t(k[3], xa + 768);
            float x[4], y[4];
            hmma0(x, k[0][0], k[0][1], k[0][2], k[0][3], q[0], q[1]); hmma0(y, k[1][0], k[1][1], k[1][2], k[1][3], q[2], q[3]);
            hmma(x, k[2][0], k[2][1], k[2][2], k[2][3], q[4], q[5]); hmma(y, k[3][0], k[3][1], k[3][2], k[3][3], q[6], q[7]);
            const uint32_t s0 = pack2(x[0] + y[0], x[1] + y[1]), s1 = pack2(x[2] + y[2], x[3] + y[3]);
            st_async1(d + to1, s0, bars + B_XS + to1);
            st_async1(d + to2, s0, bars + B_XS + to2);
            if (w < 2) { st_async1(d + to1 + 128, s1, bars + B_XS + to1); st_async1(d + to2 + 128, s1, bars + B_XS + to2); sts32(d + 128, s1); }
            sts32(d, s0);
          }
        }
        bar_arrive<NB_S, 256>();
      }
    }
    if (WG == 1) {
      if (elect_one()) load_chunk(sb + R_GA + w * 4096, s + 1, g1, bars + B_FA);
      {
        if (w > 0 && elect_one()) mbar_expect(bars + B_MB + 8 * w, w < 3 ? 3072 : SELF_STAS ? 28 * 256 : isC ? 18 * 256 : 19 * 256);
      }
      fence_async_smem();
      bar_sync<NB_B, 256>();
    }
    TRACE(7);
    WG_FENCE();
#pragma unroll
    for (int k = 0; k < 16; k++) wg_rs32<1>(acc, W[k][0], W[k][1], W[k][2], W[k][3], dsc.tok[16 + k]);
    WG_COMMIT();
    uint32_t wa[3][4];
    const uint32_t oxa = L16 + R_OX;
    if (WG == 0) {
      const uint32_t vma = oxa - (R_OX - R_VM) + w * 512, oa = opaque32(L4 + w * 512 + R_OX);
      TRACE(8);
      mbar_wait(bars + B_XS, par);
      TRACE(9);
      float sv[10];
      {
        uint32_t x[10];
        ldsm4t(x, oxa - (R_OX - R_XS)); ldsm4t(x + 4, oxa - (R_OX - R_XS) + 512); ldsm2t(x + 8, oxa - (R_OX - R_XS) + 1024);
        bar_arrive<NB_B, 256>();
#pragma unroll
        for (int j = 0; j < 5; j++) x[j] = hadd2(x[j], x[j + 5]);
        exp10(sv, x);
      }
      WG_WAIT(0);
      bar_arrive<NB_X, 256>();
      mbar_wait(bars + B_VM, par);
      uint32_t vm[4];
      ldsm4(vm, vma);
      uint32_t pb[5];
#pragma unroll
      for (int j = 0; j < 5; j++) pb[j] = pack2(sv[2 * j], sv[2 * j + 1]);
      TRACE(10);
      float o0[4], o1[4], sm[4];
      const uint32_t ONE = 0x3f803f80u;
      hmma0(o0, vt[0][0], vt[0][1], vt[0][2], vt[0][3], pb[0], pb[1]);
      hmma0(o1, vt[2][0], vt[2][1], vt[2][2], vt[2][3], pb[0], pb[1]);
      hmma0(sm, ONE, ONE, ONE, ONE, pb[0], pb[1]);
      hmma(sm, ONE, ONE, ONE, ONE, pb[2], pb[3]);
      hmma(o0, vt[1][0], vt[1][1], vt[1][2], vt[1][3], pb[2], pb[3]);
      hmma(o1, vt[3][0], vt[3][1], vt[3][2], vt[3][3], pb[2], pb[3]);
      hmma_k8(sm, ONE, ONE, pb[4]);
      hmma_k8(o0, vm[0], vm[1], pb[4]);
      hmma_k8(o1, vm[2], vm[3], pb[4]);
#pragma unroll
      for (int i = 0; i < 3; i++) ldsm4t(wa[i], woa + i * 4096);
      __syncwarp();
      const float i0 = rcp(sm[0]), i1 = rcp(sm[1]);
      sts32(oa, pack2(o0[0] * i0, o0[1] * i1)); sts32(oa + 128, pack2(o0[2] * i0, o0[3] * i1));
      sts32(oa + 256, pack2(o1[0] * i0, o1[1] * i1)); sts32(oa + 384, pack2(o1[2] * i0, o1[3] * i1));
      TRACE(11);
      bar_sync<NB_C, 128>();
    } else {
      if (!isC) {
        constexpr uint64_t dQ = mkdesc(0x400 + R_QK, 128, 1024, 0), dK = mkdesc(0x400 + R_QK + 5120, 128, 1024, 0);
        float sc[16];
        zero_regs<16>(sc);
        WG_FENCE();
#pragma unroll
        for (int k = 0; k < 4; k++) wg_ss32<1>(sc, dK + k * 16, dQ + k * 16);
        WG_COMMIT();
        const uint32_t top = rank == 0 ? to2 : to1, e = L4 + R_P + w * 256;
        WG_WAIT(0);
        bar_sync<NB_X, 256>();
        if (elect_one()) load_chunk(sb + R_GB + w * 4096, s + 1, g2, bars + B_FB);
        reg_fence<16>(sc);
        if (w < 3) {
#pragma unroll
          for (int j = 0; j < 8; j++) {
            if ((j & 1) ? (j > 1 && (w == 0 || (w == 1 && j == 7))) : (j >= 4 || w != 1)) {
              const uint32_t t = pack2(sc[2 * j], sc[2 * j + 1]), o = (j >> 1) * 768 + (j & 1) * 128;
              st_async1(e + top + 3072 + o, t, bars + top + B_TS);
              sts32(e + o, t);
            }
          }
          __syncwarp();
          if (elect_one()) mbar_arrive(bars + B_TS);
        }
      } else {
        WG_WAIT(0);
        bar_sync<NB_X, 256>();
        if (elect_one()) load_chunk(sb + R_GB + w * 4096, s + 1, g2, bars + B_FB);
      }
      TRACE(8);
      mbar_wait(bars + B_FA, 1);
      TRACE(11);
    }
    if (has_wo) {
      float* rslot = SLOT(s);
      uint32_t ob[4][4];
      float c[3][4];
      if (WG == 1) {
#pragma unroll
        for (int i = 0; i < 3; i++) ldsm4t(wa[i], woa + i * 4096);
        bar_sync<NB_D, 256>();
      }
      ldsm4t(ob[0], oxa);
      __syncwarp();
#pragma unroll
      for (int k = 0; k < 8; k++) {
        uint32_t nx[3][4];
        if ((k & 1) == 0 && k < 6) { ldsm4t(ob[(k >> 1) + 1], oxa + ((k >> 1) + 1) * 512); __syncwarp(); }
#pragma unroll
        for (int i = 0; i < 3; i++) {
          const uint32_t* o = ob[k >> 1] + (k & 1) * 2;
          if (k < 7) { ldsm4t(nx[i], woa + i * 4096 + (k + 1) * 512); if (i == 2) __syncwarp(); }
          if (k == 0) hmma0(c[i], wa[i][0], wa[i][1], wa[i][2], wa[i][3], o[0], o[1]);
          else hmma(c[i], wa[i][0], wa[i][1], wa[i][2], wa[i][3], o[0], o[1]);
#pragma unroll
          for (int q = 0; q < 4; q++) if (k < 7) wa[i][q] = nx[i][q];
        }
        if (k == ND_K && WG == 0) bar_arrive<NB_D, 256>();
      }
      const float* cv = &c[0][0];
      uint32_t r[6];
#pragma unroll
      for (int j = 0; j < 6; j++) r[j] = pack2(cv[2 * j], cv[2 * j + 1]);
      asm volatile("red.relaxed.gpu.global.add.noftz.v4.bf16x2 [%0], {%1, %2, %3, %7};\n"
                   "red.relaxed.gpu.global.add.noftz.v4.bf16x2 [%0+1024], {%4, %5, %6, %7};"
                   :: "l"(rslot), "r"(r[0]), "r"(r[1]), "r"(r[2]), "r"(r[3]), "r"(r[4]), "r"(r[5]), "r"(0x3f800000) : "memory");
    } else {
      bar_arrive<NB_D, 256>();
      if ((s & 3) == 0) {
        fence_gpu();
        if (s > 0 && elect_one()) red_add_u32(&g_flags[FL_ATT + 2 * (s - 4)], 1);
      }
      if (rank == 0 || head < 16)
        reinterpret_cast<uint4*>(g_slot)[((s + ZS) & 3) * 3072 + ((s + ZS) & 4) * 8 + rank * 2048 + head * 64 + opaque32(lane)] = make_uint4(0, 0, 0, 0);
      if (HPF && head < 16 && rank == 0 && s + HPF < NSEG && elect_one())
        asm volatile("cp.async.bulk.prefetch.L2.global [%0], 4096;" :: "l"(g_h + (size_t)((s + HPF) * 16 + head) * 4096) : "memory");
    }
    const uint32_t t_red = clk32();
    uint32_t v[8];
    const float* slot = SLOT(s);
    TRACE(13);
    if (WG == 0) {
      if (!isC) {
        token_softmax(par);
      }
      if (P1K < 0) { while (clk32() - t_red < POLL_DELAY) {} load_red(v, slot); }
      bar_sync<NB_E, 256>();
    } else {
      mbar_wait(bars + B_FB, 1);
    }
    TRACE(14);
    float ao[16];
    uint32_t v2[8];
    if (WG == 1) zero_regs<16>(ao);
    WG_FENCE();
#pragma unroll
    for (int k = 0; k < 32; k++) {
      if (WG == 0 && k == P1K) { sched_fence(head, 101); load_red(v, slot); }
      if (WG == 0 && k == P2K) { sched_fence(head, 102); load_red(v2, slot); }
      if (WG == 0 && k == 16) WG_COMMIT();
      wg_rs32<1>(acc, W[16 + k][0], W[16 + k][1], W[16 + k][2], W[16 + k][3], dsc.tok[k]);
    }
    WG_COMMIT();
    TRACE(12);
    if (WG == 1) {
      if (!isC) {
        constexpr uint64_t dP = mkdesc(0x400 + R_P, 128, 768, 0);
        const uint64_t dV = mkdesc(0x400 + R_VT, 128, 512, 0) + rank * 256, dM = mkdesc(0x400 + R_VM, 0, 128, 0) + rank * 64;
        bar_sync<NB_P, 256>();
        WG_FENCE();
        wg_ss32<0>(ao, dV, dP); wg_ss32<0>(ao, dV + 16, dP + 16); wg_ss32<0>(ao, dM, dP + 32);
        WG_COMMIT();
      }
      bar_arrive<NB_E, 256>();
      if (elect_one()) mbar_expect(bars + B_XS + 8 * w, arm_bytes);
      while (clk32() - t_red < POLL_DELAY1) {}
      load_red(v, slot);
      bar_arrive<NB_W0, 128>();
    } else {
      WG_WAIT(1);
      bar_arrive<NB_F, 256>();
      sched_fence(head, 100);
      v[3] = opaque32(v[3]);
      uint32_t tries = 0;
      if (P2K < 0) tries = finish_red(v, slot);
      else if (__builtin_expect(!red_done(v), 0)) {
#pragma unroll
        for (int j = 0; j < 8; j++) v[j] = v2[j];
        tries = 1;
        while (!red_done(v)) { if (++tries > 20000000u) __trap(); load_red(v, slot); }
      }
      forward(std::integral_constant<int, 0>(), v, s, tries);
      if (P2K >= 0) asm volatile("" :: "r"(v2[0]), "r"(v2[1]), "r"(v2[2]), "r"(v2[3]), "r"(v2[4]), "r"(v2[5]), "r"(v2[6]), "r"(v2[7]));
      TRACE(16);
    }
    WG_WAIT(0);
    reg_fence<16>(acc);
    if (WG == 0) bar_arrive<NB_G, 256>();
    TRACE(15);
    {
      uint32_t pq[8];
#pragma unroll
      for (int j = 0; j < 8; j++) pq[j] = pack2(acc[2 * j], acc[2 * j + 1]);
      if (WG == 1) {
        reg_fence<16>(ao);
#pragma unroll
        for (int j = 0; j < 8; j++) pk[j] = pack2(ao[2 * j], ao[2 * j + 1]);
      }
      if (!isC) {
        const uint32_t q = L4 + w * 256 + R_QK + WG * 5120;
#pragma unroll
        for (int j = 0; j < 8; j++) sts32(q + (j >> 1) * 1024 + (j & 1) * 128, pq[j]);
        if (WG == 1 && !ATT_LATE) store_att(s);
      } else {
        const uint32_t a = LV + warp * 1024;
        stsm4(a, pq); stsm4(a + 256, pq + 4);
      }
    }
    TRACE(17);
    if (WG == 1) {
      auto refill = [&]() {
        bar_sync<NB_F, 256>();
        if (s < NSEG - 2 && elect_one()) load_chunk(sb + R_GA + w * 4096, s + 2, 12 + w, bars + B_FA);
      };
      if (RF_FIRST) refill();
      if (has_wo) { v[3] = opaque32(v[3]); const uint32_t tries = finish_red(v, slot); forward(std::integral_constant<int, 1>(), v, s, tries); }
      if (!RF_FIRST) refill();
      TRACE(16);
    }
    if (isC && V_FENCE) { fence_async_smem(); __syncwarp(); }
    TRACE(18);
  }
  {
    constexpr uint32_t par = (NSEG - 1) & 1;
    if (WG == 1) {
      bar_sync<NB_G, 256>();
      if (ATT_LATE && !isC) store_att(NSEG - 2);
    }
    const bool proj = WG == 1 || isC;
    if (proj) mem_proj(par, [&](int i) { if (i == CX_I && isC) send_vt(); if (i == 15) zero_regs<16>(acc); });
    else fence_async_smem();
    bar_sync<NB_H, 256>();
    if (proj) {
      WG_FENCE();
#pragma unroll
      for (int k = 0; k < 16; k++) wg_ss40<0>(acc, dsc.tail_a[WG * 16 + k], dsc.tail_b[k]);
      WG_COMMIT();
      const uint32_t a = opaque32(L4 + w * 256 + (isC ? WG * 1024 + R_VM : R_QK + 4096 + WG * 5120));
      WG_WAIT(0);
      reg_fence<20>(acc);
      const uint32_t p0 = pack2(acc[16], acc[17]), p1 = pack2(acc[18], acc[19]);
      if (isC) {
        st_async1(a + to1, p0, bars + B_VM + to1); st_async1(a + to1 + 128, p1, bars + B_VM + to1);
        st_async1(a + to2, p0, bars + B_VM + to2); st_async1(a + to2 + 128, p1, bars + B_VM + to2);
      } else { sts32(a, p0); sts32(a + 128, p1); }
    }
    if (!isC) {
      if (WG == 1) {
        fence_async_smem();
        bar_sync<NB_C, 128>();
        constexpr uint64_t dQ = mkdesc(0x400 + R_QK, 128, 1024, 0), dK = mkdesc(0x400 + R_QK + 5120, 128, 1024, 0);
        float sc[16];
        zero_regs<16>(sc);
        WG_FENCE();
#pragma unroll
        for (int k = 0; k < 4; k++) wg_ss32<1>(sc, dK + k * 16, dQ + k * 16);
        WG_COMMIT();
        const uint32_t top = rank == 0 ? to2 : to1, e = L4 + R_P + w * 256;
        WG_WAIT(0);
        reg_fence<16>(sc);
        if (w < 3) {
#pragma unroll
          for (int j = 0; j < 8; j++) {
            if ((j & 1) ? (j > 1 && (w == 0 || (w == 1 && j == 7))) : (j >= 4 || w != 1)) {
              const uint32_t t = pack2(sc[2 * j], sc[2 * j + 1]), o = (j >> 1) * 768 + (j & 1) * 128;
              st_async1(e + top + 3072 + o, t, bars + top + B_TS);
              sts32(e + o, t);
            }
          }
          __syncwarp();
          if (elect_one()) mbar_arrive(bars + B_TS);
        }
        constexpr uint64_t dP = mkdesc(0x400 + R_P, 128, 768, 0);
        const uint64_t dV = mkdesc(0x400 + R_VT, 128, 512, 0) + rank * 256, dM = mkdesc(0x400 + R_VM, 0, 128, 0) + rank * 64;
        float ao[16];
        zero_regs<16>(ao);
        mbar_wait(bars + B_VT, par);
        mbar_wait(bars + B_VM, par);
        bar_sync<NB_P, 256>();
        WG_FENCE();
        wg_ss32<0>(ao, dV, dP); wg_ss32<0>(ao, dV + 16, dP + 16); wg_ss32<0>(ao, dM, dP + 32);
        WG_COMMIT();
        WG_WAIT(0);
        reg_fence<16>(ao);
#pragma unroll
        for (int j = 0; j < 8; j++) pk[j] = pack2(ao[2 * j], ao[2 * j + 1]);
        store_att(NSEG - 1);
      } else {
        token_softmax(par);
      }
    }
  }
#undef L16
#undef L8
#undef L4
#undef SLOT
#undef LV
}

__global__ void __cluster_dims__(3, 1, 1) __launch_bounds__(256, 1)
kernel_R(const __grid_constant__ CUtensorMap tmq, const __grid_constant__ CUtensorMap tmk, const __grid_constant__ CUtensorMap tmv,
         const __grid_constant__ CUtensorMap tmo, const __grid_constant__ CUtensorMap tmm, const __nv_bfloat16* __restrict__ x,
         const __nv_bfloat16* __restrict__ mem0, const __nv_bfloat16* __restrict__ cvec, const __grid_constant__ RDesc dsc) {
  extern __shared__ __align__(1024) uint8_t smem[];
  const uint32_t sb = smem_u32(smem);
  uint32_t rank; asm("mov.u32 %0, %%cluster_ctarank;" : "=r"(rank));
  rank = __shfl_sync(0xffffffffu, rank, 0);
  const int cta = blockIdx.x, head = __shfl_sync(0xffffffffu, cta / 3, 0);
  const int tid = threadIdx.x, lane = tid & 31;
  const int warp = __shfl_sync(0xffffffffu, tid >> 5, 0);
  const int wg = warp >> 2, w = warp & 3;
  const uint32_t bars = sb + R_BAR;
  const CUtensorMap* tmw = rank == 2 ? &tmv : (wg == 0 ? &tmq : &tmk);
  const int fcol = head * 128 + (rank == 2 ? wg * 64 : (int)rank * 64);

  asm volatile("griddepcontrol.launch_dependents;");
  uint32_t W[48][4];
  {
    if (sb != (rank << 24) + 0x400) __trap();
    if (tid == 0) {
      sts64(bars + 248, rank, head);
      mbar_init(bars + B_MB, 4); mbar_init(bars + B_MB + 8, 1); mbar_init(bars + B_MB + 16, 1); mbar_init(bars + B_MB + 24, SELF_STAS ? 1 : rank == 2 ? 5 : 4);
      for (int i = B_XS; i <= B_X; i += 8) mbar_init(bars + i, i == B_FA || i == B_FB || (i == B_TS && rank < 2) ? 4 : 1);
      asm volatile("fence.mbarrier_init.release.cluster;" ::: "memory");
      fence_async_smem();
    }
    __syncthreads();
    asm volatile("barrier.cluster.arrive.relaxed.aligned;" ::: "memory");
    TS(0);
    const int nwm = rank == 0 ? 6 : 5, wm0 = rank == 0 ? 0 : 5 * rank + 1, nrg = cta < 64 ? 3 : 2;
    if (elect_one()) {
      if (warp == 0) { mbar_expect(bars + B_WM, nwm * 8192); mbar_expect(bars + B_X, nrg * 16384); }
      if (warp < nwm) tma2d_p(sb + R_GA + warp * 8192, &tmm, head * 64, (wm0 + warp) * 64, bars + B_WM, POL_RW);
#pragma unroll 1
      for (int r = 0; r < nrg; r++) bulk_g2s(sb + R_TAIL + (r * 8 + warp) * 2064, x + (size_t)((cta + 96 * r) * 8 + warp) * D_, 2048, bars + B_X);
      if (w == 0) mbar_expect(bars + B_STG + wg * 16, 49152);
      if (w < 2) tma2d_p(sb + R_WO + wg * 49152 + w * 8192, tmw, fcol, rot_chunk(w, rank) * 64, bars + B_STG + wg * 16, POL_RW);
    }
    float* scr = reinterpret_cast<float*>(smem + R_VT);
#pragma unroll 1
    for (int i = tid; i < nwm * 64; i += 256) {
      const float c = __bfloat162float(cvec[wm0 * 64 + i]);
      scr[i] = __bfloat162float(__float2bfloat16(c / (1.f + __expf(-c))));
    }
    if (tid < 128) {
      uint32_t e[4] = {0u, 0u, 0u, 0u};
      if (cta >= 72 && (tid & 32)) {
        const uint16_t* mp = reinterpret_cast<const uint16_t*>(mem0) + 2 * (lane & 3) * D_ + (lane >> 2);
#pragma unroll
        for (int q = 0; q < 3; q++) {
          const int n = 3 * (tid >> 6) + q, col = wo_tile(3 * (cta & 7) + (n >> 1), (cta - 72) >> 3) * 16 + 8 * (n & 1);
          e[q] = mp[col] | (uint32_t)mp[col + D_] << 16;
        }
        e[3] = 0x42000000u;
      }
      reinterpret_cast<uint4*>(g_slot)[cta * 128 + tid] = make_uint4(e[0], e[1], e[2], e[3]);
    }
    __syncthreads();
    TS(1);
    mbar_wait_safe(bars + B_WM, 0);
    if (elect_one()) tma2d_p(sb + R_WO + wg * 49152 + (2 + w) * 8192, tmw, fcol, rot_chunk(2 + w, rank) * 64, bars + B_STG + wg * 16, POL_RW);
    {
      float a[8];
#pragma unroll
      for (int j = 0; j < 8; j++) a[j] = 0.f;
#pragma unroll 2
      for (int i = 0; i < 2 * nwm; i++) {
        uint32_t u[4];
        lds128(u, sb + R_GA + i * 4096 + tid * 16);
        const float sc = scr[i * 32 + (tid >> 3)];
#pragma unroll
        for (int j = 0; j < 4; j++) { a[2 * j] += sc * bf_lo(u[j]); a[2 * j + 1] += sc * bf_hi(u[j]); }
      }
#pragma unroll
      for (int j = 0; j < 8; j++) { a[j] += __shfl_xor_sync(0xffffffffu, a[j], 8); a[j] += __shfl_xor_sync(0xffffffffu, a[j], 16); }
      if (lane < 8) {
        sts128(sb + R_VT + 1536 + warp * 256 + lane * 32, __float_as_uint(a[0]), __float_as_uint(a[1]), __float_as_uint(a[2]), __float_as_uint(a[3]));
        sts128(sb + R_VT + 1552 + warp * 256 + lane * 32, __float_as_uint(a[4]), __float_as_uint(a[5]), __float_as_uint(a[6]), __float_as_uint(a[7]));
      }
    }
    __syncthreads();
    TS(2);
    asm volatile("barrier.cluster.wait.aligned;\nbarrier.cluster.arrive.relaxed.aligned;" ::: "memory");
    if (warp == 7) {
      float t0 = 0.f, t1 = 0.f;
#pragma unroll
      for (int i = 0; i < 8; i++) { float t[2]; lds64f(t, sb + R_VT + 1536 + i * 256 + lane * 8); t0 += t[0]; t1 += t[1]; }
      reinterpret_cast<float2*>(g_modp + rank * 2048 + head * 64)[lane] = make_float2(t0, t1);
      fence_gpu();
      __syncwarp();
      if (lane == 0) red_add_u32(&g_flags[FL_S1], 1);
      __syncwarp();
    }
    mbar_wait_safe(bars + B_X, 0);
#pragma unroll 1
    for (int r = 0; r < nrg; r++) {
      float f[32];
#pragma unroll
      for (int i = 0; i < 4; i++) {
        uint32_t u[4];
        lds128(u, sb + R_TAIL + (r * 8 + warp) * 2064 + i * 512 + lane * 16);
#pragma unroll
        for (int j = 0; j < 4; j++) { f[8 * i + 2 * j] = bf_lo(u[j]); f[8 * i + 2 * j + 1] = bf_hi(u[j]); }
      }
      float t = 0.f;
#pragma unroll
      for (int i = 0; i < 32; i++) t += f[i];
#pragma unroll
      for (int o = 1; o < 32; o <<= 1) t += __shfl_xor_sync(0xffffffffu, t, o);
      const float mean = t * (1.f / D_);
      t = 0.f;
#pragma unroll
      for (int i = 0; i < 32; i++) t = fmaf(f[i] - mean, f[i] - mean, t);
#pragma unroll
      for (int o = 1; o < 32; o <<= 1) t += __shfl_xor_sync(0xffffffffu, t, o);
      const float rstd = rsqrtf(t * (1.f / D_) + 1e-5f);
      if (lane == 0) sts64(sb + R_VT + 3584 + (r * 8 + warp) * 8, __float_as_uint(rstd), __float_as_uint(-mean * rstd));
    }
    TS(3);
    if (w < PF1 && elect_one()) tma2d_prefetch_p(tmw, fcol, rot_chunk(6 + w, rank) * 64, POL_RW);
    if (tid == 0) wait_flag(&g_flags[FL_S1], 96);
    __syncthreads();
    TS(4);
    {
      float4 p[6];
#pragma unroll
      for (int i = 0; i < 6; i++) p[i] = __ldcg(reinterpret_cast<const float4*>(g_modp + (i >> 1) * 2048) + 2 * tid + (i & 1));
      if (w < PF2 && elect_one()) tma2d_prefetch_p(tmw, fcol, (9 + w) * 64, POL_RW);
      sts128(sb + R_VT + 5120 + tid * 16, pack2(p[0].x + p[2].x + p[4].x, p[0].y + p[2].y + p[4].y), pack2(p[0].z + p[2].z + p[4].z, p[0].w + p[2].w + p[4].w),
             pack2(p[1].x + p[3].x + p[5].x, p[1].y + p[3].y + p[5].y), pack2(p[1].z + p[3].z + p[5].z, p[1].w + p[3].w + p[5].w));
    }
    __syncthreads();
#pragma unroll 2
    for (int it = 0; it < 4 * nrg; it++) {
      const int r = it >> 2, rg = cta + 96 * r, c = 16 * warp + (lane >> 3) + 4 * (it & 3);
      uint32_t a[4], b[4], u[4], o[4];
      float t[2];
      lds128(u, sb + R_TAIL + (r * 8 + (lane & 7)) * 2064 + c * 16);
      lds128(a, sb + R_VT + 5120 + c * 16); lds128(b, sb + R_VT + 7168 + c * 16);
      lds64f(t, sb + R_VT + 3584 + (r * 8 + (lane & 7)) * 8);
#pragma unroll
      for (int j = 0; j < 4; j++)
        o[j] = pack2(fmaf(fmaf(bf_lo(u[j]), t[0], t[1]), 1.f + bf_lo(b[j]), bf_lo(a[j])), fmaf(fmaf(bf_hi(u[j]), t[0], t[1]), 1.f + bf_hi(b[j]), bf_hi(a[j])));
      *reinterpret_cast<uint4*>(g_h + (size_t)(rg >> 2) * 65536 + (lane & 7) * 16 + (c & 7) * 128 +
                                (c < 96 ? (c >> 3) * 4096 + (rg & 3) * 1024 : 49152 + (rg & 3) * 4096 + ((c >> 3) - 12) * 1024)) =
          make_uint4(o[0], o[1], o[2], o[3]);
    }
    TS(5);
    __syncthreads();
    TS(6);
    if (w < PF3 && elect_one()) tma2d_p(sb + R_TAIL + warp * 8192, tmw, fcol, 768 + w * 64, bars + B_TAIL, POL_RW);
    if (warp == 3 && lane == 0) { fence_gpu(); red_add_u32(&g_flags[FL_S2], 1); }
    __syncwarp();
    asm volatile("barrier.cluster.wait.aligned;" ::: "memory");
    forward_initial(sb, rank, wg, w, lane);

    const uint32_t a0 = opaque32(sb + R_WO + wg * 49152 + ((lane >> 4) * 8 + (lane & 7)) * 128 + (((2 * w + ((lane >> 3) & 1)) ^ (lane & 7)) << 4));
    mbar_wait_safe(bars + B_STG + wg * 16, 0);
    TS(7);
#pragma unroll
    for (int i = 0; i < 24; i++) ldsm4t(W[i], a0 + i * 2048);
    auto second_wave = [&]() {
      if (w == 0) mbar_expect(bars + B_STG + wg * 16 + 8, 49152);
#pragma unroll 1
      for (int c = w; c < 6; c += 4) tma2d_p(sb + R_WO + wg * 49152 + c * 8192, tmw, fcol, rot_chunk(6 + c, rank) * 64, bars + B_STG + wg * 16 + 8, POL_RW);
      if (warp == 0) mbar_expect(bars + B_TAIL, 65536);
      if (w >= PF3) tma2d_p(sb + R_TAIL + warp * 8192, tmw, fcol, 768 + w * 64, bars + B_TAIL, POL_RW);
#pragma unroll 1
      for (int i = warp; i < PF4; i += 8) tma2d_prefetch(&tmo, 16 * wo_tile(i, rank), head * 128);
    };
    if (S2E) { __syncthreads(); if (elect_one()) second_wave(); }
    if (tid == 0) wait_flag(&g_flags[FL_S2], 96);
    __syncthreads();
    asm volatile("fence.proxy.async.global;" ::: "memory");
    if (elect_one()) {
      if (warp == 0) mbar_expect(bars + B_X, 8 * 4096);
      bulk_g2s(sb + (wg == 0 ? R_GB : R_GA) + w * 4096, g_h + (size_t)rot_chunk(warp, rank) * 4096, 4096, bars + B_X);
      if (!S2E) second_wave();
    }
    TS(8);
    float acc[20];
    mbar_wait_safe(bars + B_X, 1);
    WG_FENCE();
    wg_rs40<0>(acc, W[0], dsc.tok[16]);
#pragma unroll
    for (int k = 1; k < 24; k++) wg_rs40<1>(acc, W[k], dsc.tok[k < 16 ? 16 + k : k - 16]);
    WG_COMMIT();
    WG_WAIT(0);
    reg_fence<20>(acc);
    __syncthreads();
    if (elect_one()) {
      if (warp == 0) mbar_expect(bars + B_X, 4 * 4096);
      if (wg == 0) bulk_g2s(sb + R_GB + w * 4096, g_h + (size_t)rot_chunk(8 + w, rank) * 4096, 4096, bars + B_X);
    }
    mbar_wait_safe(bars + B_STG + wg * 16 + 8, 0);
    TS(9);
#pragma unroll
    for (int i = 0; i < 24; i++) ldsm4t(W[24 + i], a0 + i * 2048);
    __syncthreads();
    asm volatile("barrier.cluster.arrive.relaxed.aligned;" ::: "memory");
    if (elect_one()) {
      const int n = rank == 2 ? 22 : 21;
      if (warp == 0) mbar_expect(bars + B_WO, n * 4096);
#pragma unroll 1
      for (int i = warp; i < n; i += 8) tma2d(sb + R_WO + i * 4096, &tmo, 16 * wo_tile(i, rank), head * 128, bars + B_WO);
    }
    sts32(sb + R_P + warp * 768 + 640 + lane * 4, wg == 0 ? 0u : 0xff80ff80u);
    WG_FENCE();
#pragma unroll
    for (int k = 24; k < 32; k++) wg_rs40<1>(acc, W[k], dsc.tok[k - 16]);
    WG_COMMIT();
    mbar_wait_safe(bars + B_X, 0);
    WG_FENCE();
#pragma unroll
    for (int k = 32; k < 48; k++) wg_rs40<1>(acc, W[k], dsc.tok[k - 16]);
    WG_COMMIT();
    WG_WAIT(1);
    __syncthreads();
    if (elect_one()) {
      if (warp == 0) mbar_expect(bars + B_X, 4 * 4096);
      if (wg == 0) bulk_g2s(sb + R_GA + w * 4096, g_h + (size_t)(12 + w) * 4096, 4096, bars + B_X);
    }
    mbar_wait_safe(bars + B_TAIL, 0);
    mbar_wait_safe(bars + B_X, 1);
    WG_FENCE();
#pragma unroll
    for (int k = 0; k < 16; k++) wg_ss40<0>(acc, dsc.tail_a[wg * 16 + k], dsc.tail_b[k]);
    WG_COMMIT();
    WG_WAIT(0);
    reg_fence<20>(acc);
    {
      uint32_t pq[8];
#pragma unroll
      for (int j = 0; j < 8; j++) pq[j] = pack2(acc[2 * j], acc[2 * j + 1]);
      if (rank != 2) {
        const uint32_t q = sb + lane * 4 + w * 256 + R_QK + wg * 5120;
#pragma unroll
        for (int j = 0; j < 8; j++) sts32(q + (j >> 1) * 1024 + (j & 1) * 128, pq[j]);
      } else {
        const uint32_t a = sb + R_VT + ((lane >> 3) & 1) * 512 + (lane >> 4) * 128 + (lane & 7) * 16 + warp * 1024;
        stsm4(a, pq); stsm4(a + 256, pq + 4);
        fence_async_smem();
      }
    }
    __syncthreads();
    if (wg == 1 && elect_one()) {
      load_chunk(sb + R_GA + w * 4096, 1, 12 + w, bars + B_FA);
      mbar_expect(bars + B_XS + 8 * w, arm_size(w, rank == 2));
    }
    asm volatile("barrier.cluster.wait.aligned;" ::: "memory");
  }
  uint32_t rh[2];
  lds64(rh, bars + 248);
  rh[0] = __shfl_sync(0xffffffffu, rh[0], 0); rh[1] = __shfl_sync(0xffffffffu, rh[1], 0);
    if (wg == 0) r_main<0>(W, dsc, rh[1], rh[0], lane, w);
  else r_main<1>(W, dsc, rh[1], rh[0], lane, w);
  __syncthreads();
  if (rank < 2 && threadIdx.x == 0) { fence_gpu(); red_add_u32(&g_flags[FL_ATT + 8 * 15], 1); }
  asm volatile("barrier.cluster.arrive.release.aligned;\nbarrier.cluster.wait.acquire.aligned;" ::: "memory");
}

template <int TA> __device__ __forceinline__ void wg_ss256(float* d, uint64_t a, uint64_t b) {
  asm volatile("wgmma.mma_async.sync.aligned.m64n256k16.f32.bf16.bf16 {%0,%1,%2,%3,%4,%5,%6,%7,%8,%9,%10,%11,%12,%13,%14,%15,%16,%17,%18,%19,%20,%21,%22,%23,%24,%25,%26,%27,%28,%29,%30,%31,%32,%33,%34,%35,%36,%37,%38,%39,%40,%41,%42,%43,%44,%45,%46,%47,%48,%49,%50,%51,%52,%53,%54,%55,%56,%57,%58,%59,%60,%61,%62,%63,%64,%65,%66,%67,%68,%69,%70,%71,%72,%73,%74,%75,%76,%77,%78,%79,%80,%81,%82,%83,%84,%85,%86,%87,%88,%89,%90,%91,%92,%93,%94,%95,%96,%97,%98,%99,%100,%101,%102,%103,%104,%105,%106,%107,%108,%109,%110,%111,%112,%113,%114,%115,%116,%117,%118,%119,%120,%121,%122,%123,%124,%125,%126,%127}, %128, %129, 1, 1, 1, %130, 1;"
               : "+f"(d[0]), "+f"(d[1]), "+f"(d[2]), "+f"(d[3]), "+f"(d[4]), "+f"(d[5]), "+f"(d[6]), "+f"(d[7]),
                 "+f"(d[8]), "+f"(d[9]), "+f"(d[10]), "+f"(d[11]), "+f"(d[12]), "+f"(d[13]), "+f"(d[14]), "+f"(d[15]),
                 "+f"(d[16]), "+f"(d[17]), "+f"(d[18]), "+f"(d[19]), "+f"(d[20]), "+f"(d[21]), "+f"(d[22]), "+f"(d[23]),
                 "+f"(d[24]), "+f"(d[25]), "+f"(d[26]), "+f"(d[27]), "+f"(d[28]), "+f"(d[29]), "+f"(d[30]), "+f"(d[31]),
                 "+f"(d[32]), "+f"(d[33]), "+f"(d[34]), "+f"(d[35]), "+f"(d[36]), "+f"(d[37]), "+f"(d[38]), "+f"(d[39]),
                 "+f"(d[40]), "+f"(d[41]), "+f"(d[42]), "+f"(d[43]), "+f"(d[44]), "+f"(d[45]), "+f"(d[46]), "+f"(d[47]),
                 "+f"(d[48]), "+f"(d[49]), "+f"(d[50]), "+f"(d[51]), "+f"(d[52]), "+f"(d[53]), "+f"(d[54]), "+f"(d[55]),
                 "+f"(d[56]), "+f"(d[57]), "+f"(d[58]), "+f"(d[59]), "+f"(d[60]), "+f"(d[61]), "+f"(d[62]), "+f"(d[63]),
                 "+f"(d[64]), "+f"(d[65]), "+f"(d[66]), "+f"(d[67]), "+f"(d[68]), "+f"(d[69]), "+f"(d[70]), "+f"(d[71]),
                 "+f"(d[72]), "+f"(d[73]), "+f"(d[74]), "+f"(d[75]), "+f"(d[76]), "+f"(d[77]), "+f"(d[78]), "+f"(d[79]),
                 "+f"(d[80]), "+f"(d[81]), "+f"(d[82]), "+f"(d[83]), "+f"(d[84]), "+f"(d[85]), "+f"(d[86]), "+f"(d[87]),
                 "+f"(d[88]), "+f"(d[89]), "+f"(d[90]), "+f"(d[91]), "+f"(d[92]), "+f"(d[93]), "+f"(d[94]), "+f"(d[95]),
                 "+f"(d[96]), "+f"(d[97]), "+f"(d[98]), "+f"(d[99]), "+f"(d[100]), "+f"(d[101]), "+f"(d[102]), "+f"(d[103]),
                 "+f"(d[104]), "+f"(d[105]), "+f"(d[106]), "+f"(d[107]), "+f"(d[108]), "+f"(d[109]), "+f"(d[110]), "+f"(d[111]),
                 "+f"(d[112]), "+f"(d[113]), "+f"(d[114]), "+f"(d[115]), "+f"(d[116]), "+f"(d[117]), "+f"(d[118]), "+f"(d[119]),
                 "+f"(d[120]), "+f"(d[121]), "+f"(d[122]), "+f"(d[123]), "+f"(d[124]), "+f"(d[125]), "+f"(d[126]), "+f"(d[127])
               : "l"(a), "l"(b), "n"(TA));
}
template <int TA> __device__ __forceinline__ void wg_ss128(float* d, uint64_t a, uint64_t b) {
  asm volatile("wgmma.mma_async.sync.aligned.m64n128k16.f32.bf16.bf16 {%0,%1,%2,%3,%4,%5,%6,%7,%8,%9,%10,%11,%12,%13,%14,%15,%16,%17,%18,%19,%20,%21,%22,%23,%24,%25,%26,%27,%28,%29,%30,%31,%32,%33,%34,%35,%36,%37,%38,%39,%40,%41,%42,%43,%44,%45,%46,%47,%48,%49,%50,%51,%52,%53,%54,%55,%56,%57,%58,%59,%60,%61,%62,%63}, %64, %65, 1, 1, 1, %66, 1;"
               : "+f"(d[0]), "+f"(d[1]), "+f"(d[2]), "+f"(d[3]), "+f"(d[4]), "+f"(d[5]), "+f"(d[6]), "+f"(d[7]),
                 "+f"(d[8]), "+f"(d[9]), "+f"(d[10]), "+f"(d[11]), "+f"(d[12]), "+f"(d[13]), "+f"(d[14]), "+f"(d[15]),
                 "+f"(d[16]), "+f"(d[17]), "+f"(d[18]), "+f"(d[19]), "+f"(d[20]), "+f"(d[21]), "+f"(d[22]), "+f"(d[23]),
                 "+f"(d[24]), "+f"(d[25]), "+f"(d[26]), "+f"(d[27]), "+f"(d[28]), "+f"(d[29]), "+f"(d[30]), "+f"(d[31]),
                 "+f"(d[32]), "+f"(d[33]), "+f"(d[34]), "+f"(d[35]), "+f"(d[36]), "+f"(d[37]), "+f"(d[38]), "+f"(d[39]),
                 "+f"(d[40]), "+f"(d[41]), "+f"(d[42]), "+f"(d[43]), "+f"(d[44]), "+f"(d[45]), "+f"(d[46]), "+f"(d[47]),
                 "+f"(d[48]), "+f"(d[49]), "+f"(d[50]), "+f"(d[51]), "+f"(d[52]), "+f"(d[53]), "+f"(d[54]), "+f"(d[55]),
                 "+f"(d[56]), "+f"(d[57]), "+f"(d[58]), "+f"(d[59]), "+f"(d[60]), "+f"(d[61]), "+f"(d[62]), "+f"(d[63])
               : "l"(a), "l"(b), "n"(TA));
}
template <int TA> __device__ __forceinline__ void wg_ss256_first(float* d, uint64_t a, uint64_t b) {
  asm volatile("wgmma.mma_async.sync.aligned.m64n256k16.f32.bf16.bf16 {%0,%1,%2,%3,%4,%5,%6,%7,%8,%9,%10,%11,%12,%13,%14,%15,%16,%17,%18,%19,%20,%21,%22,%23,%24,%25,%26,%27,%28,%29,%30,%31,%32,%33,%34,%35,%36,%37,%38,%39,%40,%41,%42,%43,%44,%45,%46,%47,%48,%49,%50,%51,%52,%53,%54,%55,%56,%57,%58,%59,%60,%61,%62,%63,%64,%65,%66,%67,%68,%69,%70,%71,%72,%73,%74,%75,%76,%77,%78,%79,%80,%81,%82,%83,%84,%85,%86,%87,%88,%89,%90,%91,%92,%93,%94,%95,%96,%97,%98,%99,%100,%101,%102,%103,%104,%105,%106,%107,%108,%109,%110,%111,%112,%113,%114,%115,%116,%117,%118,%119,%120,%121,%122,%123,%124,%125,%126,%127}, %128, %129, 0, 1, 1, %130, 1;"
               : "=f"(d[0]), "=f"(d[1]), "=f"(d[2]), "=f"(d[3]), "=f"(d[4]), "=f"(d[5]), "=f"(d[6]), "=f"(d[7]),
                 "=f"(d[8]), "=f"(d[9]), "=f"(d[10]), "=f"(d[11]), "=f"(d[12]), "=f"(d[13]), "=f"(d[14]), "=f"(d[15]),
                 "=f"(d[16]), "=f"(d[17]), "=f"(d[18]), "=f"(d[19]), "=f"(d[20]), "=f"(d[21]), "=f"(d[22]), "=f"(d[23]),
                 "=f"(d[24]), "=f"(d[25]), "=f"(d[26]), "=f"(d[27]), "=f"(d[28]), "=f"(d[29]), "=f"(d[30]), "=f"(d[31]),
                 "=f"(d[32]), "=f"(d[33]), "=f"(d[34]), "=f"(d[35]), "=f"(d[36]), "=f"(d[37]), "=f"(d[38]), "=f"(d[39]),
                 "=f"(d[40]), "=f"(d[41]), "=f"(d[42]), "=f"(d[43]), "=f"(d[44]), "=f"(d[45]), "=f"(d[46]), "=f"(d[47]),
                 "=f"(d[48]), "=f"(d[49]), "=f"(d[50]), "=f"(d[51]), "=f"(d[52]), "=f"(d[53]), "=f"(d[54]), "=f"(d[55]),
                 "=f"(d[56]), "=f"(d[57]), "=f"(d[58]), "=f"(d[59]), "=f"(d[60]), "=f"(d[61]), "=f"(d[62]), "=f"(d[63]),
                 "=f"(d[64]), "=f"(d[65]), "=f"(d[66]), "=f"(d[67]), "=f"(d[68]), "=f"(d[69]), "=f"(d[70]), "=f"(d[71]),
                 "=f"(d[72]), "=f"(d[73]), "=f"(d[74]), "=f"(d[75]), "=f"(d[76]), "=f"(d[77]), "=f"(d[78]), "=f"(d[79]),
                 "=f"(d[80]), "=f"(d[81]), "=f"(d[82]), "=f"(d[83]), "=f"(d[84]), "=f"(d[85]), "=f"(d[86]), "=f"(d[87]),
                 "=f"(d[88]), "=f"(d[89]), "=f"(d[90]), "=f"(d[91]), "=f"(d[92]), "=f"(d[93]), "=f"(d[94]), "=f"(d[95]),
                 "=f"(d[96]), "=f"(d[97]), "=f"(d[98]), "=f"(d[99]), "=f"(d[100]), "=f"(d[101]), "=f"(d[102]), "=f"(d[103]),
                 "=f"(d[104]), "=f"(d[105]), "=f"(d[106]), "=f"(d[107]), "=f"(d[108]), "=f"(d[109]), "=f"(d[110]), "=f"(d[111]),
                 "=f"(d[112]), "=f"(d[113]), "=f"(d[114]), "=f"(d[115]), "=f"(d[116]), "=f"(d[117]), "=f"(d[118]), "=f"(d[119]),
                 "=f"(d[120]), "=f"(d[121]), "=f"(d[122]), "=f"(d[123]), "=f"(d[124]), "=f"(d[125]), "=f"(d[126]), "=f"(d[127])
               : "l"(a), "l"(b), "n"(TA));
}
template <int TA> __device__ __forceinline__ void wg_ss128_first(float* d, uint64_t a, uint64_t b) {
  asm volatile("wgmma.mma_async.sync.aligned.m64n128k16.f32.bf16.bf16 {%0,%1,%2,%3,%4,%5,%6,%7,%8,%9,%10,%11,%12,%13,%14,%15,%16,%17,%18,%19,%20,%21,%22,%23,%24,%25,%26,%27,%28,%29,%30,%31,%32,%33,%34,%35,%36,%37,%38,%39,%40,%41,%42,%43,%44,%45,%46,%47,%48,%49,%50,%51,%52,%53,%54,%55,%56,%57,%58,%59,%60,%61,%62,%63}, %64, %65, 0, 1, 1, %66, 1;"
               : "=f"(d[0]), "=f"(d[1]), "=f"(d[2]), "=f"(d[3]), "=f"(d[4]), "=f"(d[5]), "=f"(d[6]), "=f"(d[7]),
                 "=f"(d[8]), "=f"(d[9]), "=f"(d[10]), "=f"(d[11]), "=f"(d[12]), "=f"(d[13]), "=f"(d[14]), "=f"(d[15]),
                 "=f"(d[16]), "=f"(d[17]), "=f"(d[18]), "=f"(d[19]), "=f"(d[20]), "=f"(d[21]), "=f"(d[22]), "=f"(d[23]),
                 "=f"(d[24]), "=f"(d[25]), "=f"(d[26]), "=f"(d[27]), "=f"(d[28]), "=f"(d[29]), "=f"(d[30]), "=f"(d[31]),
                 "=f"(d[32]), "=f"(d[33]), "=f"(d[34]), "=f"(d[35]), "=f"(d[36]), "=f"(d[37]), "=f"(d[38]), "=f"(d[39]),
                 "=f"(d[40]), "=f"(d[41]), "=f"(d[42]), "=f"(d[43]), "=f"(d[44]), "=f"(d[45]), "=f"(d[46]), "=f"(d[47]),
                 "=f"(d[48]), "=f"(d[49]), "=f"(d[50]), "=f"(d[51]), "=f"(d[52]), "=f"(d[53]), "=f"(d[54]), "=f"(d[55]),
                 "=f"(d[56]), "=f"(d[57]), "=f"(d[58]), "=f"(d[59]), "=f"(d[60]), "=f"(d[61]), "=f"(d[62]), "=f"(d[63])
               : "l"(a), "l"(b), "n"(TA));
}

constexpr uint32_t H_SB = 0x400;
constexpr int H_STAGE = 49152, H_NST = 4;
constexpr int H_STG = H_NST * H_STAGE;
constexpr int H_VEC = H_STG + 3 * 8192;
constexpr int H_GATE = H_VEC + 6656;
constexpr int H_BAR = H_GATE + 1024;
constexpr int H_SMEM = H_BAR + 256;
constexpr int HB_FULL = 0, HB_EMPTY = 32, HB_IFULL = 64, HB_IEMPTY = 80, HB_VFULL = 96, HB_STGF = 112, HB_ITEM = 120, HB_Q = 128, HB_SRDY = 160, HB_SFREE = 184,
              HB_MFULL = 208, HB_MEMPTY = 224, HB_MAIL = 240;
constexpr int NB_HX = 4, NB_HY = 5, NB_HZ = 6;
enum { IT_END = 0, IT_MOD = 1, IT_XT = 2, IT_OUT = 3, IT_WS = 4, IT_F1 = 5, IT_F2 = 6, IT_STAT = 7 };
constexpr int N_MOD = 32, N_WS = 28, N_XT = 2, N_STAT = 4;
constexpr int MAX_ITEMS = 1400;
#define NH2 94
constexpr int NH1 = 36;
struct HList { uint32_t n, head, tbase; uint32_t it[MAX_ITEMS]; };
#define HT(i)

#define POL_WO L2_NORMAL
#define POL_W2 L2_NORMAL
#define POL_ATT L2_FIRST
#define POL_ACT L2_FIRST
#define POL_PRE L2_FIRST
__device__ __forceinline__ void mbar_arrive_n(uint32_t b, uint32_t n) { asm volatile("mbarrier.arrive.shared::cta.b64 _, [%0], %1;" :: "r"(b), "r"(n) : "memory"); }
__device__ __forceinline__ void mbar_arrive_cl(uint32_t b) { asm volatile("mbarrier.arrive.shared::cluster.b64 _, [%0];" :: "r"(b) : "memory"); }
__device__ __forceinline__ void h_free(uint32_t b, uint32_t pm) { mbar_arrive(b); mbar_arrive_cl(b ^ pm); }
__device__ __forceinline__ void tma2d_mc(uint32_t dst, const CUtensorMap* m, int c0, int c1, uint32_t bar, uint64_t pol) {
  asm volatile("cp.async.bulk.tensor.2d.shared::cluster.global.mbarrier::complete_tx::bytes.multicast::cluster.L2::cache_hint [%0], [%1, {%3, %4}], [%2], %5, %6;"
               :: "r"(dst), "l"(m), "r"(bar), "r"(c0), "r"(c1), "h"((uint16_t)3), "l"(pol) : "memory");
}
__device__ __forceinline__ void bulk_mc(uint32_t dst, const void* src, uint32_t bytes, uint32_t bar, uint64_t pol) {
  asm volatile("cp.async.bulk.shared::cluster.global.mbarrier::complete_tx::bytes.multicast::cluster.L2::cache_hint [%0], [%1], %2, [%3], %4, %5;"
               :: "r"(dst), "l"(src), "r"(bytes), "r"(bar), "h"((uint16_t)3), "l"(pol) : "memory");
}
__device__ __forceinline__ void cluster_sync() {
  asm volatile("barrier.cluster.arrive.release.aligned;\nbarrier.cluster.wait.acquire.aligned;" ::: "memory");
}
__device__ __forceinline__ void bulk_s2g(void* dst, uint32_t src, uint32_t bytes) {
  asm volatile("cp.async.bulk.global.shared::cta.bulk_group [%0], [%1], %2;" :: "l"(dst), "r"(src), "r"(bytes) : "memory");
}
__device__ __forceinline__ void tma2d_add(const CUtensorMap* m, int c0, int c1, uint32_t src) {
  asm volatile("cp.reduce.async.bulk.tensor.2d.global.shared::cta.add.tile.bulk_group [%0, {%2, %3}], [%1];" :: "l"(m), "r"(src), "r"(c0), "r"(c1) : "memory");
}
__device__ __forceinline__ void bulk_commit() { asm volatile("cp.async.bulk.commit_group;" ::: "memory"); }
template <int N> __device__ __forceinline__ void bulk_wait_read() { asm volatile("cp.async.bulk.wait_group.read %0;" :: "n"(N) : "memory"); }
__device__ __forceinline__ void bulk_wait_all() { asm volatile("cp.async.bulk.wait_group 0;" ::: "memory"); }
__device__ __forceinline__ uint32_t hfma2(uint32_t a, uint32_t b, uint32_t c) { uint32_t t; asm("fma.rn.bf16x2 %0, %1, %2, %3;" : "=r"(t) : "r"(a), "r"(b), "r"(c)); return t; }
__device__ __forceinline__ float lds32f(uint32_t a) { return __uint_as_float(lds32(a)); }

template <int BN, int TA, int K0, int K1>
__device__ __forceinline__ void h_mma(float* acc, uint64_t da, uint64_t db) {
#pragma unroll
  for (int k = K0; k < K1; k++) {
    const uint64_t a = da + k * (TA ? 256 : 2), b = db + k * 128;
    if (BN == 256) wg_ss256<TA>(acc, a, b); else wg_ss128<TA>(acc, a, b);
  }
}
template <int BN, int TA>
__device__ __forceinline__ void h_mainloop(float* acc, uint32_t sb, uint32_t pm, int nst, uint32_t& st, uint32_t& ph, int wg, bool leader, uint32_t clk_q) {
  const uint64_t da0 = TA ? mkdesc(H_SB + wg * 1024, 2048, 128, 0) : mkdesc(H_SB + wg * 8192, 16, 1024, 1);
  const uint64_t db0 = mkdesc(H_SB + 16384, 8192, 1024, 1);
  const uint32_t full = sb + H_BAR + HB_FULL, empty = sb + H_BAR + HB_EMPTY;
  uint32_t prev = st;
  {
    mbar_wait(full + st * 8, ph);
    HT(1);
    const uint64_t da = da0 + st * (H_STAGE >> 4), db = db0 + st * (H_STAGE >> 4);
    WG_FENCE();
    if (BN == 256) wg_ss256_first<TA>(acc, da, db); else wg_ss128_first<TA>(acc, da, db);
    h_mma<BN, TA, 1, 4>(acc, da, db);
    WG_COMMIT();
    if (++st == H_NST) { st = 0; ph ^= 1; }
  }
  {
    mbar_wait(full + st * 8, ph);
    const uint64_t da = da0 + st * (H_STAGE >> 4), db = db0 + st * (H_STAGE >> 4);
    WG_FENCE();
    h_mma<BN, TA, 0, 3>(acc, da, db);
    WG_COMMIT();
    h_mma<BN, TA, 3, 4>(acc, da, db);
    WG_COMMIT();
    WG_WAIT(1);
    if (leader) h_free(empty + prev * 8, pm);
    if (wg) bar_arrive<NB_HY, 256>(); else bar_sync<NB_HY, 256>();
    prev = st;
    if (++st == H_NST) { st = 0; ph ^= 1; }
  }
#pragma unroll 1
  for (int i = 4; i < nst; i++) {
    mbar_wait(full + st * 8, ph);
    const uint64_t da = da0 + st * (H_STAGE >> 4), db = db0 + st * (H_STAGE >> 4);
    WG_FENCE();
    h_mma<BN, TA, 0, 4>(acc, da, db);
    WG_COMMIT();
    WG_WAIT(1);
    if (leader) h_free(empty + prev * 8, pm);
    prev = st;
    if (++st == H_NST) { st = 0; ph ^= 1; }
  }
  if (wg) {
    WG_WAIT(0);
    if (leader) h_free(empty + prev * 8, pm);
    bar_sync<NB_HX, 256>();
  }
  {
    mbar_wait(full + st * 8, ph);
    const uint64_t da = da0 + st * (H_STAGE >> 4), db = db0 + st * (H_STAGE >> 4);
    WG_FENCE();
    h_mma<BN, TA, 0, 4>(acc, da, db);
    WG_COMMIT();
    WG_WAIT(1);
    if (leader && !wg) h_free(empty + prev * 8, pm);
    prev = st;
    if (++st == H_NST) { st = 0; ph ^= 1; }
  }
  {
    mbar_wait(full + st * 8, ph);
    const uint64_t da = da0 + st * (H_STAGE >> 4), db = db0 + st * (H_STAGE >> 4);
    WG_FENCE();
    h_mma<BN, TA, 0, 3>(acc, da, db);
    WG_COMMIT();
    h_mma<BN, TA, 3, 4>(acc, da, db);
    WG_COMMIT();
    WG_WAIT(1);
    if (leader) h_free(empty + prev * 8, pm);
    if (!wg) bar_arrive<NB_HX, 256>();
  }
}
__device__ __forceinline__ void h_release(uint32_t sb, uint32_t pm, uint32_t& st, uint32_t& ph, bool leader) {
  if (leader) h_free(sb + H_BAR + HB_EMPTY + st * 8, pm);
  if (++st == H_NST) { st = 0; ph ^= 1; }
}

__device__ __forceinline__ uint32_t stg_acquire(uint32_t sb, uint32_t g, uint32_t& b) {
  const uint32_t q = (g * 43691u) >> 17;
  b = g - 3 * q;
  mbar_wait(sb + H_BAR + HB_SFREE + b * 8, (q & 1) ^ 1);
  return sb + H_STG + b * 8192;
}
__device__ __forceinline__ void stg_release(uint32_t sb, uint32_t b, int lane) {
  __syncwarp();
  if (lane == 0) mbar_arrive(sb + H_BAR + HB_SRDY + b * 8);
}
__device__ __forceinline__ uint32_t hmul2(uint32_t a, uint32_t b) { uint32_t t; asm("mul.rn.bf16x2 %0, %1, %2;" : "=r"(t) : "r"(a), "r"(b)); return t; }
template <int BN>
__device__ __forceinline__ void h_gated(float* acc, uint32_t va, uint32_t vb, uint32_t vp, uint32_t sb, uint32_t pm, uint32_t& st, uint32_t& ph, uint32_t g0, int wg, bool leader,
                                        int warp, int lane, uint32_t clk_q) {
  uint32_t gt[BN / 8];
  mbar_wait(vb, vp);
#pragma unroll
  for (int i = 0; i < BN / 32; i++) lds128(gt + 4 * i, va + i * 64 + (lane & 3) * 16);
  WG_WAIT(0);
  reg_fence<BN / 2>(acc);
  h_release(sb, pm, st, ph, leader);
  HT(2);
  const uint32_t ro = ((warp & 3) * 16 + (lane & 7)) * 128, x0 = ((lane >> 3) ^ (lane & 7)) << 4;
  if (BN == 256 && wg) bar_sync<NB_HZ, 256>();
#pragma unroll
  for (int u = 0; u < BN / 64; u++) {
    uint32_t b;
    const uint32_t base = stg_acquire(sb, g0 + u, b) + ro;
    if (BN == 256 && u == 1 && !wg) bar_arrive<NB_HZ, 256>();
#pragma unroll
    for (int c2 = 0; c2 < 2; c2++) {
      const int c = 2 * u + c2;
#pragma unroll
      for (int h = 0; h < 2; h++) {
        uint32_t y[4];
#pragma unroll
        for (int j = 0; j < 4; j++) { const float* a = acc + c * 16 + j * 4 + h * 2; y[j] = hmul2(pack2(a[0], a[1]), gt[4 * c + j]); }
        stsm4(base + h * 1024 + (x0 ^ (c2 << 6)), y);
      }
    }
    stg_release(sb, b, lane);
  }
}

template <int BN>
__device__ __forceinline__ void h_swiglu(float* acc, uint32_t vb, uint32_t vp, uint32_t sb, uint32_t pm, uint32_t& st, uint32_t& ph, uint32_t g0, int wg, bool leader,
                                         int warp, int lane, uint32_t clk_q) {
  float rs[2], rh[2];
  mbar_wait(vb, vp);
  {
    const uint64_t da = mkdesc(H_SB + H_VEC + 4096 + wg * 1024, 0, 128, 0), db = mkdesc(H_SB + H_VEC, 1024, 0, 1);
    WG_FENCE();
    if (BN == 256) wg_ss256<0>(acc, da, db); else wg_ss128<0>(acc, da, db);
    WG_COMMIT();
  }
#pragma unroll
  for (int h = 0; h < 2; h++) { rs[h] = lds32f(sb + H_VEC + 6144 + (warp * 16 + h * 8 + (lane >> 2)) * 4); rh[h] = 0.5f * rs[h]; }
  WG_WAIT(1);
  h_release(sb, pm, st, ph, leader);
  WG_WAIT(0);
  reg_fence<BN / 2>(acc);
  HT(2);
  const uint32_t ro = ((warp & 3) * 16 + (lane & 7)) * 128, x0 = ((lane >> 3) ^ (lane & 7)) << 4;
#pragma unroll
  for (int uu = 0; uu < BN / 128; uu++) {
    uint32_t b;
    const uint32_t base = stg_acquire(sb, g0 + uu, b) + ro;
#pragma unroll
    for (int c2 = 0; c2 < 2; c2++) {
      const int c = 2 * uu + c2;
      uint32_t y[2][4];
#pragma unroll
      for (int j = 0; j < 4; j++) {
        const float* g = acc + 16 * c + 4 * j; const float* u = g + BN / 4;
        float o[4];
#pragma unroll
        for (int e = 0; e < 4; e++) {
          const float g2 = rh[e >> 1] * g[e];
          const float h = g2 * (rs[e >> 1] * u[e]);
          float t; asm("tanh.approx.f32 %0, %1;" : "=f"(t) : "f"(g2));
          o[e] = fmaf(h, t, h);
        }
        y[0][j] = pack2(o[0], o[1]); y[1][j] = pack2(o[2], o[3]);
      }
      stsm4(base + (x0 ^ (c2 << 6)), y[0]); stsm4(base + 1024 + (x0 ^ (c2 << 6)), y[1]);
    }
    stg_release(sb, b, lane);
  }
}

template <bool WS>
__device__ __forceinline__ void h_vecmat(uint32_t sb, int idx, uint32_t& st, uint32_t& ph, int tid, const __nv_bfloat16* cvec, uint8_t* w13s, uint8_t* bext,
                                         __nv_bfloat16* mod, __nv_bfloat16* gate) {
  const uint32_t stg = sb + H_STG, bars = sb + H_BAR;
  const int lane = tid & 31, warp = tid >> 5;
#pragma unroll
  for (int i = 0; i < 4; i++) {
    const int k = tid + 256 * i;
    if (WS) {
      const uint32_t s = __ldcg(reinterpret_cast<const uint16_t*>(mod) + 3 * D_ + k), c = __ldcg(reinterpret_cast<const uint16_t*>(mod) + 4 * D_ + k);
      sts32(stg + k * 4, s << 16); sts32(stg + 4096 + k * 4, c | c << 16);
    } else {
      const float c = __bfloat162float(cvec[k]);
      sts32(stg + k * 4, __float_as_uint(__bfloat162float(__float2bfloat16(c / (1.f + __expf(-c))))));
    }
  }
  bar_sync<1, 256>();
  float v[4][8], u[4][8];
#pragma unroll
  for (int b = 0; b < 4; b++)
#pragma unroll
    for (int e = 0; e < 8; e++) { v[b][e] = 0.f; u[b][e] = 0.f; }
  const int r0 = tid >> 3;
  const uint32_t off = 16384 + r0 * 128 + (((tid & 7) ^ (r0 & 7)) << 4);
  uint32_t prev = 0;
#pragma unroll 1
  for (int i = 0; i < (WS ? 16 : 8); i++) {
    mbar_wait(bars + HB_FULL + st * 8, ph);
    const uint32_t base = sb + st * H_STAGE + off;
#pragma unroll
    for (int ri = 0; ri < 2; ri++) {
      const uint32_t ka = stg + ((WS ? i * 64 : i * 128) + r0 + 32 * ri) * 4;
      const float m0 = lds32f(ka), m1 = WS ? m0 : lds32f(ka + 256);
      const uint32_t c2 = WS ? lds32(ka + 4096) : 0;
#pragma unroll
      for (int b = 0; b < 4; b++) {
        uint32_t w[4];
        lds128(w, base + b * 8192 + ri * 4096);
        const float m = b < 2 ? m0 : m1;
#pragma unroll
        for (int e = 0; e < 4; e++) {
          v[b][2 * e] = fmaf(m, bf_lo(w[e]), v[b][2 * e]); v[b][2 * e + 1] = fmaf(m, bf_hi(w[e]), v[b][2 * e + 1]);
          if (WS) { w[e] = hfma2(w[e], c2, w[e]); u[b][2 * e] += bf_lo(w[e]); u[b][2 * e + 1] += bf_hi(w[e]); }
        }
        if (WS) sts128(base + b * 8192 + ri * 4096, w[0], w[1], w[2], w[3]);
      }
    }
    if (WS) fence_async_smem();
    bar_sync<1, 256>();
    if (tid == 0) {
      if (WS) {
        bulk_s2g(w13s + (size_t)(idx * 16 + i) * 32768, sb + st * H_STAGE + 16384, 32768);
        bulk_commit();
        if (i > 0) { bulk_wait_read<1>(); mbar_arrive_n(bars + HB_EMPTY + prev * 8, 4); }
      } else mbar_arrive_n(bars + HB_EMPTY + st * 8, 4);
    }
    prev = st;
    if (++st == H_NST) { st = 0; ph ^= 1; }
  }
  if (WS && tid == 0) {
    bulk_wait_read<0>(); mbar_arrive_n(bars + HB_EMPTY + prev * 8, 4);
    bulk_wait_all(); fence_async_all(); fence_gpu();
  }
#pragma unroll
  for (int b = 0; b < 4; b++)
#pragma unroll
    for (int e = 0; e < 8; e++) {
      v[b][e] += __shfl_xor_sync(0xffffffffu, v[b][e], 8); v[b][e] += __shfl_xor_sync(0xffffffffu, v[b][e], 16);
      if (WS) { u[b][e] += __shfl_xor_sync(0xffffffffu, u[b][e], 8); u[b][e] += __shfl_xor_sync(0xffffffffu, u[b][e], 16); }
    }
  if (lane < 8) {
#pragma unroll
    for (int b = 0; b < 4; b++) {
      const uint32_t a = stg + warp * 2048 + b * 256 + lane * 32;
      sts128(a, __float_as_uint(v[b][0]), __float_as_uint(v[b][1]), __float_as_uint(v[b][2]), __float_as_uint(v[b][3]));
      sts128(a + 16, __float_as_uint(v[b][4]), __float_as_uint(v[b][5]), __float_as_uint(v[b][6]), __float_as_uint(v[b][7]));
      if (WS) {
        sts128(a + 1024, __float_as_uint(u[b][0]), __float_as_uint(u[b][1]), __float_as_uint(u[b][2]), __float_as_uint(u[b][3]));
        sts128(a + 1040, __float_as_uint(u[b][4]), __float_as_uint(u[b][5]), __float_as_uint(u[b][6]), __float_as_uint(u[b][7]));
      }
    }
  }
  bar_sync<1, 256>();
  float sv = 0.f, su = 0.f;
#pragma unroll
  for (int i = 0; i < 8; i++) {
    sv += lds32f(stg + i * 2048 + tid * 4);
    su += WS ? lds32f(stg + i * 2048 + 1024 + tid * 4) : lds32f(stg + i * 2048 + (tid ^ 128) * 4);
  }
  if (WS) {
    const __nv_bfloat16 uh = __float2bfloat16(su), ul = __float2bfloat16(su - __bfloat162float(uh));
    const __nv_bfloat16 vh = __float2bfloat16(sv), vl = __float2bfloat16(sv - __bfloat162float(vh)), z = __float2bfloat16(0.f);
    uint8_t* p = bext + idx * 4096 + (tid >> 6) * 1024 + (tid & 7) * 2;
#pragma unroll
    for (int r = 0; r < 8; r++)
      *reinterpret_cast<__nv_bfloat16*>(p + r * 128 + ((((tid & 63) >> 3) ^ r) << 4)) = r == 0 || r == 2 ? uh : r == 1 ? ul : r == 3 || r == 5 ? vh : r == 4 ? vl : z;
  } else if (tid < 128) {
    const int n = idx * 128 + tid, vec = n >> 10, col = n & 1023;
    const __nv_bfloat16 r = __float2bfloat16(sv + su);
    mod[2048 + n] = r;
    if (vec == 0 || vec == 3) gate[(vec ? D_ : 0) + (col & ~31) + ((col >> 1) & 3) * 8 + ((col >> 3) & 3) * 2 + (col & 1)] = r;
  }
}

struct HWeights { const uint8_t* p[4]; };
#define HW_T 420
#define HW_D 0
#define HW_U0 0
#define HW_U1 0
__global__ void __launch_bounds__(384, 1)
kernel_H(const __grid_constant__ CUtensorMap tmo, const __grid_constant__ CUtensorMap tm1, const __grid_constant__ CUtensorMap tm3,
         const __grid_constant__ CUtensorMap tm2, const __grid_constant__ CUtensorMap tmm, const __grid_constant__ CUtensorMap tmx,
         const __grid_constant__ CUtensorMap tmy, const __nv_bfloat16* __restrict__ x, const __nv_bfloat16* __restrict__ cvec, __nv_bfloat16* out, const __grid_constant__ HWeights rw, const __grid_constant__ HList list) {
  extern __shared__ __align__(1024) uint8_t smem[];
  uint32_t rank, pair;
  asm("mov.u32 %0, %%cluster_ctarank;" : "=r"(rank)); asm("mov.u32 %0, %%cluster_nctarank;" : "=r"(pair));
  rank = __shfl_sync(0xffffffffu, rank, 0); pair = __shfl_sync(0xffffffffu, pair, 0) - 1;
  const uint32_t sb = H_SB + (rank << 24), bars = sb + H_BAR, pm = pair << 24;
  const int tid = threadIdx.x, lane = tid & 31;
  const int warp = __shfl_sync(0xffffffffu, tid >> 5, 0);
  if (tid == 0) {
    if ((smem_u32(smem) & 0xffffff) != H_SB) __trap();
    for (int i = 0; i < H_NST; i++) { mbar_init(bars + HB_FULL + i * 8, 1); mbar_init(bars + HB_EMPTY + i * 8, 4); }
    for (int i = 0; i < 2; i++) { mbar_init(bars + HB_IFULL + i * 8, 1); mbar_init(bars + HB_IEMPTY + i * 8, 1); mbar_init(bars + HB_VFULL + i * 8, 1);
      mbar_init(bars + HB_MFULL + i * 8, 1); mbar_init(bars + HB_MEMPTY + i * 8, 1); }
    for (int i = 0; i < 3; i++) { mbar_init(bars + HB_SRDY + i * 8, 4); mbar_init(bars + HB_SFREE + i * 8, 1); }
    mbar_init(bars + HB_STGF, 1);
    asm volatile("fence.mbarrier_init.release.cluster;" ::: "memory");
    fence_async_smem();
  }
  __syncthreads();
  cluster_sync();
  asm volatile("griddepcontrol.launch_dependents;");
  if (warp >= 8) {
    asm volatile("setmaxnreg.dec.sync.aligned.u32 56;");
    if (warp == 8) {
      uint32_t st = 0, ph = 1, nv = 0, q = 0;
      uint32_t* const head = &g_flags[list.head];
      const bool claimer = lane == 0 && rank == 0;
      if (claimer) q = atomicAdd(head, 1);
#pragma unroll 1
      for (uint32_t n = 0;; n++) {
        if (pair) {
          const uint32_t o = (n & 1) * 8, p = (n >> 1) & 1;
          if (rank == 0) {
            mbar_wait(bars + HB_MEMPTY + o, p ^ 1);
            if (lane == 0) st_async1((bars + HB_MAIL + o) ^ pm, q, (bars + HB_MFULL + o) ^ pm);
          } else {
            if (lane == 0) mbar_expect(bars + HB_MFULL + o, 4);
            mbar_wait(bars + HB_MFULL + o, p);
            q = lds32(bars + HB_MAIL + o);
            __syncwarp();
            if (lane == 0) mbar_arrive_cl((bars + HB_MEMPTY + o) ^ pm);
          }
        }
        q = __shfl_sync(0xffffffffu, q, 0);
        uint32_t it = q < list.n ? list.it[q] : 0;
        const bool shA = pair && !(it >> 28 & 1), shB = pair && (it >> 28 & 1);
        if (rank && it) it += shA ? 1 << 7 : (it >> 29) << 3;
        const int type = it & 7, mt = (it >> 3) & 15, idx = (it >> 7) & 63, sz = (it >> 13) & 3, kb0 = (it >> 15) & 63, nkb = (it >> 21) & 127;
        {
          int f = FL_GO; uint32_t target = 0;
          if (type == IT_OUT) { f = lane == 0 ? FL_ATT + 8 * mt : lane == 1 ? FL_XT + 8 * mt : FL_MOD; target = lane == 0 ? 64 : lane == 1 ? N_XT : N_MOD; }
          else if (type == IT_F1) { f = lane == 0 ? FL_OUT + 8 * mt : FL_WS; target = lane == 0 ? 1024 : N_WS; }
          else if (type == IT_F2) { f = FL_F1 + 8 * mt; target = 56; }
          else if (type == IT_STAT) { f = FL_OUT + 8 * mt; target = 1024; }
          else if (type == IT_WS) { f = FL_MOD; target = N_MOD; }
          else if (type != IT_END) target = 1;
          if (lane < 3) wait_flag(&g_flags[f], target);
          __syncwarp();
          asm volatile("fence.proxy.async.global;" ::: "memory");
        }
        mbar_wait(bars + HB_IEMPTY + (n & 1) * 8, ((n >> 1) & 1) ^ 1);
        if (elect_one()) {
          sts32(bars + HB_ITEM + (n & 1) * 4, it);
          mbar_arrive(bars + HB_IFULL + (n & 1) * 8);
        }
        if (type == IT_END) break;
        const bool gemm = type == IT_OUT || type == IT_F1 || type == IT_F2;
        const int nst = gemm ? nkb : type == IT_WS ? 16 : type == IT_MOD ? 8 : 0;
        const int bn = 256 >> sz;
        const uint8_t* ap = type == IT_OUT ? g_att + (size_t)mt * 64 * 16384 : g_act + (size_t)mt * 56 * 16384;
        const uint8_t* wp = g_w13s + (size_t)(idx >> sz) * 16 * 32768 + (sz ? (idx & 1) * 8192 : 0);
        const CUtensorMap* tb = type == IT_OUT ? &tmo : type == IT_F2 ? &tm2 : type == IT_WS ? &tm1 : &tmm;
        const CUtensorMap* tc = type == IT_WS ? &tm3 : tb;
        const int c0 = gemm ? idx * bn : type == IT_WS ? idx * 128 : 2048 + idx * 128, dcol = gemm ? 128 : 0, kmul = type == IT_MOD ? 128 : 64, drow = type == IT_MOD ? 64 : 0;
        const uint32_t bytes = gemm ? 16384 + bn * 128 : 32768;
        const uint64_t pa = type == IT_OUT ? POL_ATT : POL_ACT, pb = type == IT_OUT ? POL_WO : type == IT_F2 ? POL_W2 : POL_PRE;
        if (nst < 2 && claimer) q = atomicAdd(head, 1);
#pragma unroll 1
        for (int i = 0; i < nst; i++) {
          const int kb = kb0 + i;
          const uint32_t d = sb + st * H_STAGE, fb = bars + HB_FULL + st * 8;
          if (i == nst - 2 && claimer) q = atomicAdd(head, 1);
          mbar_wait(bars + HB_EMPTY + st * 8, ph);
          if (elect_one()) {
            mbar_expect(fb, bytes);
            if (type == IT_F1) {
              if (shA) tma2d_mc(d + rank * 8192, &tmy, kb * 64, mt * 128 + rank * 64, fb, L2_NORMAL); else tma2d(d, &tmx, kb * 64, mt * 128, fb);
              if (shB) bulk_mc(d + 16384 + rank * (16384 >> sz), wp + (size_t)kb * 32768 + rank * 16384, 16384 >> sz, fb, L2_NORMAL);
              else if (sz == 0) bulk_g2s(d + 16384, wp + (size_t)kb * 32768, 32768, fb);
              else { bulk_g2s(d + 16384, wp + (size_t)kb * 32768, 8192, fb); bulk_g2s(d + 24576, wp + (size_t)kb * 32768 + 16384, 8192, fb); }
            } else {
              if (shA) bulk_mc(d + rank * 8192, ap + (size_t)kb * 16384 + rank * 8192, 8192, fb, pa);
              else if (gemm) bulk_g2s_p(d, ap + (size_t)kb * 16384, 16384, fb, pa);
              if (shB) {
                if (sz == 0) {
                  tma2d_mc(d + 16384 + rank * 16384, tb, c0 + rank * 128, kb * 64, fb, pb);
                  tma2d_mc(d + 24576 + rank * 16384, tb, c0 + rank * 128 + 64, kb * 64, fb, pb);
                } else tma2d_mc(d + 16384 + rank * 8192, tb, c0 + rank * 64, kb * 64, fb, pb);
              } else {
                tma2d_p(d + 16384, tb, c0, kb * kmul, fb, pb);
                tma2d_p(d + 24576, tb, c0 + 64, kb * kmul, fb, pb);
                if (sz == 0) { tma2d_p(d + 32768, tc, c0 + dcol, kb * kmul + drow, fb, pb); tma2d_p(d + 40960, tc, c0 + dcol + 64, kb * kmul + drow, fb, pb); }
              }
            }
          }
          if (++st == H_NST) { st = 0; ph ^= 1; }
        }
        if (gemm) {
          if (type == IT_F1) {
            if (lane == 0) wait_flag(&g_flags[FL_STAT + 8 * mt], N_STAT);
            __syncwarp();
            asm volatile("fence.proxy.async.global;" ::: "memory");
          }
          if (elect_one()) {
            const uint32_t v = sb + H_VEC, fb = bars + HB_VFULL + (nv & 1) * 8;
            if (type == IT_F1) {
              mbar_expect(fb, (4096 >> sz) + 2560);
              if (sz == 0) bulk_g2s(v, g_bext + idx * 4096, 4096, fb);
              else { const uint8_t* p = g_bext + (idx >> 1) * 4096 + (idx & 1) * 1024; bulk_g2s(v, p, 1024, fb); bulk_g2s(v + 1024, p + 2048, 1024, fb); }
              bulk_g2s(v + 4096, g_ext + mt * 2560, 2560, fb);
            } else {
              mbar_expect(fb, bn * 2);
              bulk_g2s(sb + H_GATE + (nv & 1) * 512, g_gate + (type == IT_F2 ? D_ : 0) + c0, bn * 2, fb);
            }
          }
          nv++;
        }
      }
    } else if (warp == 10) {
      if (!pair && lane == 0) {
        const uint32_t t0 = clk32() + HW_D;
        uint32_t n = 0;
#pragma unroll 1
        for (int u = HW_U0 + blockIdx.x; u < HW_U1; u += NH1, n++) {
          int m, o;
          if (u < 768) { const int r = u / 96; m = r < 4 ? r & 1 : r == 4 ? 2 : r - 5; o = (r < 2 ? 384 : r < 4 ? 0 : r == 4 ? 192 : 576) / 2 + u - r * 96; }
          else if (u < 1152) { m = (u - 768) >> 7; o = 384 + (u & 127); }
          else { m = 3; o = u - 1152; }
          while ((int32_t)(clk32() - t0 - n * HW_T) < 0) {}
          asm volatile("cp.async.bulk.prefetch.L2.global [%0], 16384;" :: "l"(rw.p[m] + (size_t)o * 16384) : "memory");
        }
      }
    } else if (warp == 9) {
      uint32_t g = 0;
#pragma unroll 1
      for (uint32_t n = 0;; n++) {
        mbar_wait(bars + HB_IFULL + (n & 1) * 8, (n >> 1) & 1);
        const uint32_t it = lds32(bars + HB_ITEM + (n & 1) * 4);
        const int type = it & 7, mt = (it >> 3) & 15, idx = (it >> 7) & 63, sz = (it >> 13) & 3, nkb = (it >> 21) & 127;
        if (type == IT_END) break;
        const bool gated = type == IT_OUT || type == IT_F2, gemm = gated || type == IT_F1;
        if (!gemm) { if (n & 1) bar_sync<3, 288>(); else bar_sync<2, 288>(); }
        if (lane == 0) {
          if (gemm) {
            const int nu = (gated ? 4 : 2) >> sz;
            uint32_t pb = 0;
#pragma unroll 1
            for (int u = 0; u < 2 * nu; u++, g++) {
              const uint32_t r = (g * 43691u) >> 17, b = g - 3 * r, src = sb + H_STG + b * 8192;
              const int w = u >= nu, uu = u - w * nu;
              mbar_wait(bars + HB_SRDY + b * 8, r & 1);
              if (u == 2 * nu - 1) mbar_arrive(bars + HB_IEMPTY + (n & 1) * 8);
              fence_async_smem();
              if (gated) tma2d_add(&tmy, idx * (256 >> sz) + uu * 64, mt * 128 + w * 64, src);
              else bulk_s2g(g_act + (size_t)(mt * 56 + idx * nu + uu) * 16384 + w * 8192, src, 8192);
              bulk_commit();
              if (u > 0) { bulk_wait_read<1>(); mbar_arrive(bars + HB_SFREE + pb * 8); }
              pb = b;
            }
            bulk_wait_read<0>();
            mbar_arrive(bars + HB_SFREE + pb * 8);
            mbar_arrive(bars + HB_STGF);
            bulk_wait_all(); fence_async_all();
          } else {
            mbar_arrive(bars + HB_STGF);
            mbar_arrive(bars + HB_IEMPTY + (n & 1) * 8);
          }
          if (type != IT_F2) {
            const uint32_t inc = type == IT_OUT ? (4 >> sz) * nkb : type == IT_F1 ? 2 >> sz : 1;
            fence_gpu();
            red_add_u32(&g_flags[type == IT_MOD ? FL_MOD : type == IT_WS ? FL_WS :
                                 (type == IT_XT ? FL_XT : type == IT_OUT ? FL_OUT : type == IT_STAT ? FL_STAT : FL_F1) + 8 * mt], inc);
          }
        }
        __syncwarp();
      }
      if (!pair) asm volatile("griddepcontrol.wait;" ::: "memory");
      uint32_t k = 0;
      if (lane == 0) { fence_gpu(); k = atomicAdd(&g_flags[FL_EXIT], 1); }
      k = __shfl_sync(0xffffffffu, k, 0);
      if (k == NH1 + NH2 - 1) {
        fence_gpu();
        for (int i = lane; i < 1024; i += 32) g_flags[i] = 0;
      }
    }
  } else {
    asm volatile("setmaxnreg.inc.sync.aligned.u32 224;");
    const int wg = warp >> 2;
    const bool leader = (tid & 127) == 0;
    uint32_t st = 0, ph = 0, nv = 0, g = 0;
#pragma unroll 1
    for (uint32_t n = 0;; n++) {
      mbar_wait(bars + HB_IFULL + (n & 1) * 8, (n >> 1) & 1);
      const uint32_t it = __shfl_sync(0xffffffffu, lds32(bars + HB_ITEM + (n & 1) * 4), 0);
      const int type = it & 7, mt = (it >> 3) & 15, idx = (it >> 7) & 63, sz = (it >> 13) & 3, nkb = (it >> 21) & 127;
      if (type == IT_END) break;
      constexpr uint32_t clk_q = 0;
      if (type == IT_OUT || type == IT_F1 || type == IT_F2) {
        const uint32_t va = sb + H_GATE + (nv & 1) * 512, vb = bars + HB_VFULL + (nv & 1) * 8, vp = (nv >> 1) & 1;
        const uint32_t nu = (type == IT_F1 ? 2 : 4) >> sz, g0 = g + wg * nu;
        nv++; g += 2 * nu;
        if (sz == 0) {
          float acc[128];
          if (type == IT_OUT) h_mainloop<256, 1>(acc, sb, pm, nkb, st, ph, wg, leader, clk_q);
          else h_mainloop<256, 0>(acc, sb, pm, nkb, st, ph, wg, leader, clk_q);
          if (type == IT_F1) h_swiglu<256>(acc, vb, vp, sb, pm, st, ph, g0, wg, leader, warp, lane, clk_q);
          else h_gated<256>(acc, va, vb, vp, sb, pm, st, ph, g0, wg, leader, warp, lane, clk_q);
        } else {
          float acc[64];
          if (type == IT_OUT) h_mainloop<128, 1>(acc, sb, pm, nkb, st, ph, wg, leader, clk_q);
          else h_mainloop<128, 0>(acc, sb, pm, nkb, st, ph, wg, leader, clk_q);
          if (type == IT_F1) h_swiglu<128>(acc, vb, vp, sb, pm, st, ph, g0, wg, leader, warp, lane, clk_q);
          else h_gated<128>(acc, va, vb, vp, sb, pm, st, ph, g0, wg, leader, warp, lane, clk_q);
        }
        HT(3);
        continue;
      } else if (type == IT_XT) {
        const uint4* xp = reinterpret_cast<const uint4*>(x + (size_t)(mt * 128 + idx * 64) * D_) + tid;
        uint4* op = reinterpret_cast<uint4*>(out + (size_t)(mt * 128 + idx * 64) * D_) + tid;
#pragma unroll 1
        for (int b = 0; b < 2; b++) {
          uint4 v[16];
#pragma unroll
          for (int i = 0; i < 16; i++) v[i] = __ldcs(xp + (b * 16 + i) * 256);
#pragma unroll
          for (int i = 0; i < 16; i++) op[(b * 16 + i) * 256] = v[i];
        }
      } else if (type == IT_STAT) {
        const int row0 = mt * 128 + idx * 32 + warp * 4;
        const uint4* xp = reinterpret_cast<const uint4*>(out + (size_t)row0 * D_) + lane;
        uint4 v[16];
#pragma unroll
        for (int i = 0; i < 16; i++) v[i] = __ldcg(xp + (i >> 2) * 128 + (i & 3) * 32);
        float s[4], m[4];
#pragma unroll
        for (int r = 0; r < 4; r++) {
          s[r] = 0.f;
#pragma unroll
          for (int i = 0; i < 4; i++) {
            const uint4 w = v[4 * r + i];
            s[r] += ((bf_lo(w.x) + bf_hi(w.x)) + (bf_lo(w.y) + bf_hi(w.y))) + ((bf_lo(w.z) + bf_hi(w.z)) + (bf_lo(w.w) + bf_hi(w.w)));
          }
        }
#pragma unroll
        for (int o = 1; o < 32; o <<= 1)
#pragma unroll
          for (int r = 0; r < 4; r++) s[r] += __shfl_xor_sync(0xffffffffu, s[r], o);
#pragma unroll
        for (int r = 0; r < 4; r++) {
          m[r] = s[r] * (1.f / D_);
          float a = 0.f, b = 0.f;
#pragma unroll
          for (int i = 0; i < 4; i++) {
            const uint4 w = v[4 * r + i];
            const uint32_t ww[4] = {w.x, w.y, w.z, w.w};
#pragma unroll
            for (int e = 0; e < 4; e++) { const float p = bf_lo(ww[e]) - m[r], t = bf_hi(ww[e]) - m[r]; a = fmaf(p, p, a); b = fmaf(t, t, b); }
          }
          s[r] = a + b;
        }
#pragma unroll
        for (int o = 1; o < 32; o <<= 1)
#pragma unroll
          for (int r = 0; r < 4; r++) s[r] += __shfl_xor_sync(0xffffffffu, s[r], o);
        if (lane < 4) {
          const float sr = lane == 0 ? s[0] : lane == 1 ? s[1] : lane == 2 ? s[2] : s[3], mr = lane == 0 ? m[0] : lane == 1 ? m[1] : lane == 2 ? m[2] : m[3];
          const float var = sr * (1.f / D_) + 1e-5f, rs = rsqrtf(var);
          const float a = -0.5f * mr, b = 0.5f * var * rs;
          const float ah = __bfloat162float(__float2bfloat16(a)), bh = __bfloat162float(__float2bfloat16(b));
          const int r = (row0 & 127) + lane;
          *reinterpret_cast<uint4*>(g_ext + mt * 2560 + r * 16) = make_uint4(pack2(ah, ah), pack2(a - ah, bh), pack2(bh, b - bh), 0u);
          *reinterpret_cast<float*>(g_ext + mt * 2560 + 2048 + r * 4) = rs;
        }
      } else {
        mbar_wait(bars + HB_STGF, (n & 1) ^ 1);
        if (type == IT_WS) h_vecmat<true>(sb, idx, st, ph, tid, cvec, g_w13s, g_bext, g_mod, g_gate);
        else h_vecmat<false>(sb, idx, st, ph, tid, cvec, g_w13s, g_bext, g_mod, g_gate);
      }
      HT(3);
      if (n & 1) bar_arrive<3, 288>(); else bar_arrive<2, 288>();
    }
  }
  cluster_sync();
}

const uint32_t h_items1[] = {
  0x1, 0x81, 0x101, 0x181, 0x201, 0x281, 0x301, 0x381, 0x401, 0x481, 0x501, 0x581, 0x601, 0x681,
  0x701, 0x781, 0x801, 0x881, 0x901, 0x981, 0xa01, 0xa81, 0xb01, 0xb81, 0xc01, 0xc81, 0xd01, 0xd81,
  0xe01, 0xe81, 0xf01, 0xf81, 0x2, 0x82, 0xa, 0x8a, 0x12, 0x92, 0x1a, 0x9a, 0x22, 0xa2,
  0x2a, 0xaa, 0x4, 0x84, 0x104, 0x184, 0x32, 0xb2, 0x3a, 0xba, 0x42, 0xc2, 0x4a, 0xca,
  0x52, 0xd2, 0x5a, 0xda, 0x62, 0xe2, 0x6a, 0xea, 0x72, 0xf2, 0x7a, 0xfa, 0x204, 0x284,
  0x304, 0x384, 0x404, 0x484, 0x504, 0x584, 0x604, 0x684, 0x704, 0x784, 0x804, 0x884, 0x904, 0x984,
  0xa04, 0xa84, 0xb04, 0xb84, 0xc04, 0xc84, 0xd04, 0xd84, 0x1000003, 0x1000083, 0x1000103, 0x1000183, 0x1040003, 0x1040083,
  0x1040103, 0x1040183, 0x1080003, 0x1080083, 0x1080103, 0x1080183, 0x10c0003, 0x10c0083, 0x10c0103, 0x10c0183, 0x1100003, 0x1100083, 0x1100103, 0x1100183,
  0x1140003, 0x1140083, 0x1140103, 0x1140183, 0x1180003, 0x1180083, 0x1180103, 0x1180183, 0x11c0003, 0x11c0083, 0x11c0103, 0x11c0183, 0x200000b, 0x200008b,
  0x200010b, 0x200018b, 0x208000b, 0x208008b, 0x208010b, 0x208018b, 0x210000b, 0x210008b, 0x210010b, 0x210018b, 0x218000b, 0x218008b, 0x218010b, 0x218018b,
  0x7, 0x87, 0x107, 0x187, 0x2000005, 0x2000085, 0x2000105, 0x2000185, 0x2000205, 0x2000285, 0x2000305, 0x2000385, 0x2000405, 0x2000485,
  0x2000505, 0x2000585, 0x2000605, 0x2000685, 0x2000705, 0x2000785, 0x2000805, 0x2000885, 0x2000905, 0x2000985, 0x2000a05, 0x2000a85, 0x2000b05, 0x2000b85,
  0x2000c05, 0x2000c85, 0x2000d05, 0x2000d85, 0x4000013, 0x4000093, 0x4000113, 0x4000193, 0x4100013, 0x4100093, 0x4100113, 0x4100193, 0xf, 0x8f,
  0x10f, 0x18f, 0x200000d, 0x200008d, 0x200010d, 0x200018d, 0x200020d, 0x200028d, 0x200030d, 0x200038d, 0x200040d, 0x200048d, 0x200050d, 0x200058d,
  0x200060d, 0x200068d, 0x200070d, 0x200078d, 0x200080d, 0x200088d, 0x200090d, 0x200098d, 0x2000a0d, 0x2000a8d, 0x2000b0d, 0x2000b8d, 0x2000c0d, 0x2000c8d,
  0x2000d0d, 0x2000d8d, 0x3800006, 0x3800086, 0x3800106, 0x3800186, 0x38e0006, 0x38e0086, 0x38e0106, 0x38e0186, 0x400001b, 0x400009b, 0x400011b, 0x400019b,
  0x410001b, 0x410009b, 0x410011b, 0x410019b, 0x380000e, 0x380008e, 0x380010e, 0x380018e, 0x38e000e, 0x38e008e, 0x38e010e, 0x38e018e, 0x17, 0x97,
  0x117, 0x197, 0x2000015, 0x2000095, 0x2000115, 0x2000195, 0x2000215, 0x2000295, 0x2000315, 0x2000395, 0x2000415, 0x2000495, 0x2000515, 0x2000595,
  0x4000023, 0x40000a3, 0x4000123, 0x40001a3, 0x4100023, 0x41000a3, 0x4100123, 0x41001a3, 0x2000615, 0x2000695, 0x2000715, 0x2000795, 0x2000815, 0x2000895,
  0x2000915, 0x2000995, 0x2000a15, 0x2000a95, 0x2000b15, 0x2000b95, 0x2000c15, 0x2000c95, 0x2000d15, 0x2000d95, 0x1f, 0x9f, 0x11f, 0x19f,
  0x200001d, 0x200009d, 0x200011d, 0x200019d, 0x200021d, 0x200029d, 0x200031d, 0x200039d, 0x200041d, 0x200049d, 0x200051d, 0x200059d, 0x400002b, 0x40000ab,
  0x400012b, 0x40001ab, 0x410002b, 0x41000ab, 0x410012b, 0x41001ab, 0x200061d, 0x200069d, 0x200071d, 0x200079d, 0x200081d, 0x200089d, 0x200091d, 0x200099d,
  0x2000a1d, 0x2000a9d, 0x2000b1d, 0x2000b9d, 0x2000c1d, 0x2000c9d, 0x2000d1d, 0x2000d9d, 0x27, 0xa7, 0x127, 0x1a7, 0x2000025, 0x20000a5,
  0x2000125, 0x20001a5, 0x2000225, 0x20002a5, 0x2000325, 0x20003a5, 0x4000033, 0x40000b3, 0x4000133, 0x40001b3, 0x4100033, 0x41000b3, 0x4100133, 0x41001b3,
  0x2000425, 0x20004a5, 0x2000525, 0x20005a5, 0x2000625, 0x20006a5, 0x2000725, 0x20007a5, 0x2000825, 0x20008a5, 0x2000925, 0x20009a5, 0x2000a25, 0x2000aa5,
  0x2000b25, 0x2000ba5, 0x2000c25, 0x2000ca5, 0x2000d25, 0x2000da5, 0x2f, 0xaf, 0x12f, 0x1af, 0x200002d, 0x20000ad, 0x200012d, 0x20001ad,
  0x200022d, 0x20002ad, 0x200032d, 0x20003ad, 0x400003b, 0x40000bb, 0x400013b, 0x40001bb, 0x410003b, 0x41000bb, 0x410013b, 0x41001bb, 0x200042d, 0x20004ad,
  0x200052d, 0x20005ad, 0x200062d, 0x20006ad, 0x200072d, 0x20007ad, 0x200082d, 0x20008ad, 0x200092d, 0x20009ad, 0x2000a2d, 0x2000aad, 0x2000b2d, 0x2000bad,
  0x2000c2d, 0x2000cad, 0x2000d2d, 0x2000dad, 0x37, 0xb7, 0x137, 0x1b7, 0x2000035, 0x20000b5, 0x2000135, 0x20001b5, 0x2000235, 0x20002b5,
  0x2000335, 0x20003b5, 0x2000435, 0x20004b5, 0x2000535, 0x20005b5, 0x4000043, 0x40000c3, 0x4000143, 0x40001c3, 0x4100043, 0x41000c3, 0x4100143, 0x41001c3,
  0x2000635, 0x20006b5, 0x2000735, 0x20007b5, 0x2000835, 0x20008b5, 0x2000935, 0x20009b5, 0x2000a35, 0x2000ab5, 0x2000b35, 0x2000bb5, 0x2000c35, 0x2000cb5,
  0x2000d35, 0x2000db5, 0x3f, 0xbf, 0x13f, 0x1bf, 0x200003d, 0x20000bd, 0x200013d, 0x20001bd, 0x200023d, 0x20002bd, 0x200033d, 0x20003bd,
  0x400004b, 0x40000cb, 0x400014b, 0x40001cb, 0x410004b, 0x41000cb, 0x410014b, 0x41001cb, 0x200043d, 0x20004bd, 0x200053d, 0x20005bd, 0x200063d, 0x20006bd,
  0x200073d, 0x20007bd, 0x200083d, 0x20008bd, 0x200093d, 0x20009bd, 0x2000a3d, 0x2000abd, 0x2000b3d, 0x2000bbd, 0x2000c3d, 0x2000cbd, 0x2000d3d, 0x2000dbd,
  0x47, 0xc7, 0x147, 0x1c7, 0x2000045, 0x20000c5, 0x2000145, 0x20001c5, 0x2000245, 0x20002c5, 0x2000345, 0x20003c5, 0x4000053, 0x40000d3,
  0x4000153, 0x40001d3, 0x4100053, 0x41000d3, 0x4100153, 0x41001d3, 0x2000445, 0x20004c5, 0x2000545, 0x20005c5, 0x2000645, 0x20006c5, 0x2000745, 0x20007c5,
  0x2000845, 0x20008c5, 0x2000945, 0x20009c5, 0x2000a45, 0x2000ac5, 0x2000b45, 0x2000bc5, 0x2000c45, 0x2000cc5, 0x2000d45, 0x2000dc5, 0x4f, 0xcf,
  0x14f, 0x1cf, 0x200004d, 0x20000cd, 0x200014d, 0x20001cd, 0x200024d, 0x20002cd, 0x200034d, 0x20003cd, 0x200044d, 0x20004cd, 0x200054d, 0x20005cd,
  0x400005b, 0x40000db, 0x400015b, 0x40001db, 0x410005b, 0x41000db, 0x410015b, 0x41001db, 0x200064d, 0x20006cd, 0x200074d, 0x20007cd, 0x200084d, 0x20008cd,
  0x200094d, 0x20009cd, 0x2000a4d, 0x2000acd, 0x2000b4d, 0x2000bcd, 0x2000c4d, 0x2000ccd, 0x2000d4d, 0x2000dcd, 0x57, 0xd7, 0x157, 0x1d7,
  0x2000055, 0x20000d5, 0x2000155, 0x20001d5, 0x2000255, 0x20002d5, 0x2000355, 0x20003d5, 0x4000063, 0x40000e3, 0x4000163, 0x40001e3, 0x4100063, 0x41000e3,
  0x4100163, 0x41001e3, 0x2000455, 0x20004d5, 0x2000555, 0x20005d5, 0x2000655, 0x20006d5, 0x2000755, 0x20007d5, 0x2000855, 0x20008d5, 0x2000955, 0x20009d5,
  0x2000a55, 0x2000ad5, 0x2000b55, 0x2000bd5, 0x2000c55, 0x2000cd5, 0x2000d55, 0x2000dd5, 0x5f, 0xdf, 0x15f, 0x1df, 0x200005d, 0x20000dd,
  0x200015d, 0x20001dd, 0x200025d, 0x20002dd, 0x200035d, 0x20003dd, 0x200006b, 0x20000eb, 0x200016b, 0x20001eb, 0x208006b, 0x20800eb, 0x208016b, 0x20801eb,
  0x210006b, 0x21000eb, 0x210016b, 0x21001eb, 0x218006b, 0x21800eb, 0x218016b, 0x21801eb, 0x200045d, 0x20004dd, 0x200055d, 0x20005dd, 0x200065d, 0x20006dd,
  0x200075d, 0x20007dd, 0x200085d, 0x20008dd, 0x200095d, 0x20009dd, 0x2000a5d, 0x2000add, 0x2000b5d, 0x2000bdd, 0x2000c5d, 0x2000cdd, 0x2000d5d, 0x2000ddd,
  0x67, 0xe7, 0x167, 0x1e7, 0x2000065, 0x20000e5, 0x2000165, 0x20001e5, 0x2000265, 0x20002e5, 0x2000365, 0x20003e5, 0x2000465, 0x20004e5,
  0x2000565, 0x20005e5, 0x2000073, 0x20000f3, 0x2000173, 0x20001f3, 0x2080073, 0x20800f3, 0x2080173, 0x20801f3, 0x2100073, 0x21000f3, 0x2100173, 0x21001f3,
  0x2180073, 0x21800f3, 0x2180173, 0x21801f3, 0x6f, 0xef, 0x16f, 0x1ef, 0x2000665, 0x20006e5, 0x2000765, 0x20007e5, 0x2000865, 0x20008e5,
  0x2000965, 0x20009e5, 0x2000a65, 0x2000ae5, 0x2000b65, 0x2000be5, 0x2000c65, 0x2000ce5, 0x2000d65, 0x2000de5, 0x200006d, 0x20000ed, 0x200016d, 0x20001ed,
  0x200026d, 0x20002ed, 0x200036d, 0x20003ed, 0x200046d, 0x20004ed, 0x200056d, 0x20005ed, 0x200066d, 0x20006ed, 0x200076d, 0x20007ed, 0x200086d, 0x20008ed,
  0x200096d, 0x20009ed, 0x2000a6d, 0x2000aed, 0x2000b6d, 0x2000bed, 0x77, 0xf7, 0x177, 0x1f7, 0x2000c6d, 0x2000ced, 0x2000d6d, 0x2000ded,
  0x2000075, 0x20000f5, 0x2000175, 0x20001f5, 0x2000275, 0x20002f5, 0x2000375, 0x20003f5, 0x2000475, 0x20004f5, 0x2000575, 0x20005f5, 0x2000675, 0x20006f5,
  0x2000775, 0x20007f5, 0x2000875, 0x20008f5, 0x2000975, 0x20009f5, 0x2000a75, 0x2000af5, 0x2000b75, 0x2000bf5, 0x2000c75, 0x2000cf5, 0x2000d75, 0x2000df5,
  0x1c0006e, 0x1c000ee, 0x1c0016e, 0x1c001ee, 0x1c7006e, 0x1c700ee, 0x1c7016e, 0x1c701ee, 0x1ce006e, 0x1ce00ee, 0x1ce016e, 0x1ce01ee, 0x1d5006e, 0x1d500ee,
  0x1d5016e, 0x1d501ee, 0x1c00076, 0x1c000f6, 0x1c00176, 0x1c001f6, 0x1c70076, 0x1c700f6, 0x1c70176, 0x1c701f6, 0x1ce0076, 0x1ce00f6, 0x1ce0176, 0x1ce01f6,
  0x1d50076, 0x1d500f6, 0x1d50176, 0x1d501f6,
};
const uint32_t h_items2[] = {
  0x100207b, 0x100217b, 0x100227b, 0x100237b, 0x104207b, 0x104217b, 0x104227b, 0x104237b, 0x108207b, 0x108217b, 0x108227b, 0x108237b, 0x10c207b, 0x10c217b,
  0x10c227b, 0x10c237b, 0x110207b, 0x110217b, 0x110227b, 0x110237b, 0x114207b, 0x114217b, 0x114227b, 0x114237b, 0x118207b, 0x118217b, 0x118227b, 0x118237b,
  0x11c207b, 0x11c217b, 0x11c227b, 0x11c237b, 0x31c00016, 0x31c00096, 0x31c00116, 0x31c00196, 0x31c70016, 0x31c70096, 0x31c70116, 0x31c70196, 0x31ce0016, 0x31ce0096,
  0x31ce0116, 0x31ce0196, 0x31d50016, 0x31d50096, 0x31d50116, 0x7f, 0x17f, 0x31d50196, 0x31c00026, 0x31c000a6, 0x31c00126, 0x31c001a6, 0x31c70026, 0x31c700a6,
  0x31c70126, 0x31c701a6, 0x31ce0026, 0x31ce00a6, 0x31ce0126, 0x31ce01a6, 0x31d50026, 0x31d500a6, 0x31d50126, 0x31d501a6, 0x31c00036, 0x31c000b6, 0x31c00136, 0x31c001b6,
  0x31c70036, 0x31c700b6, 0x31c70136, 0x31c701b6, 0x31ce0036, 0x31ce00b6, 0x31ce0136, 0x31ce01b6, 0x31d50036, 0x200207d, 0x200217d, 0x200227d, 0x200237d, 0x200247d,
  0x200257d, 0x200267d, 0x200277d, 0x200287d, 0x200297d, 0x2002a7d, 0x2002b7d, 0x2002c7d, 0x2002d7d, 0x2002e7d, 0x2002f7d, 0x200307d, 0x200317d, 0x200327d,
  0x200337d, 0x200347d, 0x200357d, 0x200367d, 0x200377d, 0x200387d, 0x200397d, 0x2003a7d, 0x2003b7d, 0x31d500b6, 0x31d50136, 0x31d501b6, 0x31c00046, 0x31c000c6,
  0x31c00146, 0x31c001c6, 0x31c70046, 0x31c700c6, 0x31c70146, 0x31c701c6, 0x31ce0046, 0x31ce00c6, 0x31ce0146, 0x31ce01c6, 0x31d50046, 0x31d500c6, 0x31d50146, 0x31d501c6,
  0x31c00056, 0x31c000d6, 0x31c00156, 0x31c001d6, 0x31c70056, 0x31c700d6, 0x31c70156, 0x31c701d6, 0x31ce0056, 0x31ce00d6, 0x31ce0156, 0x31ce01d6, 0x31d50056, 0x31d500d6,
  0x31d50156, 0x31d501d6, 0x1c00066, 0x1c00166, 0x1c70066, 0x1c70166, 0x1ce0066, 0x1ce0166, 0x1d50066, 0x1d50166, 0xe0207e, 0xe0217e, 0xe0227e, 0xe0237e,
  0xe3a07e, 0xe3a17e, 0xe3a27e, 0xe3a37e, 0xe7207e, 0xe7217e, 0xe7227e, 0xe7237e, 0xeaa07e, 0xeaa17e, 0xeaa27e, 0xeaa37e, 0xee207e, 0xee217e,
  0xee227e, 0xee237e, 0xf1a07e, 0xf1a17e, 0xf1a27e, 0xf1a37e, 0xf5207e, 0xf5217e, 0xf5227e, 0xf5237e, 0xf8a07e, 0xf8a17e, 0xf8a27e, 0xf8a37e,
};

void build_lists(HList& a, HList& b) {
  a.n = b.n = 0;
  for (uint32_t v : h_items1) a.it[a.n++] = v;
  for (uint32_t v : h_items2) b.it[b.n++] = v;
  a.head = FL_HEAD; a.tbase = 0;
  b.head = FL_HEAD2; b.tbase = a.n;
}

typedef CUresult (*EncodeFn)(CUtensorMap*, CUtensorMapDataType, cuuint32_t, void*, const cuuint64_t*, const cuuint64_t*,
                             const cuuint32_t*, const cuuint32_t*, CUtensorMapInterleave, CUtensorMapSwizzle,
                             CUtensorMapL2promotion, CUtensorMapFloatOOBfill);

void make_map(EncodeFn fn, CUtensorMap* m, const void* p, uint64_t cols, uint64_t rows, uint32_t bc, uint32_t br, CUtensorMapSwizzle sw) {
  cuuint64_t dims[2] = {cols, rows};
  cuuint64_t strides[1] = {cols * 2};
  cuuint32_t box[2] = {bc, br};
  cuuint32_t es[2] = {1, 1};
  fn(m, CU_TENSOR_MAP_DATA_TYPE_BFLOAT16, 2, const_cast<void*>(p), dims, strides, box, es, CU_TENSOR_MAP_INTERLEAVE_NONE, sw,
     CU_TENSOR_MAP_L2_PROMOTION_L2_128B, CU_TENSOR_MAP_FLOAT_OOB_FILL_NONE);
}

}

extern "C" void kernel_launch(void* const* d_in, const int* in_sizes, int n_in, void* d_out, int out_size) {
  const __nv_bfloat16* x = (const __nv_bfloat16*)d_in[0];
  const __nv_bfloat16* mem0 = (const __nv_bfloat16*)d_in[1];
  const __nv_bfloat16* cvec = (const __nv_bfloat16*)d_in[11];
  static EncodeFn enc = nullptr;
  if (!enc) {
    cudaDriverEntryPointQueryResult qr;
    void* fp = nullptr;
    cudaGetDriverEntryPoint("cuTensorMapEncodeTiled", &fp, cudaEnableDefault, &qr);
    enc = (EncodeFn)fp;
    cudaFuncSetAttribute(kernel_R, cudaFuncAttributeMaxDynamicSharedMemorySize, R_SMEM);
    cudaFuncSetAttribute(kernel_H, cudaFuncAttributeMaxDynamicSharedMemorySize, H_SMEM);
  }
  CUtensorMap tmq, tmk, tmv, tmo, tmm;
  make_map(enc, &tmm, d_in[12], 6144, 1024, 64, 64, CU_TENSOR_MAP_SWIZZLE_NONE);
  make_map(enc, &tmq, d_in[2], 4096, 1024, 64, 64, CU_TENSOR_MAP_SWIZZLE_128B);
  make_map(enc, &tmk, d_in[3], 4096, 1024, 64, 64, CU_TENSOR_MAP_SWIZZLE_128B);
  make_map(enc, &tmv, d_in[4], 4096, 1024, 64, 64, CU_TENSOR_MAP_SWIZZLE_128B);
  make_map(enc, &tmo, d_in[5], 1024, 4096, 16, 128, CU_TENSOR_MAP_SWIZZLE_32B);
  RDesc dsc;
  for (int k = 0; k < 32; k++) {
    dsc.tok[k] = mkdesc(0x400 + (k < 16 ? R_GA : R_GB) + ((k & 15) >> 2) * 4096 + (k & 3) * 256, 128, 1024, 0);
    dsc.tail_a[k] = mkdesc(0x400 + R_TAIL + k * 2048, 1024, 1024, 1);
    if (k < 16) dsc.tail_b[k] = mkdesc(0x400 + R_GA + k * 256, 128, 4096, 0);
  }
  kernel_R<<<96, 256, R_SMEM, cudaStreamPerThread>>>(tmq, tmk, tmv, tmo, tmm, x, mem0, cvec, dsc);

  CUtensorMap ho, h1, h3, h2, hm, hx, hy;
  make_map(enc, &ho, d_in[5], 1024, 4096, 64, 64, CU_TENSOR_MAP_SWIZZLE_128B);
  make_map(enc, &h1, d_in[8], F_, 1024, 64, 64, CU_TENSOR_MAP_SWIZZLE_128B);
  make_map(enc, &h3, d_in[9], F_, 1024, 64, 64, CU_TENSOR_MAP_SWIZZLE_128B);
  make_map(enc, &h2, d_in[10], 1024, F_, 64, 64, CU_TENSOR_MAP_SWIZZLE_128B);
  make_map(enc, &hm, d_in[12], 6144, 1024, 64, 64, CU_TENSOR_MAP_SWIZZLE_128B);
  make_map(enc, &hx, d_out, 1024, S_, 64, 128, CU_TENSOR_MAP_SWIZZLE_128B);
  make_map(enc, &hy, d_out, 1024, S_, 64, 64, CU_TENSOR_MAP_SWIZZLE_128B);
  HList list1, list2;
  build_lists(list1, list2);
  HWeights rw;
  for (int i = 0; i < 4; i++) rw.p[i] = (const uint8_t*)d_in[2 + i];
  cudaLaunchConfig_t cfg = {};
  cfg.gridDim = dim3(NH1); cfg.blockDim = dim3(384); cfg.dynamicSmemBytes = H_SMEM; cfg.stream = cudaStreamPerThread;
  cudaLaunchAttribute at[2];
  at[0].id = cudaLaunchAttributeProgrammaticStreamSerialization;
  at[0].val.programmaticStreamSerializationAllowed = 1;
  at[1].id = cudaLaunchAttributeClusterDimension;
  at[1].val.clusterDim.x = 2; at[1].val.clusterDim.y = 1; at[1].val.clusterDim.z = 1;
  cfg.attrs = at; cfg.numAttrs = 1;
  cudaLaunchKernelEx(&cfg, kernel_H, ho, h1, h3, h2, hm, hx, hy, x, cvec, (__nv_bfloat16*)d_out, rw, list1);
  cfg.numAttrs = 2; cfg.gridDim = dim3(NH2);
  cudaLaunchKernelEx(&cfg, kernel_H, ho, h1, h3, h2, hm, hx, hy, x, cvec, (__nv_bfloat16*)d_out, rw, list2);
}
```

```cpp
#include <cuda_runtime.h>
#include <cuda_bf16.h>
#include <cuda.h>
#include <stdint.h>
#include <type_traits>

namespace {

constexpr int S_ = 2048, D_ = 1024, NSEG = 64, F_ = 3584;

__device__ __align__(1024) uint8_t g_h[S_ * D_ * 2];
__device__ __align__(1024) uint8_t g_att[S_ * 4096 * 2];
__device__ __align__(1024) uint8_t g_act[S_ * F_ * 2];
__device__ __align__(1024) uint8_t g_w13s[28 * 16 * 32768];
__device__ __align__(1024) uint8_t g_ext[16 * 2560];
__device__ __align__(1024) uint8_t g_bext[28 * 4096];
__device__ __align__(1024) __nv_bfloat16 g_gate[2 * D_];
__device__ __align__(1024) float g_slot[4 * 3 * 8 * 4 * 32 * 4];
__device__ __align__(128) __nv_bfloat16 g_mod[6 * D_];
__device__ __align__(128) float g_modp[3 * 2 * D_];
__device__ __align__(128) uint32_t g_flags[1024];
constexpr int FL_S1 = 0, FL_S2 = 32, FL_MOD = 64, FL_HEAD = 96, FL_EXIT = 128, FL_WS = 160, FL_GO = 192, FL_HEAD2 = 224, FL_ATT = 256, FL_XT = 384, FL_OUT = 512, FL_F1 = 640, FL_STAT = 768;

__device__ __forceinline__ uint32_t smem_u32(const void* p) { return (uint32_t)__cvta_generic_to_shared(p); }
__device__ __forceinline__ uint32_t mapa(uint32_t a, uint32_t r) { uint32_t o; asm("mapa.shared::cluster.u32 %0, %1, %2;" : "=r"(o) : "r"(a), "r"(r)); return o; }
__device__ __forceinline__ uint32_t pack2(float a, float b) { uint32_t r; asm("cvt.rn.bf16x2.f32 %0, %1, %2;" : "=r"(r) : "f"(b), "f"(a)); return r; }
__device__ __forceinline__ float bf_lo(uint32_t w) { return __uint_as_float(w << 16); }
__device__ __forceinline__ float bf_hi(uint32_t w) { return __uint_as_float(w & 0xffff0000u); }
__device__ __forceinline__ float ex2(float x) { float y; asm("ex2.approx.ftz.f32 %0, %1;" : "=f"(y) : "f"(x)); return y; }
__device__ __forceinline__ float rcp(float x) { float y; asm("rcp.approx.ftz.f32 %0, %1;" : "=f"(y) : "f"(x)); return y; }
__device__ __forceinline__ uint32_t clk32() { uint64_t c; asm volatile("mov.u64 %0, %%clock64;" : "=l"(c) :: "memory"); return (uint32_t)c; }

__device__ __forceinline__ void mbar_init(uint32_t b, uint32_t n) { asm volatile("mbarrier.init.shared::cta.b64 [%0], %1;" :: "r"(b), "r"(n) : "memory"); }
__device__ __forceinline__ void mbar_arrive(uint32_t b) { asm volatile("mbarrier.arrive.shared::cta.b64 _, [%0];" :: "r"(b) : "memory"); }
__device__ __forceinline__ void mbar_expect(uint32_t b, uint32_t n) { asm volatile("mbarrier.arrive.expect_tx.shared::cta.b64 _, [%0], %1;" :: "r"(b), "r"(n) : "memory"); }
__device__ __forceinline__ uint32_t mbar_try(uint32_t b, uint32_t par) {
  uint32_t ok;
  asm volatile("{\n.reg .pred p;\nmbarrier.try_wait.parity.shared::cta.b64 p, [%1], %2;\nselp.u32 %0, 1, 0, p;\n}" : "=r"(ok) : "r"(b), "r"(par) : "memory");
  return ok;
}
__device__ __forceinline__ void mbar_wait(uint32_t b, uint32_t par) {
  asm volatile("{\n.reg .pred p;\n"
               "LOOP:\n"
               "mbarrier.try_wait.parity.shared::cta.b64 p, [%0], %1;\n"
               "@!p bra.uni LOOP;\n}" :: "r"(b), "r"(par) : "memory");
}
__device__ __forceinline__ void mbar_wait_safe(uint32_t b, uint32_t par) {
  uint32_t c = 0;
  while (!mbar_try(b, par)) { if (++c > 4000000u) __trap(); }
}
__device__ __forceinline__ bool elect_one() {
  uint32_t p;
  asm volatile("{\n.reg .pred p;\nelect.sync _|p, 0xffffffff;\nselp.u32 %0, 1, 0, p;\n}" : "=r"(p));
  return p;
}
__device__ __forceinline__ void sched_fence(uint32_t x, uint32_t y) { asm volatile("{\n.reg .pred p;\nsetp.eq.u32 p, %0, %1;\n@p trap;\n}" :: "r"(x), "r"(y) : "memory"); }
template <class T> __device__ __forceinline__ T opaque32(T x) { asm volatile("" : "+r"(x)); return x; }
template <class T> __device__ __forceinline__ T opaque64(T x) { asm volatile("" : "+l"(x)); return x; }
template <int ID, int N> __device__ __forceinline__ void bar_sync() { asm volatile("bar.sync %0, %1;" :: "n"(ID), "n"(N) : "memory"); }
template <int ID, int N> __device__ __forceinline__ void bar_arrive() { asm volatile("bar.arrive %0, %1;" :: "n"(ID), "n"(N) : "memory"); }
__device__ __forceinline__ void fence_async_smem() { asm volatile("fence.proxy.async.shared::cta;" ::: "memory"); }
__device__ __forceinline__ void fence_async_all() { asm volatile("fence.proxy.async;" ::: "memory"); }
__device__ __forceinline__ void fence_gpu() { asm volatile("fence.acq_rel.gpu;" ::: "memory"); }
__device__ __forceinline__ void red_add_u32(uint32_t* p, uint32_t v) { asm volatile("red.relaxed.gpu.global.add.u32 [%0], %1;" :: "l"(p), "r"(v) : "memory"); }
__device__ __forceinline__ uint32_t ld_acquire(const uint32_t* p) { uint32_t v; asm volatile("ld.acquire.gpu.global.u32 %0, [%1];" : "=r"(v) : "l"(p) : "memory"); return v; }
__device__ __forceinline__ void wait_flag(const uint32_t* p, uint32_t target) {
  uint32_t c = 0;
  while (ld_acquire(p) < target) { if (++c > 20000000u) __trap(); __nanosleep(20); }
}

__device__ __forceinline__ void tma2d(uint32_t dst, const CUtensorMap* m, int c0, int c1, uint32_t bar) {
  asm volatile("cp.async.bulk.tensor.2d.shared::cluster.global.mbarrier::complete_tx::bytes [%0], [%1, {%3, %4}], [%2];"
               :: "r"(dst), "l"(m), "r"(bar), "r"(c0), "r"(c1) : "memory");
}
constexpr uint64_t L2_NORMAL = 0x1000000000000000ull, L2_FIRST = 0x12F0000000000000ull;
__device__ __forceinline__ void tma2d_p(uint32_t dst, const CUtensorMap* m, int c0, int c1, uint32_t bar, uint64_t pol) {
  asm volatile("cp.async.bulk.tensor.2d.shared::cluster.global.mbarrier::complete_tx::bytes.L2::cache_hint [%0], [%1, {%3, %4}], [%2], %5;"
               :: "r"(dst), "l"(m), "r"(bar), "r"(c0), "r"(c1), "l"(pol) : "memory");
}
__device__ __forceinline__ void bulk_g2s_p(uint32_t dst, const void* src, uint32_t bytes, uint32_t bar, uint64_t pol) {
  asm volatile("cp.async.bulk.shared::cluster.global.mbarrier::complete_tx::bytes.L2::cache_hint [%0], [%1], %2, [%3], %4;"
               :: "r"(dst), "l"(src), "r"(bytes), "r"(bar), "l"(pol) : "memory");
}
#define POL_RW L2_FIRST
__device__ __forceinline__ void tma2d_prefetch_p(const CUtensorMap* m, int c0, int c1, uint64_t pol) {
  asm volatile("cp.async.bulk.prefetch.tensor.2d.L2.global.L2::cache_hint [%0, {%1, %2}], %3;" :: "l"(m), "r"(c0), "r"(c1), "l"(pol) : "memory");
}
__device__ __forceinline__ void tma2d_prefetch(const CUtensorMap* m, int c0, int c1) {
  asm volatile("cp.async.bulk.prefetch.tensor.2d.L2.global [%0, {%1, %2}];" :: "l"(m), "r"(c0), "r"(c1) : "memory");
}
__device__ __forceinline__ void bulk_g2s(uint32_t dst, const void* src, uint32_t bytes, uint32_t bar) {
  asm volatile("cp.async.bulk.shared::cluster.global.mbarrier::complete_tx::bytes [%0], [%1], %2, [%3];"
               :: "r"(dst), "l"(src), "r"(bytes), "r"(bar) : "memory");
}
__device__ __forceinline__ void bulk_s2s(uint32_t dst, uint32_t src, uint32_t bytes, uint32_t bar) {
  asm volatile("cp.async.bulk.shared::cluster.shared::cta.mbarrier::complete_tx::bytes [%0], [%1], %2, [%3];"
               :: "r"(dst), "r"(src), "r"(bytes), "r"(bar) : "memory");
}
__device__ __forceinline__ void st_async1(uint32_t dst, uint32_t a, uint32_t bar) {
  asm volatile("st.async.shared::cluster.mbarrier::complete_tx::bytes.b32 [%0], %1, [%2];" :: "r"(dst), "r"(a), "r"(bar) : "memory");
}
__device__ __forceinline__ void st_async2(uint32_t dst, uint32_t a, uint32_t b, uint32_t bar) {
  asm volatile("st.async.shared::cluster.mbarrier::complete_tx::bytes.v2.b32 [%0], {%1, %2}, [%3];" :: "r"(dst), "r"(a), "r"(b), "r"(bar) : "memory");
}
__device__ __forceinline__ void st_async4(uint32_t dst, const uint32_t* r, uint32_t bar) {
  asm volatile("st.async.shared::cluster.mbarrier::complete_tx::bytes.v4.b32 [%0], {%1, %2, %3, %4}, [%5];"
               :: "r"(dst), "r"(r[0]), "r"(r[1]), "r"(r[2]), "r"(r[3]), "r"(bar) : "memory");
}
__device__ __forceinline__ void sts32(uint32_t a, uint32_t v) { asm volatile("st.shared.b32 [%0], %1;" :: "r"(a), "r"(v) : "memory"); }
__device__ __forceinline__ void sts64(uint32_t a, uint32_t x, uint32_t y) { asm volatile("st.shared.v2.b32 [%0], {%1, %2};" :: "r"(a), "r"(x), "r"(y) : "memory"); }
__device__ __forceinline__ void sts128(uint32_t a, uint32_t x, uint32_t y, uint32_t z, uint32_t w) {
  asm volatile("st.shared.v4.b32 [%0], {%1, %2, %3, %4};" :: "r"(a), "r"(x), "r"(y), "r"(z), "r"(w) : "memory");
}
__device__ __forceinline__ void lds128(uint32_t* r, uint32_t a) {
  asm volatile("ld.shared.v4.b32 {%0, %1, %2, %3}, [%4];" : "=r"(r[0]), "=r"(r[1]), "=r"(r[2]), "=r"(r[3]) : "r"(a) : "memory");
}
__device__ __forceinline__ uint32_t lds32(uint32_t a) { uint32_t r; asm volatile("ld.shared.b32 %0, [%1];" : "=r"(r) : "r"(a) : "memory"); return r; }
__device__ __forceinline__ void lds64(uint32_t* r, uint32_t a) {
  asm volatile("ld.shared.v2.b32 {%0, %1}, [%2];" : "=r"(r[0]), "=r"(r[1]) : "r"(a) : "memory");
}
__device__ __forceinline__ void lds128f(float* r, uint32_t a) {
  asm volatile("ld.shared.v4.f32 {%0, %1, %2, %3}, [%4];" : "=f"(r[0]), "=f"(r[1]), "=f"(r[2]), "=f"(r[3]) : "r"(a) : "memory");
}
__device__ __forceinline__ void lds64f(float* r, uint32_t a) {
  asm volatile("ld.shared.v2.f32 {%0, %1}, [%2];" : "=f"(r[0]), "=f"(r[1]) : "r"(a) : "memory");
}
__device__ __forceinline__ void ldsm4(uint32_t* r, uint32_t a) {
  asm volatile("ldmatrix.sync.aligned.m8n8.x4.shared.b16 {%0, %1, %2, %3}, [%4];" : "=r"(r[0]), "=r"(r[1]), "=r"(r[2]), "=r"(r[3]) : "r"(a) : "memory");
}
__device__ __forceinline__ void ldsm4t(uint32_t* r, uint32_t a) {
  asm volatile("ldmatrix.sync.aligned.m8n8.x4.trans.shared.b16 {%0, %1, %2, %3}, [%4];" : "=r"(r[0]), "=r"(r[1]), "=r"(r[2]), "=r"(r[3]) : "r"(a) : "memory");
}
__device__ __forceinline__ void ldsm2(uint32_t* r, uint32_t a) {
  asm volatile("ldmatrix.sync.aligned.m8n8.x2.shared.b16 {%0, %1}, [%2];" : "=r"(r[0]), "=r"(r[1]) : "r"(a) : "memory");
}
__device__ __forceinline__ void stsm4(uint32_t a, const uint32_t* r) {
  asm volatile("stmatrix.sync.aligned.m8n8.x4.shared.b16 [%0], {%1, %2, %3, %4};" :: "r"(a), "r"(r[0]), "r"(r[1]), "r"(r[2]), "r"(r[3]) : "memory");
}
__device__ __forceinline__ uint32_t hadd2(uint32_t a, uint32_t b) { uint32_t t; asm("add.rn.bf16x2 %0, %1, %2;" : "=r"(t) : "r"(a), "r"(b)); return t; }
__device__ __forceinline__ uint32_t hmax2(uint32_t a, uint32_t b) { uint32_t t; asm("max.bf16x2 %0, %1, %2;" : "=r"(t) : "r"(a), "r"(b)); return t; }
__device__ __forceinline__ void ldsm2t(uint32_t* r, uint32_t a) {
  asm volatile("ldmatrix.sync.aligned.m8n8.x2.trans.shared.b16 {%0, %1}, [%2];" : "=r"(r[0]), "=r"(r[1]) : "r"(a) : "memory");
}
__device__ __forceinline__ uint32_t movm(uint32_t x) { uint32_t y; asm volatile("movmatrix.sync.aligned.m8n8.trans.b16 %0, %1;" : "=r"(y) : "r"(x)); return y; }
__device__ __forceinline__ void hmma(float* d, uint32_t a0, uint32_t a1, uint32_t a2, uint32_t a3, uint32_t b0, uint32_t b1) {
  asm volatile("mma.sync.aligned.m16n8k16.row.col.f32.bf16.bf16.f32 {%0,%1,%2,%3}, {%4,%5,%6,%7}, {%8,%9}, {%0,%1,%2,%3};"
               : "+f"(d[0]), "+f"(d[1]), "+f"(d[2]), "+f"(d[3]) : "r"(a0), "r"(a1), "r"(a2), "r"(a3), "r"(b0), "r"(b1));
}
__device__ __forceinline__ void hmma0(float* d, uint32_t a0, uint32_t a1, uint32_t a2, uint32_t a3, uint32_t b0, uint32_t b1) {
  asm volatile("mma.sync.aligned.m16n8k16.row.col.f32.bf16.bf16.f32 {%0,%1,%2,%3}, {%4,%5,%6,%7}, {%8,%9}, {%10,%10,%10,%10};"
               : "=f"(d[0]), "=f"(d[1]), "=f"(d[2]), "=f"(d[3]) : "r"(a0), "r"(a1), "r"(a2), "r"(a3), "r"(b0), "r"(b1), "f"(0.f));
}
__device__ __forceinline__ void hmma_k8(float* d, uint32_t a0, uint32_t a1, uint32_t b0) {
  asm volatile("mma.sync.aligned.m16n8k8.row.col.f32.bf16.bf16.f32 {%0,%1,%2,%3}, {%4,%5}, {%6}, {%0,%1,%2,%3};"
               : "+f"(d[0]), "+f"(d[1]), "+f"(d[2]), "+f"(d[3]) : "r"(a0), "r"(a1), "r"(b0));
}
__host__ __device__ constexpr uint64_t mkdesc(uint32_t addr, uint32_t lbo, uint32_t sbo, uint32_t sw) {
  return (uint64_t)((addr & 0x3FFFF) >> 4) | ((uint64_t)(lbo >> 4) << 16) | ((uint64_t)(sbo >> 4) << 32) | ((uint64_t)sw << 62);
}
#define WG_FENCE() asm volatile("wgmma.fence.sync.aligned;" ::: "memory")
#define WG_COMMIT() asm volatile("wgmma.commit_group.sync.aligned;" ::: "memory")
#define WG_WAIT(n) asm volatile("wgmma.wait_group.sync.aligned " #n ";" ::: "memory")
template <int N> __device__ __forceinline__ void reg_fence(float* d) {
#pragma unroll
  for (int i = 0; i < N; i++) asm volatile("" : "+f"(d[i]) :: "memory");
}
template <int N> __device__ __forceinline__ void zero_regs(float* d) {
#pragma unroll
  for (int i = 0; i < N; i++) asm volatile("mov.b32 %0, 0;" : "=f"(d[i]));
}
template <int SD>
__device__ __forceinline__ void wg_rs32(float* d, uint32_t a0, uint32_t a1, uint32_t a2, uint32_t a3, uint64_t b) {
  asm volatile("wgmma.mma_async.sync.aligned.m64n32k16.f32.bf16.bf16 {%0,%1,%2,%3,%4,%5,%6,%7,%8,%9,%10,%11,%12,%13,%14,%15}, {%16,%17,%18,%19}, %20, %21, 1, 1, 0;"
               : "+f"(d[0]), "+f"(d[1]), "+f"(d[2]), "+f"(d[3]), "+f"(d[4]), "+f"(d[5]), "+f"(d[6]), "+f"(d[7]),
                 "+f"(d[8]), "+f"(d[9]), "+f"(d[10]), "+f"(d[11]), "+f"(d[12]), "+f"(d[13]), "+f"(d[14]), "+f"(d[15])
               : "r"(a0), "r"(a1), "r"(a2), "r"(a3), "l"(b), "n"(SD));
}
template <int SD>
__device__ __forceinline__ void wg_rs40(float* d, const uint32_t* a, uint64_t b) {
  asm volatile("wgmma.mma_async.sync.aligned.m64n40k16.f32.bf16.bf16 {%0,%1,%2,%3,%4,%5,%6,%7,%8,%9,%10,%11,%12,%13,%14,%15,%16,%17,%18,%19}, {%20,%21,%22,%23}, %24, %25, 1, 1, 0;"
               : "+f"(d[0]), "+f"(d[1]), "+f"(d[2]), "+f"(d[3]), "+f"(d[4]), "+f"(d[5]), "+f"(d[6]), "+f"(d[7]),
                 "+f"(d[8]), "+f"(d[9]), "+f"(d[10]), "+f"(d[11]), "+f"(d[12]), "+f"(d[13]), "+f"(d[14]), "+f"(d[15]),
                 "+f"(d[16]), "+f"(d[17]), "+f"(d[18]), "+f"(d[19])
               : "r"(a[0]), "r"(a[1]), "r"(a[2]), "r"(a[3]), "l"(b), "n"(SD));
}
template <int TB>
__device__ __forceinline__ void wg_ss40(float* d, uint64_t a, uint64_t b) {
  asm volatile("wgmma.mma_async.sync.aligned.m64n40k16.f32.bf16.bf16 {%0,%1,%2,%3,%4,%5,%6,%7,%8,%9,%10,%11,%12,%13,%14,%15,%16,%17,%18,%19}, %20, %21, 1, 1, 1, 1, %22;"
               : "+f"(d[0]), "+f"(d[1]), "+f"(d[2]), "+f"(d[3]), "+f"(d[4]), "+f"(d[5]), "+f"(d[6]), "+f"(d[7]),
                 "+f"(d[8]), "+f"(d[9]), "+f"(d[10]), "+f"(d[11]), "+f"(d[12]), "+f"(d[13]), "+f"(d[14]), "+f"(d[15]),
                 "+f"(d[16]), "+f"(d[17]), "+f"(d[18]), "+f"(d[19])
               : "l"(a), "l"(b), "n"(TB));
}
template <int T>
__device__ __forceinline__ void wg_ss32(float* d, uint64_t a, uint64_t b) {
  asm volatile("wgmma.mma_async.sync.aligned.m64n32k16.f32.bf16.bf16 {%0,%1,%2,%3,%4,%5,%6,%7,%8,%9,%10,%11,%12,%13,%14,%15}, %16, %17, 1, 1, 1, %18, %18;"
               : "+f"(d[0]), "+f"(d[1]), "+f"(d[2]), "+f"(d[3]), "+f"(d[4]), "+f"(d[5]), "+f"(d[6]), "+f"(d[7]),
                 "+f"(d[8]), "+f"(d[9]), "+f"(d[10]), "+f"(d[11]), "+f"(d[12]), "+f"(d[13]), "+f"(d[14]), "+f"(d[15])
               : "l"(a), "l"(b), "n"(T));
}

constexpr int R_TAIL = 0;
constexpr int R_WO = 65536;
constexpr int R_QK = R_WO + 86016;
constexpr int R_P = R_QK + 10240;
constexpr int R_GA = R_P + 6400;
constexpr int R_M2 = R_GA + 16384;
constexpr int R_M1 = R_M2 + 7168;
constexpr int R_GB = R_M1 + 9216;
constexpr int R_VT = R_GB + 16384;
constexpr int R_VM = R_VT + 8192;
constexpr int R_XS = R_VM + 2048;
constexpr int R_OX = R_XS + 1280;
constexpr int R_BAR = R_OX + 2048;
constexpr int R_TRC = R_BAR + 256;
constexpr int R_SMEM = R_TRC + 1024;
constexpr int B_MB = 0, B_XS = 32, B_VM = 40, B_VT = 48, B_TS = 56, B_FA = 64, B_FB = 72, B_TAIL = 80, B_WO = 88, B_STG = 96, B_WM = 128, B_X = 136;
constexpr int NB_A = 1, NB_B = 2, NB_X = 3, NB_C = 4, NB_D = 5, NB_E = 6, NB_F = 7, NB_G = 8, NB_H = 9, NB_S = 10, NB_E2 = 11, NB_P = 12, NB_W0 = 13;

#define POLL_DELAY 750
#define POLL_DELAY1 700
#define P1K -1
#define P2K -1
#define ZS 2
#define HPF 4
#define PF1 2
#define PF2 2
#define PF3 2
#define PF4 0
#define WO_POS 1
#define WO_LATE 1
#define S2E 0
#define RF_FIRST 0
#define BX_I 5
#define NCH 4
#define TOP2 0
#define CX_I 13
#define ATT_LATE 0
#define V_FENCE 1
#define SELF_STAS 1
#define Q_FENCE 1
#define ND_K 3
#define TRACE(i)
#define TS(i)

__device__ __forceinline__ int rot_chunk(int c, int rank) {
  int G = c;
  if (c < 9) { G = c + 3 * rank; if (G >= 9) G -= 9; }
  return G;
}
__device__ __forceinline__ int wo_tile(int i, int rank) {
  if (i < 12) return 12 * rank + i;
  const int r = i - 12 + 9 * rank;
  return r < 16 ? 48 + r : 20 + r;
}
__device__ __forceinline__ void load_chunk(uint32_t dst, int seg, int G, uint32_t bar) {
  mbar_expect(bar, 4096);
  bulk_g2s(dst, g_h + (size_t)(seg * 16 + G) * 4096, 4096, bar);
}
__device__ __forceinline__ void load_red(uint32_t* v, const float* p) {
#pragma unroll
  for (int j = 0; j < 2; j++)
    asm volatile("ld.relaxed.gpu.global.v4.u32 {%0, %1, %2, %3}, [%4];"
                 : "=r"(v[4 * j]), "=r"(v[4 * j + 1]), "=r"(v[4 * j + 2]), "=r"(v[4 * j + 3]) : "l"(p + j * 256) : "memory");
}
__device__ __forceinline__ bool red_done(const uint32_t* v) { return __all_sync(0xffffffffu, (v[3] & v[7]) == 0x42000000u); }
__device__ __forceinline__ uint32_t finish_red(uint32_t* v, const float* p) {
  uint32_t tries = 0;
  if (__builtin_expect(!red_done(v), 0)) {
    do { if (++tries > 20000000u) __trap(); load_red(v, p); } while (!red_done(v));
  }
  return tries;
}
__device__ __forceinline__ void exp10(float* sv, const uint32_t* x) {
  constexpr float SC = 0.08838834764831845f * 1.4426950408889634f;
  uint32_t m2 = hmax2(hmax2(hmax2(x[0], x[1]), hmax2(x[2], x[3])), x[4]);
  m2 = hmax2(m2, __shfl_xor_sync(0xffffffffu, m2, 1));
  m2 = hmax2(m2, __shfl_xor_sync(0xffffffffu, m2, 2));
  const float nm = -fmaxf(bf_lo(m2), bf_hi(m2)) * SC;
#pragma unroll
  for (int j = 0; j < 5; j++) { sv[2 * j] = ex2(fmaf(bf_lo(x[j]), SC, nm)); sv[2 * j + 1] = ex2(fmaf(bf_hi(x[j]), SC, nm)); }
}

__device__ __forceinline__ uint32_t arm_size(int w, bool isC) {
  return w == 0 ? (isC ? 1280 : 640) : w == 1 ? (isC ? 0 : 2048) : w == 2 ? (isC ? 0 : 8192) : (isC ? 0 : 1792);
}
__device__ __forceinline__ void forward_initial(uint32_t sb, uint32_t rank, int wg, int w, int lane) {
  const uint32_t bars = sb + R_BAR, to1 = rank == 0 ? 2u << 24 : 0u - (1u << 24), to2 = rank == 2 ? 0u - (2u << 24) : 1u << 24;
  if (wg == 1 && w > 0 && elect_one()) mbar_expect(bars + B_MB + 8 * w, w < 3 ? 3072 : SELF_STAS ? 28 * 256 : rank == 2 ? 18 * 256 : 19 * 256);
  if (wg == 1 && w == 3 && rank != 2) return;
  const float* slot = g_slot + (rank * 1024 + (wg * 4 + w) * 128 + lane) * 4 + 3 * 12288 + 4 * 32;
  uint32_t v[8], u[6];
  load_red(v, slot);
  finish_red(v, slot);
#pragma unroll
  for (int j = 0; j < 6; j++) u[j] = movm(v[4 * (j / 3) + j % 3]);
  if (wg == 0) {
    const uint32_t a = sb + lane * 16 + R_M1 + w * 768, a2 = sb + lane * 8 + R_M1 + 512 + w * 768;
    st_async4(a + to1 + 3072, u, bars + to1 + B_MB + 8); st_async2(a2 + to1 + 3072, u[4], u[5], bars + to1 + B_MB + 8);
    sts128(a, u[0], u[1], u[2], u[3]); sts64(a2, u[4], u[5]);
    __syncwarp();
    if (elect_one()) mbar_arrive(bars + B_MB);
    st_async4(a + to2 + 6144, u, bars + to2 + B_MB + 16); st_async2(a2 + to2 + 6144, u[4], u[5], bars + to2 + B_MB + 16);
  } else {
    const uint32_t a = sb + lane * 4 + R_M2 + rank * 2304 + w * 768;
    const int n = w < 3 ? 6 : 2;
#pragma unroll
    for (int j = 0; j < 6; j++) if (j < n) { st_async1(a + to1 + j * 128, u[j], bars + to1 + B_MB + 24); st_async1(a + to2 + j * 128, u[j], bars + to2 + B_MB + 24); }
    if (SELF_STAS) {
#pragma unroll
      for (int j = 0; j < 6; j++) if (j < n) st_async1(a + j * 128, u[j], bars + B_MB + 24);
    } else {
#pragma unroll
      for (int j = 0; j < 6; j++) if (j < n) sts32(a + j * 128, u[j]);
      __syncwarp();
      if (elect_one()) mbar_arrive(bars + B_MB + 24);
    }
  }
}
struct RDesc { uint64_t tok[32], tail_b[16], tail_a[32]; };

template <int WG>
__device__ __forceinline__ void r_main(const uint32_t (&W)[48][4], const RDesc& dsc, int head, uint32_t rank, int lane_, int w) {
  const uint32_t sb = (rank << 24) + 0x400, bars = sb + R_BAR;
  const uint32_t to1 = rank == 0 ? 2u << 24 : 0u - (1u << 24), to2 = rank == 2 ? 0u - (2u << 24) : 1u << 24;
  const bool isC = rank == 2;
  const int lane = opaque32(lane_), warp = WG * 4 + w;
  const int gl = rot_chunk(4 * (lane & 3) + w, rank);
  const int g0 = __shfl_sync(0xffffffffu, gl, 0), g1 = __shfl_sync(0xffffffffu, gl, 1), g2 = __shfl_sync(0xffffffffu, gl, 2);
  const uint32_t arm_bytes = arm_size(w, isC);

#define L16 opaque32(sb + opaque32(lane) * 16)
#define L8 opaque32(sb + opaque32(lane) * 8)
#define L4 opaque32(sb + opaque32(lane) * 4)
#define LV opaque32(sb + R_VT + ((opaque32(lane) >> 3) & 1) * 512 + (opaque32(lane) >> 4) * 128 + (opaque32(lane) & 7) * 16)
#define SLOT(st) opaque64(slot0 + ((st) & 3) * 12288 + ((st) & 4) * 32)
  float* const slot0 = opaque64(g_slot + (rank * 1024 + warp * 128 + lane) * 4);
  const uint32_t woa = opaque32(sb + R_WO + warp * 12288 + ((lane >> 4) * 8 + (lane & 7)) * 32 + ((((lane >> 3) ^ (lane >> 2)) & 1) << 4));
  const bool has_wo = WG == 0 || isC || w < 3;
  float acc[20];
  uint32_t pk[8] = {0u, 0u, 0u, 0u, 0u, 0u, 0u, 0u};

  auto forward = [&](auto rd, const uint32_t* v, int st, uint32_t tries) {
    constexpr int RD = decltype(rd)::value;
    uint32_t u[6];
#pragma unroll
    for (int j = 0; j < 6; j++) u[j] = movm(v[4 * (j / 3) + j % 3]);
    const bool all3 = RD == 0 || w < 3;
    if (RD == 0) {
      const uint32_t a = L16 + R_M1 + w * 768, a2 = L8 + R_M1 + 512 + w * 768;
      st_async4(a + to1 + 3072, u, bars + to1 + B_MB + 8); st_async2(a2 + to1 + 3072, u[4], u[5], bars + to1 + B_MB + 8);
      sts128(a, u[0], u[1], u[2], u[3]); sts64(a2, u[4], u[5]);
      __syncwarp();
      if (elect_one()) mbar_arrive(bars + B_MB);
      st_async4(a + to2 + 6144, u, bars + to2 + B_MB + 16); st_async2(a2 + to2 + 6144, u[4], u[5], bars + to2 + B_MB + 16);
    } else {
      const uint32_t a = L4 + R_M2 + rank * 2304 + w * 768;
#pragma unroll
      for (int j = 0; j < 6; j++) if (j < 2 || all3) st_async1(a + to1 + j * 128, u[j], bars + to1 + B_MB + 24);
#pragma unroll
      for (int j = 0; j < 6; j++) if (j < 2 || all3) st_async1(a + to2 + j * 128, u[j], bars + to2 + B_MB + 24);
      if (SELF_STAS) {
#pragma unroll
        for (int j = 0; j < 6; j++) if (j < 2 || all3) st_async1(a + j * 128, u[j], bars + B_MB + 24);
      } else {
#pragma unroll
        for (int j = 0; j < 6; j++) if (j < 2 || all3) sts32(a + j * 128, u[j]);
        __syncwarp();
        if (elect_one()) mbar_arrive(bars + B_MB + 24);
      }
    }
  };

  auto send_vt = [&]() {
    if (elect_one()) {
      const uint32_t src = sb + R_VT + warp * 1024;
      bulk_s2s(src + to1, src, 1024, bars + to1 + B_VT);
      bulk_s2s(src + to2, src, 1024, bars + to2 + B_VT);
    }
  };
  auto store_att = [&](int sg) {
    uint32_t* op = reinterpret_cast<uint32_t*>(g_att + (size_t)((sg >> 2) * 64 + head * 2 + rank) * 16384 + (2 * w * 16 + (sg & 3) * 4) * 128) + opaque32(lane);
#pragma unroll
    for (int j = 0; j < 8; j++) op[(j & 1) * 512 + (j >> 1) * 32] = pk[j];
  };

  auto token_softmax = [&](uint32_t par) {
    const int ln = opaque32(lane), kg = w - (ln >> 3);
    const uint32_t r16 = sb + R_P + w * 768 + (ln & 7) * 16;
    const uint32_t ta = r16 + (kg >= 0 ? kg * 128 : 640);
    const int dg = (ln >> 2) - 2 * (ln & 3);
    const uint32_t keep = dg > 0 ? 0xffffffffu : dg == 0 ? 0x0000ffffu : 0u;
    mbar_wait(bars + B_TS, par);
    uint32_t x[6], y[4];
    ldsm4t(x, ta); ldsm4t(y, ta + 3072); ldsm2t(x + 4, r16 + 512 + ((ln >> 3) & 1) * 3072);
#pragma unroll
    for (int j = 0; j < 5; j++) x[j] = hadd2(x[j], j < 4 ? y[j] : x[5]);
    x[0] = (x[0] & keep) | (0xff80ff80u & ~keep);
    float sv[10];
    exp10(sv, x);
    float sum = (((sv[0] + sv[1]) + (sv[2] + sv[3])) + ((sv[4] + sv[5]) + (sv[6] + sv[7]))) + (sv[8] + sv[9]);
    sum += __shfl_xor_sync(0xffffffffu, sum, 1);
    sum += __shfl_xor_sync(0xffffffffu, sum, 2);
    const float inv = rcp(sum);
#pragma unroll
    for (int j = 0; j < 5; j++) x[j] = pack2(sv[2 * j] * inv, sv[2 * j + 1] * inv);
    stsm4(r16 + (kg & 3) * 128, x);
    sts32(sb + ln * 4 + w * 768 + R_P + 512, x[4]);
    fence_async_smem();
    bar_arrive<NB_P, 256>();
  };
  auto first_wo = [&](int s) {
    if (s == 0) {
      mbar_wait_safe(bars + B_WO, 0);
      TS(10);
      if (WG == 1 && head == 0 && rank == 0 && w == 0 && elect_one()) red_add_u32(&g_flags[FL_GO], 1);
    }
  };
  auto mem_proj = [&](uint32_t par, auto mid) {
    float c[NCH][4];
    uint32_t b[3][6];
    const uint32_t ma = L16, m8 = L8;
#pragma unroll
    for (int i = 0; i < 18; i++) {
      if (i < 16) {
        if (i % 4 == 0) mbar_wait(bars + B_MB + (i / 4) * 8, par);
        if (i < 12) { lds128(b[i % 3], ma + R_M1 + i * 768); lds64(b[i % 3] + 4, m8 + R_M1 + 512 + i * 768); }
        else { ldsm4(b[i % 3], ma + R_M2 + 4096 + (i - 12) * 768); ldsm2(b[i % 3] + 4, ma + R_M2 + 4096 + 512 + (i - 12) * 768); }
      }
      mid(i);
      if (i < 16) __syncwarp();
      if (i >= 2) {
        const int j = i - 2;
#pragma unroll
        for (int q = 0; q < 3; q++) {
          const uint32_t* f = W[3 * j + q];
          if (3 * j + q < NCH) hmma0(c[3 * j + q], f[0], f[1], f[2], f[3], b[j % 3][2 * q], b[j % 3][2 * q + 1]);
          else hmma(c[(3 * j + q) % NCH], f[0], f[1], f[2], f[3], b[j % 3][2 * q], b[j % 3][2 * q + 1]);
        }
      }
    }
#pragma unroll
    for (int j = 0; j < 4; j++) acc[16 + j] = NCH == 3 ? (c[0][j] + c[1][j]) + c[2][j] : (c[0][j] + c[1][j]) + (c[2][j] + c[NCH - 1][j]);
  };

  if (WG == 0) bar_arrive<NB_G, 256>();
#pragma unroll 1
  for (int s = 0; s < NSEG - 1; s++) {
    const uint32_t par = s & 1;
    TRACE(0);
    {
      float c[NCH][4];
      uint32_t b[3][6];
      const uint32_t ma = L16, m8 = L8;
#pragma unroll
      for (int i = 0; i < 18; i++) {
        if (i < 16) {
          if (i % 4 == 0 && !(i == 4 && TOP2)) mbar_wait(bars + B_MB + (i / 4) * 8, par);
          if (i == 0 && TOP2) mbar_wait(bars + B_MB + 8, par);
          if (i % 4 == 0) TRACE(1 + i / 4);
          if (i < 12) { lds128(b[i % 3], ma + R_M1 + i * 768); lds64(b[i % 3] + 4, m8 + R_M1 + 512 + i * 768); }
          else { ldsm4(b[i % 3], ma + R_M2 + 4096 + (i - 12) * 768); ldsm2(b[i % 3] + 4, ma + R_M2 + 4096 + 512 + (i - 12) * 768); }
          if (WG == 1 && i == BX_I) {
            bar_sync<NB_G, 256>();
            if (elect_one()) load_chunk(sb + R_GB + w * 4096, s + 1, g0, bars + B_FB);
          }
          if (i == CX_I) {
            if (isC) send_vt();
            if (WG == 1 && ATT_LATE && !isC && s > 0) store_att(s - 1);
          }
          __syncwarp();
        }
        if (i >= 2) {
          const int j = i - 2;
#pragma unroll
          for (int q = 0; q < 3; q++) {
            const uint32_t* f = W[3 * j + q];
            if (3 * j + q < NCH) hmma0(c[3 * j + q], f[0], f[1], f[2], f[3], b[j % 3][2 * q], b[j % 3][2 * q + 1]);
            else hmma(c[(3 * j + q) % NCH], f[0], f[1], f[2], f[3], b[j % 3][2 * q], b[j % 3][2 * q + 1]);
          }
        }
        if (i == 14) zero_regs<16>(acc);
        if (i == 16) mbar_wait(bars + B_FA, 0);
      }
#pragma unroll
      for (int j = 0; j < 4; j++) acc[16 + j] = NCH == 3 ? (c[0][j] + c[1][j]) + c[2][j] : (c[0][j] + c[1][j]) + (c[2][j] + c[NCH - 1][j]);
    }
    TRACE(5);
    bar_sync<NB_H, 256>();
    WG_FENCE();
#pragma unroll
    for (int k = 0; k < 16; k++) wg_ss40<0>(acc, dsc.tail_a[WG * 16 + k], dsc.tail_b[k]);
    WG_COMMIT();
    uint32_t vt[4][4];
    {
      const uint32_t a = opaque32(L4 + w * 256 + (isC ? WG * 1024 + R_VM : R_QK + 4096 + WG * 5120));
      const uint32_t qa = L16 + R_QK, xa = opaque32(LV + w * 2048 + (WG == 0 ? 0 : (opaque32(lane) & 8) * 64 + R_QK + 5120 - R_VT));
      const uint32_t d = opaque32(L4 + R_XS + rank * 640 + w * 256);
      if (!WO_LATE) first_wo(s);
      mbar_wait(bars + B_FB, 0);
      if (WG == 0) mbar_wait(bars + B_VT, par);
      WG_WAIT(0);
      reg_fence<20>(acc);
      TRACE(6);
      const uint32_t p0 = pack2(acc[16], acc[17]), p1 = pack2(acc[18], acc[19]);
      sts32(a, p0); sts32(a + 128, p1);
      if (isC) {
        st_async1(a + to1, p0, bars + B_VM + to1); st_async1(a + to1 + 128, p1, bars + B_VM + to1);
        st_async1(a + to2, p0, bars + B_VM + to2); st_async1(a + to2 + 128, p1, bars + B_VM + to2);
      }
      if (WG == 0) {
        bar_arrive<NB_A, 256>();
        if (Q_FENCE && !isC) fence_async_smem();
#pragma unroll
        for (int i = 0; i < 4; i++) ldsm4(vt[i], xa + (i >> 1) * 1024 + (i & 1) * 256);
        bar_sync<NB_S, 256>();
      } else {
        bar_sync<NB_A, 256>();
        if (!isC) {
          if (w < 3) {
            uint32_t q[8], k[4][4];
            ldsm4t(q, qa + 4096); ldsm4t(k[0], xa); ldsm4t(k[1], xa + 256);
            ldsm4t(q + 4, qa + 4096 + 512); ldsm4t(k[2], xa + 512); ldsm4t(k[3], xa + 768);
            float x[4], y[4];
            hmma0(x, k[0][0], k[0][1], k[0][2], k[0][3], q[0], q[1]); hmma0(y, k[1][0], k[1][1], k[1][2], k[1][3], q[2], q[3]);
            hmma(x, k[2][0], k[2][1], k[2][2], k[2][3], q[4], q[5]); hmma(y, k[3][0], k[3][1], k[3][2], k[3][3], q[6], q[7]);
            const uint32_t s0 = pack2(x[0] + y[0], x[1] + y[1]), s1 = pack2(x[2] + y[2], x[3] + y[3]);
            st_async1(d + to1, s0, bars + B_XS + to1);
            st_async1(d + to2, s0, bars + B_XS + to2);
            if (w < 2) { st_async1(d + to1 + 128, s1, bars + B_XS + to1); st_async1(d + to2 + 128, s1, bars + B_XS + to2); sts32(d + 128, s1); }
            sts32(d, s0);
          }
        }
        bar_arrive<NB_S, 256>();
      }
    }
    if (WG == 1) {
      if (elect_one()) load_chunk(sb + R_GA + w * 4096, s + 1, g1, bars + B_FA);
      {
        if (w > 0 && elect_one()) mbar_expect(bars + B_MB + 8 * w, w < 3 ? 3072 : SELF_STAS ? 28 * 256 : isC ? 18 * 256 : 19 * 256);
      }
      fence_async_smem();
      bar_sync<NB_B, 256>();
    }
    TRACE(7);
    WG_FENCE();
#pragma unroll
    for (int k = 0; k < 16; k++) wg_rs32<1>(acc, W[k][0], W[k][1], W[k][2], W[k][3], dsc.tok[16 + k]);
    WG_COMMIT();
    uint32_t wa[3][4];
    const uint32_t oxa = L16 + R_OX;
    if (WG == 0) {
      const uint32_t vma = oxa - (R_OX - R_VM) + w * 512, oa = opaque32(L4 + w * 512 + R_OX);
      TRACE(8);
      mbar_wait(bars + B_XS, par);
      TRACE(9);
      float sv[10];
      {
        uint32_t x[10];
        ldsm4t(x, oxa - (R_OX - R_XS)); ldsm4t(x + 4, oxa - (R_OX - R_XS) + 512); ldsm2t(x + 8, oxa - (R_OX - R_XS) + 1024);
        bar_arrive<NB_B, 256>();
#pragma unroll
        for (int j = 0; j < 5; j++) x[j] = hadd2(x[j], x[j + 5]);
        exp10(sv, x);
      }
      WG_WAIT(0);
      bar_arrive<NB_X, 256>();
      mbar_wait(bars + B_VM, par);
      uint32_t vm[4];
      ldsm4(vm, vma);
      uint32_t pb[5];
#pragma unroll
      for (int j = 0; j < 5; j++) pb[j] = pack2(sv[2 * j], sv[2 * j + 1]);
      TRACE(10);
      float o0[4], o1[4], sm[4];
      const uint32_t ONE = 0x3f803f80u;
      hmma0(o0, vt[0][0], vt[0][1], vt[0][2], vt[0][3], pb[0], pb[1]);
      hmma0(o1, vt[2][0], vt[2][1], vt[2][2], vt[2][3], pb[0], pb[1]);
      hmma0(sm, ONE, ONE, ONE, ONE, pb[0], pb[1]);
      hmma(sm, ONE, ONE, ONE, ONE, pb[2], pb[3]);
      hmma(o0, vt[1][0], vt[1][1], vt[1][2], vt[1][3], pb[2], pb[3]);
      hmma(o1, vt[3][0], vt[3][1], vt[3][2], vt[3][3], pb[2], pb[3]);
      hmma_k8(sm, ONE, ONE, pb[4]);
      hmma_k8(o0, vm[0], vm[1], pb[4]);
      hmma_k8(o1, vm[2], vm[3], pb[4]);
      if (WO_LATE) first_wo(s);
#pragma unroll
      for (int i = 0; i < 3; i++) ldsm4t(wa[i], woa + i * 4096);
      __syncwarp();
      const float i0 = rcp(sm[0]), i1 = rcp(sm[1]);
      sts32(oa, pack2(o0[0] * i0, o0[1] * i1)); sts32(oa + 128, pack2(o0[2] * i0, o0[3] * i1));
      sts32(oa + 256, pack2(o1[0] * i0, o1[1] * i1)); sts32(oa + 384, pack2(o1[2] * i0, o1[3] * i1));
      TRACE(11);
      bar_sync<NB_C, 128>();
    } else {
      if (!isC) {
        constexpr uint64_t dQ = mkdesc(0x400 + R_QK, 128, 1024, 0), dK = mkdesc(0x400 + R_QK + 5120, 128, 1024, 0);
        float sc[16];
        zero_regs<16>(sc);
        WG_FENCE();
#pragma unroll
        for (int k = 0; k < 4; k++) wg_ss32<1>(sc, dK + k * 16, dQ + k * 16);
        WG_COMMIT();
        const uint32_t top = rank == 0 ? to2 : to1, e = L4 + R_P + w * 256;
        WG_WAIT(0);
        bar_sync<NB_X, 256>();
        if (elect_one()) load_chunk(sb + R_GB + w * 4096, s + 1, g2, bars + B_FB);
        reg_fence<16>(sc);
        if (w < 3) {
#pragma unroll
          for (int j = 0; j < 8; j++) {
            if ((j & 1) ? (j > 1 && (w == 0 || (w == 1 && j == 7))) : (j >= 4 || w != 1)) {
              const uint32_t t = pack2(sc[2 * j], sc[2 * j + 1]), o = (j >> 1) * 768 + (j & 1) * 128;
              st_async1(e + top + 3072 + o, t, bars + top + B_TS);
              sts32(e + o, t);
            }
          }
          __syncwarp();
          if (elect_one()) mbar_arrive(bars + B_TS);
        }
      } else {
        WG_WAIT(0);
        bar_sync<NB_X, 256>();
        if (elect_one()) load_chunk(sb + R_GB + w * 4096, s + 1, g2, bars + B_FB);
      }
      TRACE(8);
      mbar_wait(bars + B_FA, 1);
      TRACE(11);
    }
    if (has_wo) {
      float* rslot = SLOT(s);
      uint32_t ob[4][4];
      float c[3][4];
      if (WG == 1) {
        if (WO_LATE) first_wo(s);
#pragma unroll
        for (int i = 0; i < 3; i++) ldsm4t(wa[i], woa + i * 4096);
        bar_sync<NB_D, 256>();
      }
      ldsm4t(ob[0], oxa);
      __syncwarp();
#pragma unroll
      for (int k = 0; k < 8; k++) {
        uint32_t nx[3][4];
        if ((k & 1) == 0 && k < 6) { ldsm4t(ob[(k >> 1) + 1], oxa + ((k >> 1) + 1) * 512); __syncwarp(); }
#pragma unroll
        for (int i = 0; i < 3; i++) {
          const uint32_t* o = ob[k >> 1] + (k & 1) * 2;
          if (k < 7) { ldsm4t(nx[i], woa + i * 4096 + (k + 1) * 512); if (i == 2) __syncwarp(); }
          if (k == 0) hmma0(c[i], wa[i][0], wa[i][1], wa[i][2], wa[i][3], o[0], o[1]);
          else hmma(c[i], wa[i][0], wa[i][1], wa[i][2], wa[i][3], o[0], o[1]);
#pragma unroll
          for (int q = 0; q < 4; q++) if (k < 7) wa[i][q] = nx[i][q];
        }
        if (k == ND_K && WG == 0) bar_arrive<NB_D, 256>();
      }
      const float* cv = &c[0][0];
      uint32_t r[6];
#pragma unroll
      for (int j = 0; j < 6; j++) r[j] = pack2(cv[2 * j], cv[2 * j + 1]);
      asm volatile("red.relaxed.gpu.global.add.noftz.v4.bf16x2 [%0], {%1, %2, %3, %7};\n"
                   "red.relaxed.gpu.global.add.noftz.v4.bf16x2 [%0+1024], {%4, %5, %6, %7};"
                   :: "l"(rslot), "r"(r[0]), "r"(r[1]), "r"(r[2]), "r"(r[3]), "r"(r[4]), "r"(r[5]), "r"(0x3f800000) : "memory");
    } else {
      bar_arrive<NB_D, 256>();
      if ((s & 3) == 0) {
        fence_gpu();
        if (s > 0 && elect_one()) red_add_u32(&g_flags[FL_ATT + 2 * (s - 4)], 1);
      }
      if (rank == 0 || head < 16)
        reinterpret_cast<uint4*>(g_slot)[((s + ZS) & 3) * 3072 + ((s + ZS) & 4) * 8 + rank * 2048 + head * 64 + opaque32(lane)] = make_uint4(0, 0, 0, 0);
      if (HPF && head < 16 && rank == 0 && s + HPF < NSEG && elect_one())
        asm volatile("cp.async.bulk.prefetch.L2.global [%0], 4096;" :: "l"(g_h + (size_t)((s + HPF) * 16 + head) * 4096) : "memory");
    }
    const uint32_t t_red = clk32();
    uint32_t v[8];
    const float* slot = SLOT(s);
    TRACE(13);
    if (WG == 0) {
      if (!isC) {
        token_softmax(par);
      }
      if (P1K < 0) { while (clk32() - t_red < POLL_DELAY) {} load_red(v, slot); }
      bar_sync<NB_E, 256>();
    } else {
      mbar_wait(bars + B_FB, 1);
    }
    TRACE(14);
    float ao[16];
    uint32_t v2[8];
    if (WG == 1) zero_regs<16>(ao);
    WG_FENCE();
#pragma unroll
    for (int k = 0; k < 32; k++) {
      if (WG == 0 && k == P1K) { sched_fence(head, 101); load_red(v, slot); }
      if (WG == 0 && k == P2K) { sched_fence(head, 102); load_red(v2, slot); }
      if (WG == 0 && k == 16) WG_COMMIT();
      wg_rs32<1>(acc, W[16 + k][0], W[16 + k][1], W[16 + k][2], W[16 + k][3], dsc.tok[k]);
    }
    WG_COMMIT();
    TRACE(12);
    if (WG == 1) {
      if (!isC) {
        constexpr uint64_t dP = mkdesc(0x400 + R_P, 128, 768, 0);
        const uint64_t dV = mkdesc(0x400 + R_VT, 128, 512, 0) + rank * 256, dM = mkdesc(0x400 + R_VM, 0, 128, 0) + rank * 64;
        bar_sync<NB_P, 256>();
        WG_FENCE();
        wg_ss32<0>(ao, dV, dP); wg_ss32<0>(ao, dV + 16, dP + 16); wg_ss32<0>(ao, dM, dP + 32);
        WG_COMMIT();
      }
      bar_arrive<NB_E, 256>();
      if (elect_one()) mbar_expect(bars + B_XS + 8 * w, arm_bytes);
      while (clk32() - t_red < POLL_DELAY1) {}
      load_red(v, slot);
      bar_arrive<NB_W0, 128>();
    } else {
      WG_WAIT(1);
      bar_arrive<NB_F, 256>();
      sched_fence(head, 100);
      v[3] = opaque32(v[3]);
      uint32_t tries = 0;
      if (P2K < 0) tries = finish_red(v, slot);
      else if (__builtin_expect(!red_done(v), 0)) {
#pragma unroll
        for (int j = 0; j < 8; j++) v[j] = v2[j];
        tries = 1;
        while (!red_done(v)) { if (++tries > 20000000u) __trap(); load_red(v, slot); }
      }
      forward(std::integral_constant<int, 0>(), v, s, tries);
      if (P2K >= 0) asm volatile("" :: "r"(v2[0]), "r"(v2[1]), "r"(v2[2]), "r"(v2[3]), "r"(v2[4]), "r"(v2[5]), "r"(v2[6]), "r"(v2[7]));
      TRACE(16);
    }
    WG_WAIT(0);
    reg_fence<16>(acc);
    if (WG == 0) bar_arrive<NB_G, 256>();
    TRACE(15);
    {
      uint32_t pq[8];
#pragma unroll
      for (int j = 0; j < 8; j++) pq[j] = pack2(acc[2 * j], acc[2 * j + 1]);
      if (WG == 1) {
        reg_fence<16>(ao);
#pragma unroll
        for (int j = 0; j < 8; j++) pk[j] = pack2(ao[2 * j], ao[2 * j + 1]);
      }
      if (!isC) {
        const uint32_t q = L4 + w * 256 + R_QK + WG * 5120;
#pragma unroll
        for (int j = 0; j < 8; j++) sts32(q + (j >> 1) * 1024 + (j & 1) * 128, pq[j]);
        if (WG == 1 && !ATT_LATE) store_att(s);
      } else {
        const uint32_t a = LV + warp * 1024;
        stsm4(a, pq); stsm4(a + 256, pq + 4);
      }
    }
    TRACE(17);
    if (WG == 1) {
      auto refill = [&]() {
        bar_sync<NB_F, 256>();
        if (s < NSEG - 2 && elect_one()) load_chunk(sb + R_GA + w * 4096, s + 2, 12 + w, bars + B_FA);
      };
      if (RF_FIRST) refill();
      if (has_wo) { v[3] = opaque32(v[3]); const uint32_t tries = finish_red(v, slot); forward(std::integral_constant<int, 1>(), v, s, tries); }
      if (!RF_FIRST) refill();
      TRACE(16);
    }
    if (isC && V_FENCE) { fence_async_smem(); __syncwarp(); }
    TRACE(18);
  }
  {
    constexpr uint32_t par = (NSEG - 1) & 1;
    if (WG == 1) {
      bar_sync<NB_G, 256>();
      if (ATT_LATE && !isC) store_att(NSEG - 2);
    }
    const bool proj = WG == 1 || isC;
    if (proj) mem_proj(par, [&](int i) { if (i == CX_I && isC) send_vt(); if (i == 15) zero_regs<16>(acc); });
    else fence_async_smem();
    bar_sync<NB_H, 256>();
    if (proj) {
      WG_FENCE();
#pragma unroll
      for (int k = 0; k < 16; k++) wg_ss40<0>(acc, dsc.tail_a[WG * 16 + k], dsc.tail_b[k]);
      WG_COMMIT();
      const uint32_t a = opaque32(L4 + w * 256 + (isC ? WG * 1024 + R_VM : R_QK + 4096 + WG * 5120));
      WG_WAIT(0);
      reg_fence<20>(acc);
      const uint32_t p0 = pack2(acc[16], acc[17]), p1 = pack2(acc[18], acc[19]);
      if (isC) {
        st_async1(a + to1, p0, bars + B_VM + to1); st_async1(a + to1 + 128, p1, bars + B_VM + to1);
        st_async1(a + to2, p0, bars + B_VM + to2); st_async1(a + to2 + 128, p1, bars + B_VM + to2);
      } else { sts32(a, p0); sts32(a + 128, p1); }
    }
    if (!isC) {
      if (WG == 1) {
        fence_async_smem();
        bar_sync<NB_C, 128>();
        constexpr uint64_t dQ = mkdesc(0x400 + R_QK, 128, 1024, 0), dK = mkdesc(0x400 + R_QK + 5120, 128, 1024, 0);
        float sc[16];
        zero_regs<16>(sc);
        WG_FENCE();
#pragma unroll
        for (int k = 0; k < 4; k++) wg_ss32<1>(sc, dK + k * 16, dQ + k * 16);
        WG_COMMIT();
        const uint32_t top = rank == 0 ? to2 : to1, e = L4 + R_P + w * 256;
        WG_WAIT(0);
        reg_fence<16>(sc);
        if (w < 3) {
#pragma unroll
          for (int j = 0; j < 8; j++) {
            if ((j & 1) ? (j > 1 && (w == 0 || (w == 1 && j == 7))) : (j >= 4 || w != 1)) {
              const uint32_t t = pack2(sc[2 * j], sc[2 * j + 1]), o = (j >> 1) * 768 + (j & 1) * 128;
              st_async1(e + top + 3072 + o, t, bars + top + B_TS);
              sts32(e + o, t);
            }
          }
          __syncwarp();
          if (elect_one()) mbar_arrive(bars + B_TS);
        }
        constexpr uint64_t dP = mkdesc(0x400 + R_P, 128, 768, 0);
        const uint64_t dV = mkdesc(0x400 + R_VT, 128, 512, 0) + rank * 256, dM = mkdesc(0x400 + R_VM, 0, 128, 0) + rank * 64;
        float ao[16];
        zero_regs<16>(ao);
        mbar_wait(bars + B_VT, par);
        mbar_wait(bars + B_VM, par);
        bar_sync<NB_P, 256>();
        WG_FENCE();
        wg_ss32<0>(ao, dV, dP); wg_ss32<0>(ao, dV + 16, dP + 16); wg_ss32<0>(ao, dM, dP + 32);
        WG_COMMIT();
        WG_WAIT(0);
        reg_fence<16>(ao);
#pragma unroll
        for (int j = 0; j < 8; j++) pk[j] = pack2(ao[2 * j], ao[2 * j + 1]);
        store_att(NSEG - 1);
      } else {
        token_softmax(par);
      }
    }
  }
#undef L16
#undef L8
#undef L4
#undef SLOT
#undef LV
}

__global__ void __cluster_dims__(3, 1, 1) __launch_bounds__(256, 1)
kernel_R(const __grid_constant__ CUtensorMap tmq, const __grid_constant__ CUtensorMap tmk, const __grid_constant__ CUtensorMap tmv,
         const __grid_constant__ CUtensorMap tmo, const __grid_constant__ CUtensorMap tmm, const __nv_bfloat16* __restrict__ x,
         const __nv_bfloat16* __restrict__ mem0, const __nv_bfloat16* __restrict__ cvec, const __grid_constant__ RDesc dsc) {
  extern __shared__ __align__(1024) uint8_t smem[];
  const uint32_t sb = smem_u32(smem);
  uint32_t rank; asm("mov.u32 %0, %%cluster_ctarank;" : "=r"(rank));
  rank = __shfl_sync(0xffffffffu, rank, 0);
  const int cta = blockIdx.x, head = __shfl_sync(0xffffffffu, cta / 3, 0);
  const int tid = threadIdx.x, lane = tid & 31;
  const int warp = __shfl_sync(0xffffffffu, tid >> 5, 0);
  const int wg = warp >> 2, w = warp & 3;
  const uint32_t bars = sb + R_BAR;
  const CUtensorMap* tmw = rank == 2 ? &tmv : (wg == 0 ? &tmq : &tmk);
  const int fcol = head * 128 + (rank == 2 ? wg * 64 : (int)rank * 64);

  asm volatile("griddepcontrol.launch_dependents;");
  uint32_t W[48][4];
  {
    if (sb != (rank << 24) + 0x400) __trap();
    if (tid == 0) {
      sts64(bars + 248, rank, head);
      mbar_init(bars + B_MB, 4); mbar_init(bars + B_MB + 8, 1); mbar_init(bars + B_MB + 16, 1); mbar_init(bars + B_MB + 24, SELF_STAS ? 1 : rank == 2 ? 5 : 4);
      for (int i = B_XS; i <= B_X; i += 8) mbar_init(bars + i, i == B_FA || i == B_FB || (i == B_TS && rank < 2) ? 4 : 1);
      asm volatile("fence.mbarrier_init.release.cluster;" ::: "memory");
      fence_async_smem();
    }
    __syncthreads();
    asm volatile("barrier.cluster.arrive.relaxed.aligned;" ::: "memory");
    TS(0);
    const int nwm = rank == 0 ? 6 : 5, wm0 = rank == 0 ? 0 : 5 * rank + 1, nrg = cta < 64 ? 3 : 2;
    if (elect_one()) {
      if (warp == 0) { mbar_expect(bars + B_WM, nwm * 8192); mbar_expect(bars + B_X, nrg * 16384); }
      if (warp < nwm) tma2d_p(sb + R_GA + warp * 8192, &tmm, head * 64, (wm0 + warp) * 64, bars + B_WM, POL_RW);
#pragma unroll 1
      for (int r = 0; r < nrg; r++) bulk_g2s(sb + R_TAIL + (r * 8 + warp) * 2064, x + (size_t)((cta + 96 * r) * 8 + warp) * D_, 2048, bars + B_X);
      if (w == 0) mbar_expect(bars + B_STG + wg * 16, 49152);
      if (w < 2) tma2d_p(sb + R_WO + wg * 49152 + w * 8192, tmw, fcol, rot_chunk(w, rank) * 64, bars + B_STG + wg * 16, POL_RW);
    }
    float* scr = reinterpret_cast<float*>(smem + R_VT);
#pragma unroll 1
    for (int i = tid; i < nwm * 64; i += 256) {
      const float c = __bfloat162float(cvec[wm0 * 64 + i]);
      scr[i] = __bfloat162float(__float2bfloat16(c / (1.f + __expf(-c))));
    }
    if (tid < 128) {
      uint32_t e[4] = {0u, 0u, 0u, 0u};
      if (cta >= 72 && (tid & 32)) {
        const uint16_t* mp = reinterpret_cast<const uint16_t*>(mem0) + 2 * (lane & 3) * D_ + (lane >> 2);
#pragma unroll
        for (int q = 0; q < 3; q++) {
          const int n = 3 * (tid >> 6) + q, col = wo_tile(3 * (cta & 7) + (n >> 1), (cta - 72) >> 3) * 16 + 8 * (n & 1);
          e[q] = mp[col] | (uint32_t)mp[col + D_] << 16;
        }
        e[3] = 0x42000000u;
      }
      reinterpret_cast<uint4*>(g_slot)[cta * 128 + tid] = make_uint4(e[0], e[1], e[2], e[3]);
    }
    __syncthreads();
    TS(1);
    mbar_wait_safe(bars + B_WM, 0);
    if (elect_one()) tma2d_p(sb + R_WO + wg * 49152 + (2 + w) * 8192, tmw, fcol, rot_chunk(2 + w, rank) * 64, bars + B_STG + wg * 16, POL_RW);
    {
      float a[8];
#pragma unroll
      for (int j = 0; j < 8; j++) a[j] = 0.f;
#pragma unroll 2
      for (int i = 0; i < 2 * nwm; i++) {
        uint32_t u[4];
        lds128(u, sb + R_GA + i * 4096 + tid * 16);
        const float sc = scr[i * 32 + (tid >> 3)];
#pragma unroll
        for (int j = 0; j < 4; j++) { a[2 * j] += sc * bf_lo(u[j]); a[2 * j + 1] += sc * bf_hi(u[j]); }
      }
#pragma unroll
      for (int j = 0; j < 8; j++) { a[j] += __shfl_xor_sync(0xffffffffu, a[j], 8); a[j] += __shfl_xor_sync(0xffffffffu, a[j], 16); }
      if (lane < 8) {
        sts128(sb + R_VT + 1536 + warp * 256 + lane * 32, __float_as_uint(a[0]), __float_as_uint(a[1]), __float_as_uint(a[2]), __float_as_uint(a[3]));
        sts128(sb + R_VT + 1552 + warp * 256 + lane * 32, __float_as_uint(a[4]), __float_as_uint(a[5]), __float_as_uint(a[6]), __float_as_uint(a[7]));
      }
    }
    __syncthreads();
    TS(2);
    asm volatile("barrier.cluster.wait.aligned;\nbarrier.cluster.arrive.relaxed.aligned;" ::: "memory");
    if (warp == 7) {
      float t0 = 0.f, t1 = 0.f;
#pragma unroll
      for (int i = 0; i < 8; i++) { float t[2]; lds64f(t, sb + R_VT + 1536 + i * 256 + lane * 8); t0 += t[0]; t1 += t[1]; }
      reinterpret_cast<float2*>(g_modp + rank * 2048 + head * 64)[lane] = make_float2(t0, t1);
      fence_gpu();
      __syncwarp();
      if (lane == 0) red_add_u32(&g_flags[FL_S1], 1);
      __syncwarp();
    }
    mbar_wait_safe(bars + B_X, 0);
#pragma unroll 1
    for (int r = 0; r < nrg; r++) {
      float f[32];
#pragma unroll
      for (int i = 0; i < 4; i++) {
        uint32_t u[4];
        lds128(u, sb + R_TAIL + (r * 8 + warp) * 2064 + i * 512 + lane * 16);
#pragma unroll
        for (int j = 0; j < 4; j++) { f[8 * i + 2 * j] = bf_lo(u[j]); f[8 * i + 2 * j + 1] = bf_hi(u[j]); }
      }
      float t = 0.f;
#pragma unroll
      for (int i = 0; i < 32; i++) t += f[i];
#pragma unroll
      for (int o = 1; o < 32; o <<= 1) t += __shfl_xor_sync(0xffffffffu, t, o);
      const float mean = t * (1.f / D_);
      t = 0.f;
#pragma unroll
      for (int i = 0; i < 32; i++) t = fmaf(f[i] - mean, f[i] - mean, t);
#pragma unroll
      for (int o = 1; o < 32; o <<= 1) t += __shfl_xor_sync(0xffffffffu, t, o);
      const float rstd = rsqrtf(t * (1.f / D_) + 1e-5f);
      if (lane == 0) sts64(sb + R_VT + 3584 + (r * 8 + warp) * 8, __float_as_uint(rstd), __float_as_uint(-mean * rstd));
    }
    TS(3);
    if (w < PF1 && elect_one()) tma2d_prefetch_p(tmw, fcol, rot_chunk(6 + w, rank) * 64, POL_RW);
    if (tid == 0) wait_flag(&g_flags[FL_S1], 96);
    __syncthreads();
    TS(4);
    {
      float4 p[6];
#pragma unroll
      for (int i = 0; i < 6; i++) p[i] = __ldcg(reinterpret_cast<const float4*>(g_modp + (i >> 1) * 2048) + 2 * tid + (i & 1));
      if (w < PF2 && elect_one()) tma2d_prefetch_p(tmw, fcol, (9 + w) * 64, POL_RW);
      sts128(sb + R_VT + 5120 + tid * 16, pack2(p[0].x + p[2].x + p[4].x, p[0].y + p[2].y + p[4].y), pack2(p[0].z + p[2].z + p[4].z, p[0].w + p[2].w + p[4].w),
             pack2(p[1].x + p[3].x + p[5].x, p[1].y + p[3].y + p[5].y), pack2(p[1].z + p[3].z + p[5].z, p[1].w + p[3].w + p[5].w));
    }
    __syncthreads();
#pragma unroll 2
    for (int it = 0; it < 4 * nrg; it++) {
      const int r = it >> 2, rg = cta + 96 * r, c = 16 * warp + (lane >> 3) + 4 * (it & 3);
      uint32_t a[4], b[4], u[4], o[4];
      float t[2];
      lds128(u, sb + R_TAIL + (r * 8 + (lane & 7)) * 2064 + c * 16);
      lds128(a, sb + R_VT + 5120 + c * 16); lds128(b, sb + R_VT + 7168 + c * 16);
      lds64f(t, sb + R_VT + 3584 + (r * 8 + (lane & 7)) * 8);
#pragma unroll
      for (int j = 0; j < 4; j++)
        o[j] = pack2(fmaf(fmaf(bf_lo(u[j]), t[0], t[1]), 1.f + bf_lo(b[j]), bf_lo(a[j])), fmaf(fmaf(bf_hi(u[j]), t[0], t[1]), 1.f + bf_hi(b[j]), bf_hi(a[j])));
      *reinterpret_cast<uint4*>(g_h + (size_t)(rg >> 2) * 65536 + (lane & 7) * 16 + (c & 7) * 128 +
                                (c < 96 ? (c >> 3) * 4096 + (rg & 3) * 1024 : 49152 + (rg & 3) * 4096 + ((c >> 3) - 12) * 1024)) =
          make_uint4(o[0], o[1], o[2], o[3]);
    }
    TS(5);
    __syncthreads();
    TS(6);
    if (w < PF3 && elect_one()) tma2d_p(sb + R_TAIL + warp * 8192, tmw, fcol, 768 + w * 64, bars + B_TAIL, POL_RW);
    if (warp == 3 && lane == 0) { fence_gpu(); red_add_u32(&g_flags[FL_S2], 1); }
    __syncwarp();
    asm volatile("barrier.cluster.wait.aligned;" ::: "memory");
    forward_initial(sb, rank, wg, w, lane);

    const uint32_t a0 = opaque32(sb + R_WO + wg * 49152 + ((lane >> 4) * 8 + (lane & 7)) * 128 + (((2 * w + ((lane >> 3) & 1)) ^ (lane & 7)) << 4));
    mbar_wait_safe(bars + B_STG + wg * 16, 0);
    TS(7);
#pragma unroll
    for (int i = 0; i < 24; i++) ldsm4t(W[i], a0 + i * 2048);
    auto second_wave = [&]() {
      if (w == 0) mbar_expect(bars + B_STG + wg * 16 + 8, 49152);
#pragma unroll 1
      for (int c = w; c < 6; c += 4) tma2d_p(sb + R_WO + wg * 49152 + c * 8192, tmw, fcol, rot_chunk(6 + c, rank) * 64, bars + B_STG + wg * 16 + 8, POL_RW);
      if (warp == 0) mbar_expect(bars + B_TAIL, 65536);
      if (w >= PF3) tma2d_p(sb + R_TAIL + warp * 8192, tmw, fcol, 768 + w * 64, bars + B_TAIL, POL_RW);
#pragma unroll 1
      for (int i = warp; i < PF4; i += 8) tma2d_prefetch(&tmo, 16 * wo_tile(i, rank), head * 128);
    };
    if (S2E) { __syncthreads(); if (elect_one()) second_wave(); }
    if (tid == 0) wait_flag(&g_flags[FL_S2], 96);
    __syncthreads();
    asm volatile("fence.proxy.async.global;" ::: "memory");
    if (elect_one()) {
      if (warp == 0) mbar_expect(bars + B_X, 8 * 4096);
      bulk_g2s(sb + (wg == 0 ? R_GB : R_GA) + w * 4096, g_h + (size_t)rot_chunk(warp, rank) * 4096, 4096, bars + B_X);
      if (!S2E) second_wave();
    }
    TS(8);
    float acc[20];
    mbar_wait_safe(bars + B_X, 1);
    WG_FENCE();
    wg_rs40<0>(acc, W[0], dsc.tok[16]);
#pragma unroll
    for (int k = 1; k < 24; k++) wg_rs40<1>(acc, W[k], dsc.tok[k < 16 ? 16 + k : k - 16]);
    WG_COMMIT();
    WG_WAIT(0);
    reg_fence<20>(acc);
    __syncthreads();
    if (elect_one()) {
      if (warp == 0) mbar_expect(bars + B_X, 4 * 4096);
      if (wg == 0) bulk_g2s(sb + R_GB + w * 4096, g_h + (size_t)rot_chunk(8 + w, rank) * 4096, 4096, bars + B_X);
    }
    mbar_wait_safe(bars + B_STG + wg * 16 + 8, 0);
    TS(9);
#pragma unroll
    for (int i = 0; i < 24; i++) ldsm4t(W[24 + i], a0 + i * 2048);
    __syncthreads();
    asm volatile("barrier.cluster.arrive.relaxed.aligned;" ::: "memory");
    auto load_wo = [&]() {
      const int n = rank == 2 ? 22 : 21;
      if (warp == 0) mbar_expect(bars + B_WO, n * 4096);
#pragma unroll 1
      for (int i = warp; i < n; i += 8) tma2d(sb + R_WO + i * 4096, &tmo, 16 * wo_tile(i, rank), head * 128, bars + B_WO);
    };
    if (WO_POS == 0 && elect_one()) load_wo();
    sts32(sb + R_P + warp * 768 + 640 + lane * 4, wg == 0 ? 0u : 0xff80ff80u);
    WG_FENCE();
#pragma unroll
    for (int k = 24; k < 32; k++) wg_rs40<1>(acc, W[k], dsc.tok[k - 16]);
    WG_COMMIT();
    mbar_wait_safe(bars + B_X, 0);
    WG_FENCE();
#pragma unroll
    for (int k = 32; k < 48; k++) wg_rs40<1>(acc, W[k], dsc.tok[k - 16]);
    WG_COMMIT();
    WG_WAIT(1);
    __syncthreads();
    if (elect_one()) {
      if (warp == 0) mbar_expect(bars + B_X, 4 * 4096);
      if (wg == 0) bulk_g2s(sb + R_GA + w * 4096, g_h + (size_t)(12 + w) * 4096, 4096, bars + B_X);
    }
    if (WO_POS == 1) { __syncthreads(); if (elect_one()) load_wo(); }
    mbar_wait_safe(bars + B_TAIL, 0);
    mbar_wait_safe(bars + B_X, 1);
    WG_FENCE();
#pragma unroll
    for (int k = 0; k < 16; k++) wg_ss40<0>(acc, dsc.tail_a[wg * 16 + k], dsc.tail_b[k]);
    WG_COMMIT();
    WG_WAIT(0);
    reg_fence<20>(acc);
    {
      uint32_t pq[8];
#pragma unroll
      for (int j = 0; j < 8; j++) pq[j] = pack2(acc[2 * j], acc[2 * j + 1]);
      if (rank != 2) {
        const uint32_t q = sb + lane * 4 + w * 256 + R_QK + wg * 5120;
#pragma unroll
        for (int j = 0; j < 8; j++) sts32(q + (j >> 1) * 1024 + (j & 1) * 128, pq[j]);
      } else {
        const uint32_t a = sb + R_VT + ((lane >> 3) & 1) * 512 + (lane >> 4) * 128 + (lane & 7) * 16 + warp * 1024;
        stsm4(a, pq); stsm4(a + 256, pq + 4);
        fence_async_smem();
      }
    }
    __syncthreads();
    if (wg == 1 && elect_one()) {
      load_chunk(sb + R_GA + w * 4096, 1, 12 + w, bars + B_FA);
      mbar_expect(bars + B_XS + 8 * w, arm_size(w, rank == 2));
    }
    asm volatile("barrier.cluster.wait.aligned;" ::: "memory");
  }
  uint32_t rh[2];
  lds64(rh, bars + 248);
  rh[0] = __shfl_sync(0xffffffffu, rh[0], 0); rh[1] = __shfl_sync(0xffffffffu, rh[1], 0);
    if (wg == 0) r_main<0>(W, dsc, rh[1], rh[0], lane, w);
  else r_main<1>(W, dsc, rh[1], rh[0], lane, w);
  __syncthreads();
  if (rank < 2 && threadIdx.x == 0) { fence_gpu(); red_add_u32(&g_flags[FL_ATT + 8 * 15], 1); }
  asm volatile("barrier.cluster.arrive.release.aligned;\nbarrier.cluster.wait.acquire.aligned;" ::: "memory");
}

template <int TA> __device__ __forceinline__ void wg_ss256(float* d, uint64_t a, uint64_t b) {
  asm volatile("wgmma.mma_async.sync.aligned.m64n256k16.f32.bf16.bf16 {%0,%1,%2,%3,%4,%5,%6,%7,%8,%9,%10,%11,%12,%13,%14,%15,%16,%17,%18,%19,%20,%21,%22,%23,%24,%25,%26,%27,%28,%29,%30,%31,%32,%33,%34,%35,%36,%37,%38,%39,%40,%41,%42,%43,%44,%45,%46,%47,%48,%49,%50,%51,%52,%53,%54,%55,%56,%57,%58,%59,%60,%61,%62,%63,%64,%65,%66,%67,%68,%69,%70,%71,%72,%73,%74,%75,%76,%77,%78,%79,%80,%81,%82,%83,%84,%85,%86,%87,%88,%89,%90,%91,%92,%93,%94,%95,%96,%97,%98,%99,%100,%101,%102,%103,%104,%105,%106,%107,%108,%109,%110,%111,%112,%113,%114,%115,%116,%117,%118,%119,%120,%121,%122,%123,%124,%125,%126,%127}, %128, %129, 1, 1, 1, %130, 1;"
               : "+f"(d[0]), "+f"(d[1]), "+f"(d[2]), "+f"(d[3]), "+f"(d[4]), "+f"(d[5]), "+f"(d[6]), "+f"(d[7]),
                 "+f"(d[8]), "+f"(d[9]), "+f"(d[10]), "+f"(d[11]), "+f"(d[12]), "+f"(d[13]), "+f"(d[14]), "+f"(d[15]),
                 "+f"(d[16]), "+f"(d[17]), "+f"(d[18]), "+f"(d[19]), "+f"(d[20]), "+f"(d[21]), "+f"(d[22]), "+f"(d[23]),
                 "+f"(d[24]), "+f"(d[25]), "+f"(d[26]), "+f"(d[27]), "+f"(d[28]), "+f"(d[29]), "+f"(d[30]), "+f"(d[31]),
                 "+f"(d[32]), "+f"(d[33]), "+f"(d[34]), "+f"(d[35]), "+f"(d[36]), "+f"(d[37]), "+f"(d[38]), "+f"(d[39]),
                 "+f"(d[40]), "+f"(d[41]), "+f"(d[42]), "+f"(d[43]), "+f"(d[44]), "+f"(d[45]), "+f"(d[46]), "+f"(d[47]),
                 "+f"(d[48]), "+f"(d[49]), "+f"(d[50]), "+f"(d[51]), "+f"(d[52]), "+f"(d[53]), "+f"(d[54]), "+f"(d[55]),
                 "+f"(d[56]), "+f"(d[57]), "+f"(d[58]), "+f"(d[59]), "+f"(d[60]), "+f"(d[61]), "+f"(d[62]), "+f"(d[63]),
                 "+f"(d[64]), "+f"(d[65]), "+f"(d[66]), "+f"(d[67]), "+f"(d[68]), "+f"(d[69]), "+f"(d[70]), "+f"(d[71]),
                 "+f"(d[72]), "+f"(d[73]), "+f"(d[74]), "+f"(d[75]), "+f"(d[76]), "+f"(d[77]), "+f"(d[78]), "+f"(d[79]),
                 "+f"(d[80]), "+f"(d[81]), "+f"(d[82]), "+f"(d[83]), "+f"(d[84]), "+f"(d[85]), "+f"(d[86]), "+f"(d[87]),
                 "+f"(d[88]), "+f"(d[89]), "+f"(d[90]), "+f"(d[91]), "+f"(d[92]), "+f"(d[93]), "+f"(d[94]), "+f"(d[95]),
                 "+f"(d[96]), "+f"(d[97]), "+f"(d[98]), "+f"(d[99]), "+f"(d[100]), "+f"(d[101]), "+f"(d[102]), "+f"(d[103]),
                 "+f"(d[104]), "+f"(d[105]), "+f"(d[106]), "+f"(d[107]), "+f"(d[108]), "+f"(d[109]), "+f"(d[110]), "+f"(d[111]),
                 "+f"(d[112]), "+f"(d[113]), "+f"(d[114]), "+f"(d[115]), "+f"(d[116]), "+f"(d[117]), "+f"(d[118]), "+f"(d[119]),
                 "+f"(d[120]), "+f"(d[121]), "+f"(d[122]), "+f"(d[123]), "+f"(d[124]), "+f"(d[125]), "+f"(d[126]), "+f"(d[127])
               : "l"(a), "l"(b), "n"(TA));
}
template <int TA> __device__ __forceinline__ void wg_ss128(float* d, uint64_t a, uint64_t b) {
  asm volatile("wgmma.mma_async.sync.aligned.m64n128k16.f32.bf16.bf16 {%0,%1,%2,%3,%4,%5,%6,%7,%8,%9,%10,%11,%12,%13,%14,%15,%16,%17,%18,%19,%20,%21,%22,%23,%24,%25,%26,%27,%28,%29,%30,%31,%32,%33,%34,%35,%36,%37,%38,%39,%40,%41,%42,%43,%44,%45,%46,%47,%48,%49,%50,%51,%52,%53,%54,%55,%56,%57,%58,%59,%60,%61,%62,%63}, %64, %65, 1, 1, 1, %66, 1;"
               : "+f"(d[0]), "+f"(d[1]), "+f"(d[2]), "+f"(d[3]), "+f"(d[4]), "+f"(d[5]), "+f"(d[6]), "+f"(d[7]),
                 "+f"(d[8]), "+f"(d[9]), "+f"(d[10]), "+f"(d[11]), "+f"(d[12]), "+f"(d[13]), "+f"(d[14]), "+f"(d[15]),
                 "+f"(d[16]), "+f"(d[17]), "+f"(d[18]), "+f"(d[19]), "+f"(d[20]), "+f"(d[21]), "+f"(d[22]), "+f"(d[23]),
                 "+f"(d[24]), "+f"(d[25]), "+f"(d[26]), "+f"(d[27]), "+f"(d[28]), "+f"(d[29]), "+f"(d[30]), "+f"(d[31]),
                 "+f"(d[32]), "+f"(d[33]), "+f"(d[34]), "+f"(d[35]), "+f"(d[36]), "+f"(d[37]), "+f"(d[38]), "+f"(d[39]),
                 "+f"(d[40]), "+f"(d[41]), "+f"(d[42]), "+f"(d[43]), "+f"(d[44]), "+f"(d[45]), "+f"(d[46]), "+f"(d[47]),
                 "+f"(d[48]), "+f"(d[49]), "+f"(d[50]), "+f"(d[51]), "+f"(d[52]), "+f"(d[53]), "+f"(d[54]), "+f"(d[55]),
                 "+f"(d[56]), "+f"(d[57]), "+f"(d[58]), "+f"(d[59]), "+f"(d[60]), "+f"(d[61]), "+f"(d[62]), "+f"(d[63])
               : "l"(a), "l"(b), "n"(TA));
}
template <int TA> __device__ __forceinline__ void wg_ss256_first(float* d, uint64_t a, uint64_t b) {
  asm volatile("wgmma.mma_async.sync.aligned.m64n256k16.f32.bf16.bf16 {%0,%1,%2,%3,%4,%5,%6,%7,%8,%9,%10,%11,%12,%13,%14,%15,%16,%17,%18,%19,%20,%21,%22,%23,%24,%25,%26,%27,%28,%29,%30,%31,%32,%33,%34,%35,%36,%37,%38,%39,%40,%41,%42,%43,%44,%45,%46,%47,%48,%49,%50,%51,%52,%53,%54,%55,%56,%57,%58,%59,%60,%61,%62,%63,%64,%65,%66,%67,%68,%69,%70,%71,%72,%73,%74,%75,%76,%77,%78,%79,%80,%81,%82,%83,%84,%85,%86,%87,%88,%89,%90,%91,%92,%93,%94,%95,%96,%97,%98,%99,%100,%101,%102,%103,%104,%105,%106,%107,%108,%109,%110,%111,%112,%113,%114,%115,%116,%117,%118,%119,%120,%121,%122,%123,%124,%125,%126,%127}, %128, %129, 0, 1, 1, %130, 1;"
               : "=f"(d[0]), "=f"(d[1]), "=f"(d[2]), "=f"(d[3]), "=f"(d[4]), "=f"(d[5]), "=f"(d[6]), "=f"(d[7]),
                 "=f"(d[8]), "=f"(d[9]), "=f"(d[10]), "=f"(d[11]), "=f"(d[12]), "=f"(d[13]), "=f"(d[14]), "=f"(d[15]),
                 "=f"(d[16]), "=f"(d[17]), "=f"(d[18]), "=f"(d[19]), "=f"(d[20]), "=f"(d[21]), "=f"(d[22]), "=f"(d[23]),
                 "=f"(d[24]), "=f"(d[25]), "=f"(d[26]), "=f"(d[27]), "=f"(d[28]), "=f"(d[29]), "=f"(d[30]), "=f"(d[31]),
                 "=f"(d[32]), "=f"(d[33]), "=f"(d[34]), "=f"(d[35]), "=f"(d[36]), "=f"(d[37]), "=f"(d[38]), "=f"(d[39]),
                 "=f"(d[40]), "=f"(d[41]), "=f"(d[42]), "=f"(d[43]), "=f"(d[44]), "=f"(d[45]), "=f"(d[46]), "=f"(d[47]),
                 "=f"(d[48]), "=f"(d[49]), "=f"(d[50]), "=f"(d[51]), "=f"(d[52]), "=f"(d[53]), "=f"(d[54]), "=f"(d[55]),
                 "=f"(d[56]), "=f"(d[57]), "=f"(d[58]), "=f"(d[59]), "=f"(d[60]), "=f"(d[61]), "=f"(d[62]), "=f"(d[63]),
                 "=f"(d[64]), "=f"(d[65]), "=f"(d[66]), "=f"(d[67]), "=f"(d[68]), "=f"(d[69]), "=f"(d[70]), "=f"(d[71]),
                 "=f"(d[72]), "=f"(d[73]), "=f"(d[74]), "=f"(d[75]), "=f"(d[76]), "=f"(d[77]), "=f"(d[78]), "=f"(d[79]),
                 "=f"(d[80]), "=f"(d[81]), "=f"(d[82]), "=f"(d[83]), "=f"(d[84]), "=f"(d[85]), "=f"(d[86]), "=f"(d[87]),
                 "=f"(d[88]), "=f"(d[89]), "=f"(d[90]), "=f"(d[91]), "=f"(d[92]), "=f"(d[93]), "=f"(d[94]), "=f"(d[95]),
                 "=f"(d[96]), "=f"(d[97]), "=f"(d[98]), "=f"(d[99]), "=f"(d[100]), "=f"(d[101]), "=f"(d[102]), "=f"(d[103]),
                 "=f"(d[104]), "=f"(d[105]), "=f"(d[106]), "=f"(d[107]), "=f"(d[108]), "=f"(d[109]), "=f"(d[110]), "=f"(d[111]),
                 "=f"(d[112]), "=f"(d[113]), "=f"(d[114]), "=f"(d[115]), "=f"(d[116]), "=f"(d[117]), "=f"(d[118]), "=f"(d[119]),
                 "=f"(d[120]), "=f"(d[121]), "=f"(d[122]), "=f"(d[123]), "=f"(d[124]), "=f"(d[125]), "=f"(d[126]), "=f"(d[127])
               : "l"(a), "l"(b), "n"(TA));
}
template <int TA> __device__ __forceinline__ void wg_ss128_first(float* d, uint64_t a, uint64_t b) {
  asm volatile("wgmma.mma_async.sync.aligned.m64n128k16.f32.bf16.bf16 {%0,%1,%2,%3,%4,%5,%6,%7,%8,%9,%10,%11,%12,%13,%14,%15,%16,%17,%18,%19,%20,%21,%22,%23,%24,%25,%26,%27,%28,%29,%30,%31,%32,%33,%34,%35,%36,%37,%38,%39,%40,%41,%42,%43,%44,%45,%46,%47,%48,%49,%50,%51,%52,%53,%54,%55,%56,%57,%58,%59,%60,%61,%62,%63}, %64, %65, 0, 1, 1, %66, 1;"
               : "=f"(d[0]), "=f"(d[1]), "=f"(d[2]), "=f"(d[3]), "=f"(d[4]), "=f"(d[5]), "=f"(d[6]), "=f"(d[7]),
                 "=f"(d[8]), "=f"(d[9]), "=f"(d[10]), "=f"(d[11]), "=f"(d[12]), "=f"(d[13]), "=f"(d[14]), "=f"(d[15]),
                 "=f"(d[16]), "=f"(d[17]), "=f"(d[18]), "=f"(d[19]), "=f"(d[20]), "=f"(d[21]), "=f"(d[22]), "=f"(d[23]),
                 "=f"(d[24]), "=f"(d[25]), "=f"(d[26]), "=f"(d[27]), "=f"(d[28]), "=f"(d[29]), "=f"(d[30]), "=f"(d[31]),
                 "=f"(d[32]), "=f"(d[33]), "=f"(d[34]), "=f"(d[35]), "=f"(d[36]), "=f"(d[37]), "=f"(d[38]), "=f"(d[39]),
                 "=f"(d[40]), "=f"(d[41]), "=f"(d[42]), "=f"(d[43]), "=f"(d[44]), "=f"(d[45]), "=f"(d[46]), "=f"(d[47]),
                 "=f"(d[48]), "=f"(d[49]), "=f"(d[50]), "=f"(d[51]), "=f"(d[52]), "=f"(d[53]), "=f"(d[54]), "=f"(d[55]),
                 "=f"(d[56]), "=f"(d[57]), "=f"(d[58]), "=f"(d[59]), "=f"(d[60]), "=f"(d[61]), "=f"(d[62]), "=f"(d[63])
               : "l"(a), "l"(b), "n"(TA));
}

constexpr uint32_t H_SB = 0x400;
constexpr int H_STAGE = 49152, H_NST = 4;
constexpr int H_STG = H_NST * H_STAGE;
constexpr int H_VEC = H_STG + 3 * 8192;
constexpr int H_GATE = H_VEC + 6656;
constexpr int H_BAR = H_GATE + 1024;
constexpr int H_SMEM = H_BAR + 256;
constexpr int HB_FULL = 0, HB_EMPTY = 32, HB_IFULL = 64, HB_IEMPTY = 80, HB_VFULL = 96, HB_STGF = 112, HB_ITEM = 120, HB_Q = 128, HB_SRDY = 160, HB_SFREE = 184,
              HB_MFULL = 208, HB_MEMPTY = 224, HB_MAIL = 240;
constexpr int NB_HX = 4, NB_HY = 5, NB_HZ = 6;
enum { IT_END = 0, IT_MOD = 1, IT_XT = 2, IT_OUT = 3, IT_WS = 4, IT_F1 = 5, IT_F2 = 6, IT_STAT = 7 };
constexpr int N_MOD = 32, N_WS = 28, N_XT = 2, N_STAT = 4;
constexpr int MAX_ITEMS = 1400;
#define NH2 94
constexpr int NH1 = 36;
struct HList { uint32_t n, head, tbase; uint32_t it[MAX_ITEMS]; };
#define HT(i)

#define POL_WO L2_NORMAL
#define POL_W2 L2_NORMAL
#define POL_ATT L2_FIRST
#define POL_ACT L2_FIRST
#define POL_PRE L2_FIRST
__device__ __forceinline__ void mbar_arrive_n(uint32_t b, uint32_t n) { asm volatile("mbarrier.arrive.shared::cta.b64 _, [%0], %1;" :: "r"(b), "r"(n) : "memory"); }
__device__ __forceinline__ void mbar_arrive_cl(uint32_t b) { asm volatile("mbarrier.arrive.shared::cluster.b64 _, [%0];" :: "r"(b) : "memory"); }
__device__ __forceinline__ void h_free(uint32_t b, uint32_t pm) { mbar_arrive(b); mbar_arrive_cl(b ^ pm); }
__device__ __forceinline__ void tma2d_mc(uint32_t dst, const CUtensorMap* m, int c0, int c1, uint32_t bar, uint64_t pol) {
  asm volatile("cp.async.bulk.tensor.2d.shared::cluster.global.mbarrier::complete_tx::bytes.multicast::cluster.L2::cache_hint [%0], [%1, {%3, %4}], [%2], %5, %6;"
               :: "r"(dst), "l"(m), "r"(bar), "r"(c0), "r"(c1), "h"((uint16_t)3), "l"(pol) : "memory");
}
__device__ __forceinline__ void bulk_mc(uint32_t dst, const void* src, uint32_t bytes, uint32_t bar, uint64_t pol) {
  asm volatile("cp.async.bulk.shared::cluster.global.mbarrier::complete_tx::bytes.multicast::cluster.L2::cache_hint [%0], [%1], %2, [%3], %4, %5;"
               :: "r"(dst), "l"(src), "r"(bytes), "r"(bar), "h"((uint16_t)3), "l"(pol) : "memory");
}
__device__ __forceinline__ void cluster_sync() {
  asm volatile("barrier.cluster.arrive.release.aligned;\nbarrier.cluster.wait.acquire.aligned;" ::: "memory");
}
__device__ __forceinline__ void bulk_s2g(void* dst, uint32_t src, uint32_t bytes) {
  asm volatile("cp.async.bulk.global.shared::cta.bulk_group [%0], [%1], %2;" :: "l"(dst), "r"(src), "r"(bytes) : "memory");
}
__device__ __forceinline__ void tma2d_add(const CUtensorMap* m, int c0, int c1, uint32_t src) {
  asm volatile("cp.reduce.async.bulk.tensor.2d.global.shared::cta.add.tile.bulk_group [%0, {%2, %3}], [%1];" :: "l"(m), "r"(src), "r"(c0), "r"(c1) : "memory");
}
__device__ __forceinline__ void bulk_commit() { asm volatile("cp.async.bulk.commit_group;" ::: "memory"); }
template <int N> __device__ __forceinline__ void bulk_wait_read() { asm volatile("cp.async.bulk.wait_group.read %0;" :: "n"(N) : "memory"); }
__device__ __forceinline__ void bulk_wait_all() { asm volatile("cp.async.bulk.wait_group 0;" ::: "memory"); }
__device__ __forceinline__ uint32_t hfma2(uint32_t a, uint32_t b, uint32_t c) { uint32_t t; asm("fma.rn.bf16x2 %0, %1, %2, %3;" : "=r"(t) : "r"(a), "r"(b), "r"(c)); return t; }
__device__ __forceinline__ float lds32f(uint32_t a) { return __uint_as_float(lds32(a)); }

template <int BN, int TA, int K0, int K1>
__device__ __forceinline__ void h_mma(float* acc, uint64_t da, uint64_t db) {
#pragma unroll
  for (int k = K0; k < K1; k++) {
    const uint64_t a = da + k * (TA ? 256 : 2), b = db + k * 128;
    if (BN == 256) wg_ss256<TA>(acc, a, b); else wg_ss128<TA>(acc, a, b);
  }
}
template <int BN, int TA>
__device__ __forceinline__ void h_mainloop(float* acc, uint32_t sb, uint32_t pm, int nst, uint32_t& st, uint32_t& ph, int wg, bool leader, uint32_t clk_q) {
  const uint64_t da0 = TA ? mkdesc(H_SB + wg * 1024, 2048, 128, 0) : mkdesc(H_SB + wg * 8192, 16, 1024, 1);
  const uint64_t db0 = mkdesc(H_SB + 16384, 8192, 1024, 1);
  const uint32_t full = sb + H_BAR + HB_FULL, empty = sb + H_BAR + HB_EMPTY;
  uint32_t prev = st;
  {
    mbar_wait(full + st * 8, ph);
    HT(1);
    const uint64_t da = da0 + st * (H_STAGE >> 4), db = db0 + st * (H_STAGE >> 4);
    WG_FENCE();
    if (BN == 256) wg_ss256_first<TA>(acc, da, db); else wg_ss128_first<TA>(acc, da, db);
    h_mma<BN, TA, 1, 4>(acc, da, db);
    WG_COMMIT();
    if (++st == H_NST) { st = 0; ph ^= 1; }
  }
  {
    mbar_wait(full + st * 8, ph);
    const uint64_t da = da0 + st * (H_STAGE >> 4), db = db0 + st * (H_STAGE >> 4);
    WG_FENCE();
    h_mma<BN, TA, 0, 3>(acc, da, db);
    WG_COMMIT();
    h_mma<BN, TA, 3, 4>(acc, da, db);
    WG_COMMIT();
    WG_WAIT(1);
    if (leader) h_free(empty + prev * 8, pm);
    if (wg) bar_arrive<NB_HY, 256>(); else bar_sync<NB_HY, 256>();
    prev = st;
    if (++st == H_NST) { st = 0; ph ^= 1; }
  }
#pragma unroll 1
  for (int i = 4; i < nst; i++) {
    mbar_wait(full + st * 8, ph);
    const uint64_t da = da0 + st * (H_STAGE >> 4), db = db0 + st * (H_STAGE >> 4);
    WG_FENCE();
    h_mma<BN, TA, 0, 4>(acc, da, db);
    WG_COMMIT();
    WG_WAIT(1);
    if (leader) h_free(empty + prev * 8, pm);
    prev = st;
    if (++st == H_NST) { st = 0; ph ^= 1; }
  }
  if (wg) {
    WG_WAIT(0);
    if (leader) h_free(empty + prev * 8, pm);
    bar_sync<NB_HX, 256>();
  }
  {
    mbar_wait(full + st * 8, ph);
    const uint64_t da = da0 + st * (H_STAGE >> 4), db = db0 + st * (H_STAGE >> 4);
    WG_FENCE();
    h_mma<BN, TA, 0, 4>(acc, da, db);
    WG_COMMIT();
    WG_WAIT(1);
    if (leader && !wg) h_free(empty + prev * 8, pm);
    prev = st;
    if (++st == H_NST) { st = 0; ph ^= 1; }
  }
  {
    mbar_wait(full + st * 8, ph);
    const uint64_t da = da0 + st * (H_STAGE >> 4), db = db0 + st * (H_STAGE >> 4);
    WG_FENCE();
    h_mma<BN, TA, 0, 3>(acc, da, db);
    WG_COMMIT();
    h_mma<BN, TA, 3, 4>(acc, da, db);
    WG_COMMIT();
    WG_WAIT(1);
    if (leader) h_free(empty + prev * 8, pm);
    if (!wg) bar_arrive<NB_HX, 256>();
  }
}
__device__ __forceinline__ void h_release(uint32_t sb, uint32_t pm, uint32_t& st, uint32_t& ph, bool leader) {
  if (leader) h_free(sb + H_BAR + HB_EMPTY + st * 8, pm);
  if (++st == H_NST) { st = 0; ph ^= 1; }
}

__device__ __forceinline__ uint32_t stg_acquire(uint32_t sb, uint32_t g, uint32_t& b) {
  const uint32_t q = (g * 43691u) >> 17;
  b = g - 3 * q;
  mbar_wait(sb + H_BAR + HB_SFREE + b * 8, (q & 1) ^ 1);
  return sb + H_STG + b * 8192;
}
__device__ __forceinline__ void stg_release(uint32_t sb, uint32_t b, int lane) {
  __syncwarp();
  if (lane == 0) mbar_arrive(sb + H_BAR + HB_SRDY + b * 8);
}
__device__ __forceinline__ uint32_t hmul2(uint32_t a, uint32_t b) { uint32_t t; asm("mul.rn.bf16x2 %0, %1, %2;" : "=r"(t) : "r"(a), "r"(b)); return t; }
template <int BN>
__device__ __forceinline__ void h_gated(float* acc, uint32_t va, uint32_t vb, uint32_t vp, uint32_t sb, uint32_t pm, uint32_t& st, uint32_t& ph, uint32_t g0, int wg, bool leader,
                                        int warp, int lane, uint32_t clk_q) {
  uint32_t gt[BN / 8];
  mbar_wait(vb, vp);
#pragma unroll
  for (int i = 0; i < BN / 32; i++) lds128(gt + 4 * i, va + i * 64 + (lane & 3) * 16);
  WG_WAIT(0);
  reg_fence<BN / 2>(acc);
  h_release(sb, pm, st, ph, leader);
  HT(2);
  const uint32_t ro = ((warp & 3) * 16 + (lane & 7)) * 128, x0 = ((lane >> 3) ^ (lane & 7)) << 4;
  if (BN == 256 && wg) bar_sync<NB_HZ, 256>();
#pragma unroll
  for (int u = 0; u < BN / 64; u++) {
    uint32_t b;
    const uint32_t base = stg_acquire(sb, g0 + u, b) + ro;
    if (BN == 256 && u == 1 && !wg) bar_arrive<NB_HZ, 256>();
#pragma unroll
    for (int c2 = 0; c2 < 2; c2++) {
      const int c = 2 * u + c2;
#pragma unroll
      for (int h = 0; h < 2; h++) {
        uint32_t y[4];
#pragma unroll
        for (int j = 0; j < 4; j++) { const float* a = acc + c * 16 + j * 4 + h * 2; y[j] = hmul2(pack2(a[0], a[1]), gt[4 * c + j]); }
        stsm4(base + h * 1024 + (x0 ^ (c2 << 6)), y);
      }
    }
    stg_release(sb, b, lane);
  }
}

template <int BN>
__device__ __forceinline__ void h_swiglu(float* acc, uint32_t vb, uint32_t vp, uint32_t sb, uint32_t pm, uint32_t& st, uint32_t& ph, uint32_t g0, int wg, bool leader,
                                         int warp, int lane, uint32_t clk_q) {
  float rs[2], rh[2];
  mbar_wait(vb, vp);
  {
    const uint64_t da = mkdesc(H_SB + H_VEC + 4096 + wg * 1024, 0, 128, 0), db = mkdesc(H_SB + H_VEC, 1024, 0, 1);
    WG_FENCE();
    if (BN == 256) wg_ss256<0>(acc, da, db); else wg_ss128<0>(acc, da, db);
    WG_COMMIT();
  }
#pragma unroll
  for (int h = 0; h < 2; h++) { rs[h] = lds32f(sb + H_VEC + 6144 + (warp * 16 + h * 8 + (lane >> 2)) * 4); rh[h] = 0.5f * rs[h]; }
  WG_WAIT(1);
  h_release(sb, pm, st, ph, leader);
  WG_WAIT(0);
  reg_fence<BN / 2>(acc);
  HT(2);
  const uint32_t ro = ((warp & 3) * 16 + (lane & 7)) * 128, x0 = ((lane >> 3) ^ (lane & 7)) << 4;
#pragma unroll
  for (int uu = 0; uu < BN / 128; uu++) {
    uint32_t b;
    const uint32_t base = stg_acquire(sb, g0 + uu, b) + ro;
#pragma unroll
    for (int c2 = 0; c2 < 2; c2++) {
      const int c = 2 * uu + c2;
      uint32_t y[2][4];
#pragma unroll
      for (int j = 0; j < 4; j++) {
        const float* g = acc + 16 * c + 4 * j; const float* u = g + BN / 4;
        float o[4];
#pragma unroll
        for (int e = 0; e < 4; e++) {
          const float g2 = rh[e >> 1] * g[e];
          const float h = g2 * (rs[e >> 1] * u[e]);
          float t; asm("tanh.approx.f32 %0, %1;" : "=f"(t) : "f"(g2));
          o[e] = fmaf(h, t, h);
        }
        y[0][j] = pack2(o[0], o[1]); y[1][j] = pack2(o[2], o[3]);
      }
      stsm4(base + (x0 ^ (c2 << 6)), y[0]); stsm4(base + 1024 + (x0 ^ (c2 << 6)), y[1]);
    }
    stg_release(sb, b, lane);
  }
}

template <bool WS>
__device__ __forceinline__ void h_vecmat(uint32_t sb, int idx, uint32_t& st, uint32_t& ph, int tid, const __nv_bfloat16* cvec, uint8_t* w13s, uint8_t* bext,
                                         __nv_bfloat16* mod, __nv_bfloat16* gate) {
  const uint32_t stg = sb + H_STG, bars = sb + H_BAR;
  const int lane = tid & 31, warp = tid >> 5;
#pragma unroll
  for (int i = 0; i < 4; i++) {
    const int k = tid + 256 * i;
    if (WS) {
      const uint32_t s = __ldcg(reinterpret_cast<const uint16_t*>(mod) + 3 * D_ + k), c = __ldcg(reinterpret_cast<const uint16_t*>(mod) + 4 * D_ + k);
      sts32(stg + k * 4, s << 16); sts32(stg + 4096 + k * 4, c | c << 16);
    } else {
      const float c = __bfloat162float(cvec[k]);
      sts32(stg + k * 4, __float_as_uint(__bfloat162float(__float2bfloat16(c / (1.f + __expf(-c))))));
    }
  }
  bar_sync<1, 256>();
  float v[4][8], u[4][8];
#pragma unroll
  for (int b = 0; b < 4; b++)
#pragma unroll
    for (int e = 0; e < 8; e++) { v[b][e] = 0.f; u[b][e] = 0.f; }
  const int r0 = tid >> 3;
  const uint32_t off = 16384 + r0 * 128 + (((tid & 7) ^ (r0 & 7)) << 4);
  uint32_t prev = 0;
#pragma unroll 1
  for (int i = 0; i < (WS ? 16 : 8); i++) {
    mbar_wait(bars + HB_FULL + st * 8, ph);
    const uint32_t base = sb + st * H_STAGE + off;
#pragma unroll
    for (int ri = 0; ri < 2; ri++) {
      const uint32_t ka = stg + ((WS ? i * 64 : i * 128) + r0 + 32 * ri) * 4;
      const float m0 = lds32f(ka), m1 = WS ? m0 : lds32f(ka + 256);
      const uint32_t c2 = WS ? lds32(ka + 4096) : 0;
#pragma unroll
      for (int b = 0; b < 4; b++) {
        uint32_t w[4];
        lds128(w, base + b * 8192 + ri * 4096);
        const float m = b < 2 ? m0 : m1;
#pragma unroll
        for (int e = 0; e < 4; e++) {
          v[b][2 * e] = fmaf(m, bf_lo(w[e]), v[b][2 * e]); v[b][2 * e + 1] = fmaf(m, bf_hi(w[e]), v[b][2 * e + 1]);
          if (WS) { w[e] = hfma2(w[e], c2, w[e]); u[b][2 * e] += bf_lo(w[e]); u[b][2 * e + 1] += bf_hi(w[e]); }
        }
        if (WS) sts128(base + b * 8192 + ri * 4096, w[0], w[1], w[2], w[3]);
      }
    }
    if (WS) fence_async_smem();
    bar_sync<1, 256>();
    if (tid == 0) {
      if (WS) {
        bulk_s2g(w13s + (size_t)(idx * 16 + i) * 32768, sb + st * H_STAGE + 16384, 32768);
        bulk_commit();
        if (i > 0) { bulk_wait_read<1>(); mbar_arrive_n(bars + HB_EMPTY + prev * 8, 4); }
      } else mbar_arrive_n(bars + HB_EMPTY + st * 8, 4);
    }
    prev = st;
    if (++st == H_NST) { st = 0; ph ^= 1; }
  }
  if (WS && tid == 0) {
    bulk_wait_read<0>(); mbar_arrive_n(bars + HB_EMPTY + prev * 8, 4);
    bulk_wait_all(); fence_async_all(); fence_gpu();
  }
#pragma unroll
  for (int b = 0; b < 4; b++)
#pragma unroll
    for (int e = 0; e < 8; e++) {
      v[b][e] += __shfl_xor_sync(0xffffffffu, v[b][e], 8); v[b][e] += __shfl_xor_sync(0xffffffffu, v[b][e], 16);
      if (WS) { u[b][e] += __shfl_xor_sync(0xffffffffu, u[b][e], 8); u[b][e] += __shfl_xor_sync(0xffffffffu, u[b][e], 16); }
    }
  if (lane < 8) {
#pragma unroll
    for (int b = 0; b < 4; b++) {
      const uint32_t a = stg + warp * 2048 + b * 256 + lane * 32;
      sts128(a, __float_as_uint(v[b][0]), __float_as_uint(v[b][1]), __float_as_uint(v[b][2]), __float_as_uint(v[b][3]));
      sts128(a + 16, __float_as_uint(v[b][4]), __float_as_uint(v[b][5]), __float_as_uint(v[b][6]), __float_as_uint(v[b][7]));
      if (WS) {
        sts128(a + 1024, __float_as_uint(u[b][0]), __float_as_uint(u[b][1]), __float_as_uint(u[b][2]), __float_as_uint(u[b][3]));
        sts128(a + 1040, __float_as_uint(u[b][4]), __float_as_uint(u[b][5]), __float_as_uint(u[b][6]), __float_as_uint(u[b][7]));
      }
    }
  }
  bar_sync<1, 256>();
  float sv = 0.f, su = 0.f;
#pragma unroll
  for (int i = 0; i < 8; i++) {
    sv += lds32f(stg + i * 2048 + tid * 4);
    su += WS ? lds32f(stg + i * 2048 + 1024 + tid * 4) : lds32f(stg + i * 2048 + (tid ^ 128) * 4);
  }
  if (WS) {
    const __nv_bfloat16 uh = __float2bfloat16(su), ul = __float2bfloat16(su - __bfloat162float(uh));
    const __nv_bfloat16 vh = __float2bfloat16(sv), vl = __float2bfloat16(sv - __bfloat162float(vh)), z = __float2bfloat16(0.f);
    uint8_t* p = bext + idx * 4096 + (tid >> 6) * 1024 + (tid & 7) * 2;
#pragma unroll
    for (int r = 0; r < 8; r++)
      *reinterpret_cast<__nv_bfloat16*>(p + r * 128 + ((((tid & 63) >> 3) ^ r) << 4)) = r == 0 || r == 2 ? uh : r == 1 ? ul : r == 3 || r == 5 ? vh : r == 4 ? vl : z;
  } else if (tid < 128) {
    const int n = idx * 128 + tid, vec = n >> 10, col = n & 1023;
    const __nv_bfloat16 r = __float2bfloat16(sv + su);
    mod[2048 + n] = r;
    if (vec == 0 || vec == 3) gate[(vec ? D_ : 0) + (col & ~31) + ((col >> 1) & 3) * 8 + ((col >> 3) & 3) * 2 + (col & 1)] = r;
  }
}

struct HWeights { const uint8_t* p[4]; };
#define HW_T 420
#define HW_D 0
#define HW_U0 0
#define HW_U1 0
__global__ void __launch_bounds__(384, 1)
kernel_H(const __grid_constant__ CUtensorMap tmo, const __grid_constant__ CUtensorMap tm1, const __grid_constant__ CUtensorMap tm3,
         const __grid_constant__ CUtensorMap tm2, const __grid_constant__ CUtensorMap tmm, const __grid_constant__ CUtensorMap tmx,
         const __grid_constant__ CUtensorMap tmy, const __nv_bfloat16* __restrict__ x, const __nv_bfloat16* __restrict__ cvec, __nv_bfloat16* out, const __grid_constant__ HWeights rw, const __grid_constant__ HList list) {
  extern __shared__ __align__(1024) uint8_t smem[];
  uint32_t rank, pair;
  asm("mov.u32 %0, %%cluster_ctarank;" : "=r"(rank)); asm("mov.u32 %0, %%cluster_nctarank;" : "=r"(pair));
  rank = __shfl_sync(0xffffffffu, rank, 0); pair = __shfl_sync(0xffffffffu, pair, 0) - 1;
  const uint32_t sb = H_SB + (rank << 24), bars = sb + H_BAR, pm = pair << 24;
  const int tid = threadIdx.x, lane = tid & 31;
  const int warp = __shfl_sync(0xffffffffu, tid >> 5, 0);
  if (tid == 0) {
    if ((smem_u32(smem) & 0xffffff) != H_SB) __trap();
    for (int i = 0; i < H_NST; i++) { mbar_init(bars + HB_FULL + i * 8, 1); mbar_init(bars + HB_EMPTY + i * 8, 4); }
    for (int i = 0; i < 2; i++) { mbar_init(bars + HB_IFULL + i * 8, 1); mbar_init(bars + HB_IEMPTY + i * 8, 1); mbar_init(bars + HB_VFULL + i * 8, 1);
      mbar_init(bars + HB_MFULL + i * 8, 1); mbar_init(bars + HB_MEMPTY + i * 8, 1); }
    for (int i = 0; i < 3; i++) { mbar_init(bars + HB_SRDY + i * 8, 4); mbar_init(bars + HB_SFREE + i * 8, 1); }
    mbar_init(bars + HB_STGF, 1);
    asm volatile("fence.mbarrier_init.release.cluster;" ::: "memory");
    fence_async_smem();
  }
  __syncthreads();
  cluster_sync();
  asm volatile("griddepcontrol.launch_dependents;");
  if (warp >= 8) {
    asm volatile("setmaxnreg.dec.sync.aligned.u32 56;");
    if (warp == 8) {
      uint32_t st = 0, ph = 1, nv = 0, q = 0;
      uint32_t* const head = &g_flags[list.head];
      const bool claimer = lane == 0 && rank == 0;
      if (claimer) q = atomicAdd(head, 1);
#pragma unroll 1
      for (uint32_t n = 0;; n++) {
        if (pair) {
          const uint32_t o = (n & 1) * 8, p = (n >> 1) & 1;
          if (rank == 0) {
            mbar_wait(bars + HB_MEMPTY + o, p ^ 1);
            if (lane == 0) st_async1((bars + HB_MAIL + o) ^ pm, q, (bars + HB_MFULL + o) ^ pm);
          } else {
            if (lane == 0) mbar_expect(bars + HB_MFULL + o, 4);
            mbar_wait(bars + HB_MFULL + o, p);
            q = lds32(bars + HB_MAIL + o);
            __syncwarp();
            if (lane == 0) mbar_arrive_cl((bars + HB_MEMPTY + o) ^ pm);
          }
        }
        q = __shfl_sync(0xffffffffu, q, 0);
        uint32_t it = q < list.n ? list.it[q] : 0;
        const bool shA = pair && !(it >> 28 & 1), shB = pair && (it >> 28 & 1);
        if (rank && it) it += shA ? 1 << 7 : (it >> 29) << 3;
        const int type = it & 7, mt = (it >> 3) & 15, idx = (it >> 7) & 63, sz = (it >> 13) & 3, kb0 = (it >> 15) & 63, nkb = (it >> 21) & 127;
        {
          int f = FL_GO; uint32_t target = 0;
          if (type == IT_OUT) { f = lane == 0 ? FL_ATT + 8 * mt : lane == 1 ? FL_XT + 8 * mt : FL_MOD; target = lane == 0 ? 64 : lane == 1 ? N_XT : N_MOD; }
          else if (type == IT_F1) { f = lane == 0 ? FL_OUT + 8 * mt : FL_WS; target = lane == 0 ? 1024 : N_WS; }
          else if (type == IT_F2) { f = FL_F1 + 8 * mt; target = 56; }
          else if (type == IT_STAT) { f = FL_OUT + 8 * mt; target = 1024; }
          else if (type == IT_WS) { f = FL_MOD; target = N_MOD; }
          else if (type != IT_END) target = 1;
          if (lane < 3) wait_flag(&g_flags[f], target);
          __syncwarp();
          asm volatile("fence.proxy.async.global;" ::: "memory");
        }
        mbar_wait(bars + HB_IEMPTY + (n & 1) * 8, ((n >> 1) & 1) ^ 1);
        if (elect_one()) {
          sts32(bars + HB_ITEM + (n & 1) * 4, it);
          mbar_arrive(bars + HB_IFULL + (n & 1) * 8);
        }
        if (type == IT_END) break;
        const bool gemm = type == IT_OUT || type == IT_F1 || type == IT_F2;
        const int nst = gemm ? nkb : type == IT_WS ? 16 : type == IT_MOD ? 8 : 0;
        const int bn = 256 >> sz;
        const uint8_t* ap = type == IT_OUT ? g_att + (size_t)mt * 64 * 16384 : g_act + (size_t)mt * 56 * 16384;
        const uint8_t* wp = g_w13s + (size_t)(idx >> sz) * 16 * 32768 + (sz ? (idx & 1) * 8192 : 0);
        const CUtensorMap* tb = type == IT_OUT ? &tmo : type == IT_F2 ? &tm2 : type == IT_WS ? &tm1 : &tmm;
        const CUtensorMap* tc = type == IT_WS ? &tm3 : tb;
        const int c0 = gemm ? idx * bn : type == IT_WS ? idx * 128 : 2048 + idx * 128, dcol = gemm ? 128 : 0, kmul = type == IT_MOD ? 128 : 64, drow = type == IT_MOD ? 64 : 0;
        const uint32_t bytes = gemm ? 16384 + bn * 128 : 32768;
        const uint64_t pa = type == IT_OUT ? POL_ATT : POL_ACT, pb = type == IT_OUT ? POL_WO : type == IT_F2 ? POL_W2 : POL_PRE;
        if (nst < 2 && claimer) q = atomicAdd(head, 1);
#pragma unroll 1
        for (int i = 0; i < nst; i++) {
          const int kb = kb0 + i;
          const uint32_t d = sb + st * H_STAGE, fb = bars + HB_FULL + st * 8;
          if (i == nst - 2 && claimer) q = atomicAdd(head, 1);
          mbar_wait(bars + HB_EMPTY + st * 8, ph);
          if (elect_one()) {
            mbar_expect(fb, bytes);
            if (type == IT_F1) {
              if (shA) tma2d_mc(d + rank * 8192, &tmy, kb * 64, mt * 128 + rank * 64, fb, L2_NORMAL); else tma2d(d, &tmx, kb * 64, mt * 128, fb);
              if (shB) bulk_mc(d + 16384 + rank * (16384 >> sz), wp + (size_t)kb * 32768 + rank * 16384, 16384 >> sz, fb, L2_NORMAL);
              else if (sz == 0) bulk_g2s(d + 16384, wp + (size_t)kb * 32768, 32768, fb);
              else { bulk_g2s(d + 16384, wp + (size_t)kb * 32768, 8192, fb); bulk_g2s(d + 24576, wp + (size_t)kb * 32768 + 16384, 8192, fb); }
            } else {
              if (shA) bulk_mc(d + rank * 8192, ap + (size_t)kb * 16384 + rank * 8192, 8192, fb, pa);
              else if (gemm) bulk_g2s_p(d, ap + (size_t)kb * 16384, 16384, fb, pa);
              if (shB) {
                if (sz == 0) {
                  tma2d_mc(d + 16384 + rank * 16384, tb, c0 + rank * 128, kb * 64, fb, pb);
                  tma2d_mc(d + 24576 + rank * 16384, tb, c0 + rank * 128 + 64, kb * 64, fb, pb);
                } else tma2d_mc(d + 16384 + rank * 8192, tb, c0 + rank * 64, kb * 64, fb, pb);
              } else {
                tma2d_p(d + 16384, tb, c0, kb * kmul, fb, pb);
                tma2d_p(d + 24576, tb, c0 + 64, kb * kmul, fb, pb);
                if (sz == 0) { tma2d_p(d + 32768, tc, c0 + dcol, kb * kmul + drow, fb, pb); tma2d_p(d + 40960, tc, c0 + dcol + 64, kb * kmul + drow, fb, pb); }
              }
            }
          }
          if (++st == H_NST) { st = 0; ph ^= 1; }
        }
        if (gemm) {
          if (type == IT_F1) {
            if (lane == 0) wait_flag(&g_flags[FL_STAT + 8 * mt], N_STAT);
            __syncwarp();
            asm volatile("fence.proxy.async.global;" ::: "memory");
          }
          if (elect_one()) {
            const uint32_t v = sb + H_VEC, fb = bars + HB_VFULL + (nv & 1) * 8;
            if (type == IT_F1) {
              mbar_expect(fb, (4096 >> sz) + 2560);
              if (sz == 0) bulk_g2s(v, g_bext + idx * 4096, 4096, fb);
              else { const uint8_t* p = g_bext + (idx >> 1) * 4096 + (idx & 1) * 1024; bulk_g2s(v, p, 1024, fb); bulk_g2s(v + 1024, p + 2048, 1024, fb); }
              bulk_g2s(v + 4096, g_ext + mt * 2560, 2560, fb);
            } else {
              mbar_expect(fb, bn * 2);
              bulk_g2s(sb + H_GATE + (nv & 1) * 512, g_gate + (type == IT_F2 ? D_ : 0) + c0, bn * 2, fb);
            }
          }
          nv++;
        }
      }
    } else if (warp == 10) {
      if (!pair && lane == 0) {
        const uint32_t t0 = clk32() + HW_D;
        uint32_t n = 0;
#pragma unroll 1
        for (int u = HW_U0 + blockIdx.x; u < HW_U1; u += NH1, n++) {
          int m, o;
          if (u < 768) { const int r = u / 96; m = r < 4 ? r & 1 : r == 4 ? 2 : r - 5; o = (r < 2 ? 384 : r < 4 ? 0 : r == 4 ? 192 : 576) / 2 + u - r * 96; }
          else if (u < 1152) { m = (u - 768) >> 7; o = 384 + (u & 127); }
          else { m = 3; o = u - 1152; }
          while ((int32_t)(clk32() - t0 - n * HW_T) < 0) {}
          asm volatile("cp.async.bulk.prefetch.L2.global [%0], 16384;" :: "l"(rw.p[m] + (size_t)o * 16384) : "memory");
        }
      }
    } else if (warp == 9) {
      uint32_t g = 0;
#pragma unroll 1
      for (uint32_t n = 0;; n++) {
        mbar_wait(bars + HB_IFULL + (n & 1) * 8, (n >> 1) & 1);
        const uint32_t it = lds32(bars + HB_ITEM + (n & 1) * 4);
        const int type = it & 7, mt = (it >> 3) & 15, idx = (it >> 7) & 63, sz = (it >> 13) & 3, nkb = (it >> 21) & 127;
        if (type == IT_END) break;
        const bool gated = type == IT_OUT || type == IT_F2, gemm = gated || type == IT_F1;
        if (!gemm) { if (n & 1) bar_sync<3, 288>(); else bar_sync<2, 288>(); }
        if (lane == 0) {
          if (gemm) {
            const int nu = (gated ? 4 : 2) >> sz;
            uint32_t pb = 0;
#pragma unroll 1
            for (int u = 0; u < 2 * nu; u++, g++) {
              const uint32_t r = (g * 43691u) >> 17, b = g - 3 * r, src = sb + H_STG + b * 8192;
              const int w = u >= nu, uu = u - w * nu;
              mbar_wait(bars + HB_SRDY + b * 8, r & 1);
              if (u == 2 * nu - 1) mbar_arrive(bars + HB_IEMPTY + (n & 1) * 8);
              fence_async_smem();
              if (gated) tma2d_add(&tmy, idx * (256 >> sz) + uu * 64, mt * 128 + w * 64, src);
              else bulk_s2g(g_act + (size_t)(mt * 56 + idx * nu + uu) * 16384 + w * 8192, src, 8192);
              bulk_commit();
              if (u > 0) { bulk_wait_read<1>(); mbar_arrive(bars + HB_SFREE + pb * 8); }
              pb = b;
            }
            bulk_wait_read<0>();
            mbar_arrive(bars + HB_SFREE + pb * 8);
            mbar_arrive(bars + HB_STGF);
            bulk_wait_all(); fence_async_all();
          } else {
            mbar_arrive(bars + HB_STGF);
            mbar_arrive(bars + HB_IEMPTY + (n & 1) * 8);
          }
          if (type != IT_F2) {
            const uint32_t inc = type == IT_OUT ? (4 >> sz) * nkb : type == IT_F1 ? 2 >> sz : 1;
            fence_gpu();
            red_add_u32(&g_flags[type == IT_MOD ? FL_MOD : type == IT_WS ? FL_WS :
                                 (type == IT_XT ? FL_XT : type == IT_OUT ? FL_OUT : type == IT_STAT ? FL_STAT : FL_F1) + 8 * mt], inc);
          }
        }
        __syncwarp();
      }
      if (!pair) asm volatile("griddepcontrol.wait;" ::: "memory");
      uint32_t k = 0;
      if (lane == 0) { fence_gpu(); k = atomicAdd(&g_flags[FL_EXIT], 1); }
      k = __shfl_sync(0xffffffffu, k, 0);
      if (k == NH1 + NH2 - 1) {
        fence_gpu();
        for (int i = lane; i < 1024; i += 32) g_flags[i] = 0;
      }
    }
  } else {
    asm volatile("setmaxnreg.inc.sync.aligned.u32 224;");
    const int wg = warp >> 2;
    const bool leader = (tid & 127) == 0;
    uint32_t st = 0, ph = 0, nv = 0, g = 0;
#pragma unroll 1
    for (uint32_t n = 0;; n++) {
      mbar_wait(bars + HB_IFULL + (n & 1) * 8, (n >> 1) & 1);
      const uint32_t it = __shfl_sync(0xffffffffu, lds32(bars + HB_ITEM + (n & 1) * 4), 0);
      const int type = it & 7, mt = (it >> 3) & 15, idx = (it >> 7) & 63, sz = (it >> 13) & 3, nkb = (it >> 21) & 127;
      if (type == IT_END) break;
      constexpr uint32_t clk_q = 0;
      if (type == IT_OUT || type == IT_F1 || type == IT_F2) {
        const uint32_t va = sb + H_GATE + (nv & 1) * 512, vb = bars + HB_VFULL + (nv & 1) * 8, vp = (nv >> 1) & 1;
        const uint32_t nu = (type == IT_F1 ? 2 : 4) >> sz, g0 = g + wg * nu;
        nv++; g += 2 * nu;
        if (sz == 0) {
          float acc[128];
          if (type == IT_OUT) h_mainloop<256, 1>(acc, sb, pm, nkb, st, ph, wg, leader, clk_q);
          else h_mainloop<256, 0>(acc, sb, pm, nkb, st, ph, wg, leader, clk_q);
          if (type == IT_F1) h_swiglu<256>(acc, vb, vp, sb, pm, st, ph, g0, wg, leader, warp, lane, clk_q);
          else h_gated<256>(acc, va, vb, vp, sb, pm, st, ph, g0, wg, leader, warp, lane, clk_q);
        } else {
          float acc[64];
          if (type == IT_OUT) h_mainloop<128, 1>(acc, sb, pm, nkb, st, ph, wg, leader, clk_q);
          else h_mainloop<128, 0>(acc, sb, pm, nkb, st, ph, wg, leader, clk_q);
          if (type == IT_F1) h_swiglu<128>(acc, vb, vp, sb, pm, st, ph, g0, wg, leader, warp, lane, clk_q);
          else h_gated<128>(acc, va, vb, vp, sb, pm, st, ph, g0, wg, leader, warp, lane, clk_q);
        }
        HT(3);
        continue;
      } else if (type == IT_XT) {
        const uint4* xp = reinterpret_cast<const uint4*>(x + (size_t)(mt * 128 + idx * 64) * D_) + tid;
        uint4* op = reinterpret_cast<uint4*>(out + (size_t)(mt * 128 + idx * 64) * D_) + tid;
#pragma unroll 1
        for (int b = 0; b < 2; b++) {
          uint4 v[16];
#pragma unroll
          for (int i = 0; i < 16; i++) v[i] = __ldcs(xp + (b * 16 + i) * 256);
#pragma unroll
          for (int i = 0; i < 16; i++) op[(b * 16 + i) * 256] = v[i];
        }
      } else if (type == IT_STAT) {
        const int row0 = mt * 128 + idx * 32 + warp * 4;
        const uint4* xp = reinterpret_cast<const uint4*>(out + (size_t)row0 * D_) + lane;
        uint4 v[16];
#pragma unroll
        for (int i = 0; i < 16; i++) v[i] = __ldcg(xp + (i >> 2) * 128 + (i & 3) * 32);
        float s[4], m[4];
#pragma unroll
        for (int r = 0; r < 4; r++) {
          s[r] = 0.f;
#pragma unroll
          for (int i = 0; i < 4; i++) {
            const uint4 w = v[4 * r + i];
            s[r] += ((bf_lo(w.x) + bf_hi(w.x)) + (bf_lo(w.y) + bf_hi(w.y))) + ((bf_lo(w.z) + bf_hi(w.z)) + (bf_lo(w.w) + bf_hi(w.w)));
          }
        }
#pragma unroll
        for (int o = 1; o < 32; o <<= 1)
#pragma unroll
          for (int r = 0; r < 4; r++) s[r] += __shfl_xor_sync(0xffffffffu, s[r], o);
#pragma unroll
        for (int r = 0; r < 4; r++) {
          m[r] = s[r] * (1.f / D_);
          float a = 0.f, b = 0.f;
#pragma unroll
          for (int i = 0; i < 4; i++) {
            const uint4 w = v[4 * r + i];
            const uint32_t ww[4] = {w.x, w.y, w.z, w.w};
#pragma unroll
            for (int e = 0; e < 4; e++) { const float p = bf_lo(ww[e]) - m[r], t = bf_hi(ww[e]) - m[r]; a = fmaf(p, p, a); b = fmaf(t, t, b); }
          }
          s[r] = a + b;
        }
#pragma unroll
        for (int o = 1; o < 32; o <<= 1)
#pragma unroll
          for (int r = 0; r < 4; r++) s[r] += __shfl_xor_sync(0xffffffffu, s[r], o);
        if (lane < 4) {
          const float sr = lane == 0 ? s[0] : lane == 1 ? s[1] : lane == 2 ? s[2] : s[3], mr = lane == 0 ? m[0] : lane == 1 ? m[1] : lane == 2 ? m[2] : m[3];
          const float var = sr * (1.f / D_) + 1e-5f, rs = rsqrtf(var);
          const float a = -0.5f * mr, b = 0.5f * var * rs;
          const float ah = __bfloat162float(__float2bfloat16(a)), bh = __bfloat162float(__float2bfloat16(b));
          const int r = (row0 & 127) + lane;
          *reinterpret_cast<uint4*>(g_ext + mt * 2560 + r * 16) = make_uint4(pack2(ah, ah), pack2(a - ah, bh), pack2(bh, b - bh), 0u);
          *reinterpret_cast<float*>(g_ext + mt * 2560 + 2048 + r * 4) = rs;
        }
      } else {
        mbar_wait(bars + HB_STGF, (n & 1) ^ 1);
        if (type == IT_WS) h_vecmat<true>(sb, idx, st, ph, tid, cvec, g_w13s, g_bext, g_mod, g_gate);
        else h_vecmat<false>(sb, idx, st, ph, tid, cvec, g_w13s, g_bext, g_mod, g_gate);
      }
      HT(3);
      if (n & 1) bar_arrive<3, 288>(); else bar_arrive<2, 288>();
    }
  }
  cluster_sync();
}

const uint32_t h_items1[] = {
  0x1, 0x81, 0x101, 0x181, 0x201, 0x281, 0x301, 0x381, 0x401, 0x481, 0x501, 0x581, 0x601, 0x681,
  0x701, 0x781, 0x801, 0x881, 0x901, 0x981, 0xa01, 0xa81, 0xb01, 0xb81, 0xc01, 0xc81, 0xd01, 0xd81,
  0xe01, 0xe81, 0xf01, 0xf81, 0x2, 0x82, 0xa, 0x8a, 0x12, 0x92, 0x1a, 0x9a, 0x22, 0xa2,
  0x2a, 0xaa, 0x4, 0x84, 0x104, 0x184, 0x32, 0xb2, 0x3a, 0xba, 0x42, 0xc2, 0x4a, 0xca,
  0x52, 0xd2, 0x5a, 0xda, 0x62, 0xe2, 0x6a, 0xea, 0x72, 0xf2, 0x7a, 0xfa, 0x204, 0x284,
  0x304, 0x384, 0x404, 0x484, 0x504, 0x584, 0x604, 0x684, 0x704, 0x784, 0x804, 0x884, 0x904, 0x984,
  0xa04, 0xa84, 0xb04, 0xb84, 0xc04, 0xc84, 0xd04, 0xd84, 0x1000003, 0x1000083, 0x1000103, 0x1000183, 0x1040003, 0x1040083,
  0x1040103, 0x1040183, 0x1080003, 0x1080083, 0x1080103, 0x1080183, 0x10c0003, 0x10c0083, 0x10c0103, 0x10c0183, 0x1100003, 0x1100083, 0x1100103, 0x1100183,
  0x1140003, 0x1140083, 0x1140103, 0x1140183, 0x1180003, 0x1180083, 0x1180103, 0x1180183, 0x11c0003, 0x11c0083, 0x11c0103, 0x11c0183, 0x200000b, 0x200008b,
  0x200010b, 0x200018b, 0x208000b, 0x208008b, 0x208010b, 0x208018b, 0x210000b, 0x210008b, 0x210010b, 0x210018b, 0x218000b, 0x218008b, 0x218010b, 0x218018b,
  0x7, 0x87, 0x107, 0x187, 0x2000005, 0x2000085, 0x2000105, 0x2000185, 0x2000205, 0x2000285, 0x2000305, 0x2000385, 0x2000405, 0x2000485,
  0x2000505, 0x2000585, 0x2000605, 0x2000685, 0x2000705, 0x2000785, 0x2000805, 0x2000885, 0x2000905, 0x2000985, 0x2000a05, 0x2000a85, 0x2000b05, 0x2000b85,
  0x2000c05, 0x2000c85, 0x2000d05, 0x2000d85, 0x4000013, 0x4000093, 0x4000113, 0x4000193, 0x4100013, 0x4100093, 0x4100113, 0x4100193, 0xf, 0x8f,
  0x10f, 0x18f, 0x200000d, 0x200008d, 0x200010d, 0x200018d, 0x200020d, 0x200028d, 0x200030d, 0x200038d, 0x200040d, 0x200048d, 0x200050d, 0x200058d,
  0x200060d, 0x200068d, 0x200070d, 0x200078d, 0x200080d, 0x200088d, 0x200090d, 0x200098d, 0x2000a0d, 0x2000a8d, 0x2000b0d, 0x2000b8d, 0x2000c0d, 0x2000c8d,
  0x2000d0d, 0x2000d8d, 0x3800006, 0x3800086, 0x3800106, 0x3800186, 0x38e0006, 0x38e0086, 0x38e0106, 0x38e0186, 0x400001b, 0x400009b, 0x400011b, 0x400019b,
  0x410001b, 0x410009b, 0x410011b, 0x410019b, 0x380000e, 0x380008e, 0x380010e, 0x380018e, 0x38e000e, 0x38e008e, 0x38e010e, 0x38e018e, 0x17, 0x97,
  0x117, 0x197, 0x2000015, 0x2000095, 0x2000115, 0x2000195, 0x2000215, 0x2000295, 0x2000315, 0x2000395, 0x2000415, 0x2000495, 0x2000515, 0x2000595,
  0x4000023, 0x40000a3, 0x4000123, 0x40001a3, 0x4100023, 0x41000a3, 0x4100123, 0x41001a3, 0x2000615, 0x2000695, 0x2000715, 0x2000795, 0x2000815, 0x2000895,
  0x2000915, 0x2000995, 0x2000a15, 0x2000a95, 0x2000b15, 0x2000b95, 0x2000c15, 0x2000c95, 0x2000d15, 0x2000d95, 0x1f, 0x9f, 0x11f, 0x19f,
  0x200001d, 0x200009d, 0x200011d, 0x200019d, 0x200021d, 0x200029d, 0x200031d, 0x200039d, 0x200041d, 0x200049d, 0x200051d, 0x200059d, 0x400002b, 0x40000ab,
  0x400012b, 0x40001ab, 0x410002b, 0x41000ab, 0x410012b, 0x41001ab, 0x200061d, 0x200069d, 0x200071d, 0x200079d, 0x200081d, 0x200089d, 0x200091d, 0x200099d,
  0x2000a1d, 0x2000a9d, 0x2000b1d, 0x2000b9d, 0x2000c1d, 0x2000c9d, 0x2000d1d, 0x2000d9d, 0x27, 0xa7, 0x127, 0x1a7, 0x2000025, 0x20000a5,
  0x2000125, 0x20001a5, 0x2000225, 0x20002a5, 0x2000325, 0x20003a5, 0x4000033, 0x40000b3, 0x4000133, 0x40001b3, 0x4100033, 0x41000b3, 0x4100133, 0x41001b3,
  0x2000425, 0x20004a5, 0x2000525, 0x20005a5, 0x2000625, 0x20006a5, 0x2000725, 0x20007a5, 0x2000825, 0x20008a5, 0x2000925, 0x20009a5, 0x2000a25, 0x2000aa5,
  0x2000b25, 0x2000ba5, 0x2000c25, 0x2000ca5, 0x2000d25, 0x2000da5, 0x2f, 0xaf, 0x12f, 0x1af, 0x200002d, 0x20000ad, 0x200012d, 0x20001ad,
  0x200022d, 0x20002ad, 0x200032d, 0x20003ad, 0x400003b, 0x40000bb, 0x400013b, 0x40001bb, 0x410003b, 0x41000bb, 0x410013b, 0x41001bb, 0x200042d, 0x20004ad,
  0x200052d, 0x20005ad, 0x200062d, 0x20006ad, 0x200072d, 0x20007ad, 0x200082d, 0x20008ad, 0x200092d, 0x20009ad, 0x2000a2d, 0x2000aad, 0x2000b2d, 0x2000bad,
  0x2000c2d, 0x2000cad, 0x2000d2d, 0x2000dad, 0x37, 0xb7, 0x137, 0x1b7, 0x2000035, 0x20000b5, 0x2000135, 0x20001b5, 0x2000235, 0x20002b5,
  0x2000335, 0x20003b5, 0x2000435, 0x20004b5, 0x2000535, 0x20005b5, 0x4000043, 0x40000c3, 0x4000143, 0x40001c3, 0x4100043, 0x41000c3, 0x4100143, 0x41001c3,
  0x2000635, 0x20006b5, 0x2000735, 0x20007b5, 0x2000835, 0x20008b5, 0x2000935, 0x20009b5, 0x2000a35, 0x2000ab5, 0x2000b35, 0x2000bb5, 0x2000c35, 0x2000cb5,
  0x2000d35, 0x2000db5, 0x3f, 0xbf, 0x13f, 0x1bf, 0x200003d, 0x20000bd, 0x200013d, 0x20001bd, 0x200023d, 0x20002bd, 0x200033d, 0x20003bd,
  0x400004b, 0x40000cb, 0x400014b, 0x40001cb, 0x410004b, 0x41000cb, 0x410014b, 0x41001cb, 0x200043d, 0x20004bd, 0x200053d, 0x20005bd, 0x200063d, 0x20006bd,
  0x200073d, 0x20007bd, 0x200083d, 0x20008bd, 0x200093d, 0x20009bd, 0x2000a3d, 0x2000abd, 0x2000b3d, 0x2000bbd, 0x2000c3d, 0x2000cbd, 0x2000d3d, 0x2000dbd,
  0x47, 0xc7, 0x147, 0x1c7, 0x2000045, 0x20000c5, 0x2000145, 0x20001c5, 0x2000245, 0x20002c5, 0x2000345, 0x20003c5, 0x4000053, 0x40000d3,
  0x4000153, 0x40001d3, 0x4100053, 0x41000d3, 0x4100153, 0x41001d3, 0x2000445, 0x20004c5, 0x2000545, 0x20005c5, 0x2000645, 0x20006c5, 0x2000745, 0x20007c5,
  0x2000845, 0x20008c5, 0x2000945, 0x20009c5, 0x2000a45, 0x2000ac5, 0x2000b45, 0x2000bc5, 0x2000c45, 0x2000cc5, 0x2000d45, 0x2000dc5, 0x4f, 0xcf,
  0x14f, 0x1cf, 0x200004d, 0x20000cd, 0x200014d, 0x20001cd, 0x200024d, 0x20002cd, 0x200034d, 0x20003cd, 0x200044d, 0x20004cd, 0x200054d, 0x20005cd,
  0x400005b, 0x40000db, 0x400015b, 0x40001db, 0x410005b, 0x41000db, 0x410015b, 0x41001db, 0x200064d, 0x20006cd, 0x200074d, 0x20007cd, 0x200084d, 0x20008cd,
  0x200094d, 0x20009cd, 0x2000a4d, 0x2000acd, 0x2000b4d, 0x2000bcd, 0x2000c4d, 0x2000ccd, 0x2000d4d, 0x2000dcd, 0x57, 0xd7, 0x157, 0x1d7,
  0x2000055, 0x20000d5, 0x2000155, 0x20001d5, 0x2000255, 0x20002d5, 0x2000355, 0x20003d5, 0x4000063, 0x40000e3, 0x4000163, 0x40001e3, 0x4100063, 0x41000e3,
  0x4100163, 0x41001e3, 0x2000455, 0x20004d5, 0x2000555, 0x20005d5, 0x2000655, 0x20006d5, 0x2000755, 0x20007d5, 0x2000855, 0x20008d5, 0x2000955, 0x20009d5,
  0x2000a55, 0x2000ad5, 0x2000b55, 0x2000bd5, 0x2000c55, 0x2000cd5, 0x2000d55, 0x2000dd5, 0x5f, 0xdf, 0x15f, 0x1df, 0x200005d, 0x20000dd,
  0x200015d, 0x20001dd, 0x200025d, 0x20002dd, 0x200035d, 0x20003dd, 0x200006b, 0x20000eb, 0x200016b, 0x20001eb, 0x208006b, 0x20800eb, 0x208016b, 0x20801eb,
  0x210006b, 0x21000eb, 0x210016b, 0x21001eb, 0x218006b, 0x21800eb, 0x218016b, 0x21801eb, 0x200045d, 0x20004dd, 0x200055d, 0x20005dd, 0x200065d, 0x20006dd,
  0x200075d, 0x20007dd, 0x200085d, 0x20008dd, 0x200095d, 0x20009dd, 0x2000a5d, 0x2000add, 0x2000b5d, 0x2000bdd, 0x2000c5d, 0x2000cdd, 0x2000d5d, 0x2000ddd,
  0x67, 0xe7, 0x167, 0x1e7, 0x2000065, 0x20000e5, 0x2000165, 0x20001e5, 0x2000265, 0x20002e5, 0x2000365, 0x20003e5, 0x2000465, 0x20004e5,
  0x2000565, 0x20005e5, 0x2000073, 0x20000f3, 0x2000173, 0x20001f3, 0x2080073, 0x20800f3, 0x2080173, 0x20801f3, 0x2100073, 0x21000f3, 0x2100173, 0x21001f3,
  0x2180073, 0x21800f3, 0x2180173, 0x21801f3, 0x6f, 0xef, 0x16f, 0x1ef, 0x2000665, 0x20006e5, 0x2000765, 0x20007e5, 0x2000865, 0x20008e5,
  0x2000965, 0x20009e5, 0x2000a65, 0x2000ae5, 0x2000b65, 0x2000be5, 0x2000c65, 0x2000ce5, 0x2000d65, 0x2000de5, 0x200006d, 0x20000ed, 0x200016d, 0x20001ed,
  0x200026d, 0x20002ed, 0x200036d, 0x20003ed, 0x200046d, 0x20004ed, 0x200056d, 0x20005ed, 0x200066d, 0x20006ed, 0x200076d, 0x20007ed, 0x200086d, 0x20008ed,
  0x200096d, 0x20009ed, 0x2000a6d, 0x2000aed, 0x2000b6d, 0x2000bed, 0x77, 0xf7, 0x177, 0x1f7, 0x2000c6d, 0x2000ced, 0x2000d6d, 0x2000ded,
  0x2000075, 0x20000f5, 0x2000175, 0x20001f5, 0x2000275, 0x20002f5, 0x2000375, 0x20003f5, 0x2000475, 0x20004f5, 0x2000575, 0x20005f5, 0x2000675, 0x20006f5,
  0x2000775, 0x20007f5, 0x2000875, 0x20008f5, 0x2000975, 0x20009f5, 0x2000a75, 0x2000af5, 0x2000b75, 0x2000bf5, 0x2000c75, 0x2000cf5, 0x2000d75, 0x2000df5,
  0x1c0006e, 0x1c000ee, 0x1c0016e, 0x1c001ee, 0x1c7006e, 0x1c700ee, 0x1c7016e, 0x1c701ee, 0x1ce006e, 0x1ce00ee, 0x1ce016e, 0x1ce01ee, 0x1d5006e, 0x1d500ee,
  0x1d5016e, 0x1d501ee, 0x1c00076, 0x1c000f6, 0x1c00176, 0x1c001f6, 0x1c70076, 0x1c700f6, 0x1c70176, 0x1c701f6, 0x1ce0076, 0x1ce00f6, 0x1ce0176, 0x1ce01f6,
  0x1d50076, 0x1d500f6, 0x1d50176, 0x1d501f6,
};
const uint32_t h_items2[] = {
  0x100207b, 0x100217b, 0x100227b, 0x100237b, 0x104207b, 0x104217b, 0x104227b, 0x104237b, 0x108207b, 0x108217b, 0x108227b, 0x108237b, 0x10c207b, 0x10c217b,
  0x10c227b, 0x10c237b, 0x110207b, 0x110217b, 0x110227b, 0x110237b, 0x114207b, 0x114217b, 0x114227b, 0x114237b, 0x118207b, 0x118217b, 0x118227b, 0x118237b,
  0x11c207b, 0x11c217b, 0x11c227b, 0x11c237b, 0x31c00016, 0x31c00096, 0x31c00116, 0x31c00196, 0x31c70016, 0x31c70096, 0x31c70116, 0x31c70196, 0x31ce0016, 0x31ce0096,
  0x31ce0116, 0x31ce0196, 0x31d50016, 0x31d50096, 0x31d50116, 0x7f, 0x17f, 0x31d50196, 0x31c00026, 0x31c000a6, 0x31c00126, 0x31c001a6, 0x31c70026, 0x31c700a6,
  0x31c70126, 0x31c701a6, 0x31ce0026, 0x31ce00a6, 0x31ce0126, 0x31ce01a6, 0x31d50026, 0x31d500a6, 0x31d50126, 0x31d501a6, 0x31c00036, 0x31c000b6, 0x31c00136, 0x31c001b6,
  0x31c70036, 0x31c700b6, 0x31c70136, 0x31c701b6, 0x31ce0036, 0x31ce00b6, 0x31ce0136, 0x31ce01b6, 0x31d50036, 0x200207d, 0x200217d, 0x200227d, 0x200237d, 0x200247d,
  0x200257d, 0x200267d, 0x200277d, 0x200287d, 0x200297d, 0x2002a7d, 0x2002b7d, 0x2002c7d, 0x2002d7d, 0x2002e7d, 0x2002f7d, 0x200307d, 0x200317d, 0x200327d,
  0x200337d, 0x200347d, 0x200357d, 0x200367d, 0x200377d, 0x200387d, 0x200397d, 0x2003a7d, 0x2003b7d, 0x31d500b6, 0x31d50136, 0x31d501b6, 0x31c00046, 0x31c000c6,
  0x31c00146, 0x31c001c6, 0x31c70046, 0x31c700c6, 0x31c70146, 0x31c701c6, 0x31ce0046, 0x31ce00c6, 0x31ce0146, 0x31ce01c6, 0x31d50046, 0x31d500c6, 0x31d50146, 0x31d501c6,
  0x31c00056, 0x31c000d6, 0x31c00156, 0x31c001d6, 0x31c70056, 0x31c700d6, 0x31c70156, 0x31c701d6, 0x31ce0056, 0x31ce00d6, 0x31ce0156, 0x31ce01d6, 0x31d50056, 0x31d500d6,
  0x31d50156, 0x31d501d6, 0x1c00066, 0x1c00166, 0x1c70066, 0x1c70166, 0x1ce0066, 0x1ce0166, 0x1d50066, 0x1d50166, 0xe0207e, 0xe0217e, 0xe0227e, 0xe0237e,
  0xe3a07e, 0xe3a17e, 0xe3a27e, 0xe3a37e, 0xe7207e, 0xe7217e, 0xe7227e, 0xe7237e, 0xeaa07e, 0xeaa17e, 0xeaa27e, 0xeaa37e, 0xee207e, 0xee217e,
  0xee227e, 0xee237e, 0xf1a07e, 0xf1a17e, 0xf1a27e, 0xf1a37e, 0xf5207e, 0xf5217e, 0xf5227e, 0xf5237e, 0xf8a07e, 0xf8a17e, 0xf8a27e, 0xf8a37e,
};

void build_lists(HList& a, HList& b) {
  a.n = b.n = 0;
  for (uint32_t v : h_items1) a.it[a.n++] = v;
  for (uint32_t v : h_items2) b.it[b.n++] = v;
  a.head = FL_HEAD; a.tbase = 0;
  b.head = FL_HEAD2; b.tbase = a.n;
}

typedef CUresult (*EncodeFn)(CUtensorMap*, CUtensorMapDataType, cuuint32_t, void*, const cuuint64_t*, const cuuint64_t*,
                             const cuuint32_t*, const cuuint32_t*, CUtensorMapInterleave, CUtensorMapSwizzle,
                             CUtensorMapL2promotion, CUtensorMapFloatOOBfill);

void make_map(EncodeFn fn, CUtensorMap* m, const void* p, uint64_t cols, uint64_t rows, uint32_t bc, uint32_t br, CUtensorMapSwizzle sw) {
  cuuint64_t dims[2] = {cols, rows};
  cuuint64_t strides[1] = {cols * 2};
  cuuint32_t box[2] = {bc, br};
  cuuint32_t es[2] = {1, 1};
  fn(m, CU_TENSOR_MAP_DATA_TYPE_BFLOAT16, 2, const_cast<void*>(p), dims, strides, box, es, CU_TENSOR_MAP_INTERLEAVE_NONE, sw,
     CU_TENSOR_MAP_L2_PROMOTION_L2_128B, CU_TENSOR_MAP_FLOAT_OOB_FILL_NONE);
}

}

extern "C" void kernel_launch(void* const* d_in, const int* in_sizes, int n_in, void* d_out, int out_size) {
  const __nv_bfloat16* x = (const __nv_bfloat16*)d_in[0];
  const __nv_bfloat16* mem0 = (const __nv_bfloat16*)d_in[1];
  const __nv_bfloat16* cvec = (const __nv_bfloat16*)d_in[11];
  static EncodeFn enc = nullptr;
  if (!enc) {
    cudaDriverEntryPointQueryResult qr;
    void* fp = nullptr;
    cudaGetDriverEntryPoint("cuTensorMapEncodeTiled", &fp, cudaEnableDefault, &qr);
    enc = (EncodeFn)fp;
    cudaFuncSetAttribute(kernel_R, cudaFuncAttributeMaxDynamicSharedMemorySize, R_SMEM);
    cudaFuncSetAttribute(kernel_H, cudaFuncAttributeMaxDynamicSharedMemorySize, H_SMEM);
  }
  CUtensorMap tmq, tmk, tmv, tmo, tmm;
  make_map(enc, &tmm, d_in[12], 6144, 1024, 64, 64, CU_TENSOR_MAP_SWIZZLE_NONE);
  make_map(enc, &tmq, d_in[2], 4096, 1024, 64, 64, CU_TENSOR_MAP_SWIZZLE_128B);
  make_map(enc, &tmk, d_in[3], 4096, 1024, 64, 64, CU_TENSOR_MAP_SWIZZLE_128B);
  make_map(enc, &tmv, d_in[4], 4096, 1024, 64, 64, CU_TENSOR_MAP_SWIZZLE_128B);
  make_map(enc, &tmo, d_in[5], 1024, 4096, 16, 128, CU_TENSOR_MAP_SWIZZLE_32B);
  RDesc dsc;
  for (int k = 0; k < 32; k++) {
    dsc.tok[k] = mkdesc(0x400 + (k < 16 ? R_GA : R_GB) + ((k & 15) >> 2) * 4096 + (k & 3) * 256, 128, 1024, 0);
    dsc.tail_a[k] = mkdesc(0x400 + R_TAIL + k * 2048, 1024, 1024, 1);
    if (k < 16) dsc.tail_b[k] = mkdesc(0x400 + R_GA + k * 256, 128, 4096, 0);
  }
  kernel_R<<<96, 256, R_SMEM, cudaStreamPerThread>>>(tmq, tmk, tmv, tmo, tmm, x, mem0, cvec, dsc);

  CUtensorMap ho, h1, h3, h2, hm, hx, hy;
  make_map(enc, &ho, d_in[5], 1024, 4096, 64, 64, CU_TENSOR_MAP_SWIZZLE_128B);
  make_map(enc, &h1, d_in[8], F_, 1024, 64, 64, CU_TENSOR_MAP_SWIZZLE_128B);
  make_map(enc, &h3, d_in[9], F_, 1024, 64, 64, CU_TENSOR_MAP_SWIZZLE_128B);
  make_map(enc, &h2, d_in[10], 1024, F_, 64, 64, CU_TENSOR_MAP_SWIZZLE_128B);
  make_map(enc, &hm, d_in[12], 6144, 1024, 64, 64, CU_TENSOR_MAP_SWIZZLE_128B);
  make_map(enc, &hx, d_out, 1024, S_, 64, 128, CU_TENSOR_MAP_SWIZZLE_128B);
  make_map(enc, &hy, d_out, 1024, S_, 64, 64, CU_TENSOR_MAP_SWIZZLE_128B);
  HList list1, list2;
  build_lists(list1, list2);
  HWeights rw;
  for (int i = 0; i < 4; i++) rw.p[i] = (const uint8_t*)d_in[2 + i];
  cudaLaunchConfig_t cfg = {};
  cfg.gridDim = dim3(NH1); cfg.blockDim = dim3(384); cfg.dynamicSmemBytes = H_SMEM; cfg.stream = cudaStreamPerThread;
  cudaLaunchAttribute at[2];
  at[0].id = cudaLaunchAttributeProgrammaticStreamSerialization;
  at[0].val.programmaticStreamSerializationAllowed = 1;
  at[1].id = cudaLaunchAttributeClusterDimension;
  at[1].val.clusterDim.x = 2; at[1].val.clusterDim.y = 1; at[1].val.clusterDim.z = 1;
  cfg.attrs = at; cfg.numAttrs = 1;
  cudaLaunchKernelEx(&cfg, kernel_H, ho, h1, h3, h2, hm, hx, hy, x, cvec, (__nv_bfloat16*)d_out, rw, list1);
  cfg.numAttrs = 2; cfg.gridDim = dim3(NH2);
  cudaLaunchKernelEx(&cfg, kernel_H, ho, h1, h3, h2, hm, hx, hy, x, cvec, (__nv_bfloat16*)d_out, rw, list2);
}
```

```cpp
#include <cuda_runtime.h>
#include <cuda_bf16.h>
#include <cuda.h>
#include <stdint.h>
#include <type_traits>

namespace {

constexpr int S_ = 2048, D_ = 1024, NSEG = 64, F_ = 3584;

__device__ __align__(1024) uint8_t g_h[S_ * D_ * 2];
__device__ __align__(1024) uint8_t g_att[S_ * 4096 * 2];
__device__ __align__(1024) uint8_t g_act[S_ * F_ * 2];
__device__ __align__(1024) uint8_t g_w13s[28 * 16 * 32768];
__device__ __align__(1024) uint8_t g_ext[16 * 2560];
__device__ __align__(1024) uint8_t g_bext[28 * 4096];
__device__ __align__(1024) __nv_bfloat16 g_gate[2 * D_];
__device__ __align__(1024) float g_slot[4 * 3 * 8 * 4 * 32 * 4];
__device__ __align__(128) __nv_bfloat16 g_mod[6 * D_];
__device__ __align__(128) float g_modp[3 * 2 * D_];
__device__ __align__(128) uint32_t g_flags[1024];
constexpr int FL_S1 = 0, FL_S2 = 32, FL_MOD = 64, FL_HEAD = 96, FL_EXIT = 128, FL_WS = 160, FL_GO = 192, FL_HEAD2 = 224, FL_ATT = 256, FL_XT = 384, FL_OUT = 512, FL_F1 = 640, FL_STAT = 768;

__device__ __forceinline__ uint32_t smem_u32(const void* p) { return (uint32_t)__cvta_generic_to_shared(p); }
__device__ __forceinline__ uint32_t mapa(uint32_t a, uint32_t r) { uint32_t o; asm("mapa.shared::cluster.u32 %0, %1, %2;" : "=r"(o) : "r"(a), "r"(r)); return o; }
__device__ __forceinline__ uint32_t pack2(float a, float b) { uint32_t r; asm("cvt.rn.bf16x2.f32 %0, %1, %2;" : "=r"(r) : "f"(b), "f"(a)); return r; }
__device__ __forceinline__ float bf_lo(uint32_t w) { return __uint_as_float(w << 16); }
__device__ __forceinline__ float bf_hi(uint32_t w) { return __uint_as_float(w & 0xffff0000u); }
__device__ __forceinline__ float ex2(float x) { float y; asm("ex2.approx.ftz.f32 %0, %1;" : "=f"(y) : "f"(x)); return y; }
__device__ __forceinline__ float rcp(float x) { float y; asm("rcp.approx.ftz.f32 %0, %1;" : "=f"(y) : "f"(x)); return y; }
__device__ __forceinline__ uint32_t clk32() { uint64_t c; asm volatile("mov.u64 %0, %%clock64;" : "=l"(c) :: "memory"); return (uint32_t)c; }

__device__ __forceinline__ void mbar_init(uint32_t b, uint32_t n) { asm volatile("mbarrier.init.shared::cta.b64 [%0], %1;" :: "r"(b), "r"(n) : "memory"); }
__device__ __forceinline__ void mbar_arrive(uint32_t b) { asm volatile("mbarrier.arrive.shared::cta.b64 _, [%0];" :: "r"(b) : "memory"); }
__device__ __forceinline__ void mbar_expect(uint32_t b, uint32_t n) { asm volatile("mbarrier.arrive.expect_tx.shared::cta.b64 _, [%0], %1;" :: "r"(b), "r"(n) : "memory"); }
__device__ __forceinline__ uint32_t mbar_try(uint32_t b, uint32_t par) {
  uint32_t ok;
  asm volatile("{\n.reg .pred p;\nmbarrier.try_wait.parity.shared::cta.b64 p, [%1], %2;\nselp.u32 %0, 1, 0, p;\n}" : "=r"(ok) : "r"(b), "r"(par) : "memory");
  return ok;
}
__device__ __forceinline__ void mbar_wait(uint32_t b, uint32_t par) {
  asm volatile("{\n.reg .pred p;\n"
               "LOOP:\n"
               "mbarrier.try_wait.parity.shared::cta.b64 p, [%0], %1;\n"
               "@!p bra.uni LOOP;\n}" :: "r"(b), "r"(par) : "memory");
}
__device__ __forceinline__ void mbar_wait_safe(uint32_t b, uint32_t par) {
  uint32_t c = 0;
  while (!mbar_try(b, par)) { if (++c > 4000000u) __trap(); }
}
__device__ __forceinline__ bool elect_one() {
  uint32_t p;
  asm volatile("{\n.reg .pred p;\nelect.sync _|p, 0xffffffff;\nselp.u32 %0, 1, 0, p;\n}" : "=r"(p));
  return p;
}
__device__ __forceinline__ void sched_fence(uint32_t x, uint32_t y) { asm volatile("{\n.reg .pred p;\nsetp.eq.u32 p, %0, %1;\n@p trap;\n}" :: "r"(x), "r"(y) : "memory"); }
template <class T> __device__ __forceinline__ T opaque32(T x) { asm volatile("" : "+r"(x)); return x; }
template <class T> __device__ __forceinline__ T opaque64(T x) { asm volatile("" : "+l"(x)); return x; }
template <int ID, int N> __device__ __forceinline__ void bar_sync() { asm volatile("bar.sync %0, %1;" :: "n"(ID), "n"(N) : "memory"); }
template <int ID, int N> __device__ __forceinline__ void bar_arrive() { asm volatile("bar.arrive %0, %1;" :: "n"(ID), "n"(N) : "memory"); }
__device__ __forceinline__ void fence_async_smem() { asm volatile("fence.proxy.async.shared::cta;" ::: "memory"); }
__device__ __forceinline__ void fence_async_all() { asm volatile("fence.proxy.async;" ::: "memory"); }
__device__ __forceinline__ void fence_gpu() { asm volatile("fence.acq_rel.gpu;" ::: "memory"); }
__device__ __forceinline__ void red_add_u32(uint32_t* p, uint32_t v) { asm volatile("red.relaxed.gpu.global.add.u32 [%0], %1;" :: "l"(p), "r"(v) : "memory"); }
__device__ __forceinline__ uint32_t ld_acquire(const uint32_t* p) { uint32_t v; asm volatile("ld.acquire.gpu.global.u32 %0, [%1];" : "=r"(v) : "l"(p) : "memory"); return v; }
__device__ __forceinline__ uint32_t ldg16(const void* p) {
  uint16_t v; asm volatile("ld.global.nc.u16 %0, [%1];" : "=h"(v) : "l"(p)); return v;
}
#define PF1_POS 1
#define PF2_POS 1
#define ST_A 2
#define ST_B 6
#define ST_C 6
#define ST_D 6
#define TOK_E 1
#define RG_MAP 0
#define S2_LATE 0
#define S2A_POS 0
#define ALIGN1 1
#define PFP 0
#define PFQ 0
#define SENT 0
#define SENT_NS 40
#define PF5 0
#define FAST_ST 1
#define FAST_LN 1
#define S2A 1
#define EARLY_LD 1
__device__ __forceinline__ void wait_flag(const uint32_t* p, uint32_t target) {
  uint32_t c = 0;
  while (ld_acquire(p) < target) { if (++c > 20000000u) __trap(); __nanosleep(20); }
}

__device__ __forceinline__ void tma2d(uint32_t dst, const CUtensorMap* m, int c0, int c1, uint32_t bar) {
  asm volatile("cp.async.bulk.tensor.2d.shared::cluster.global.mbarrier::complete_tx::bytes [%0], [%1, {%3, %4}], [%2];"
               :: "r"(dst), "l"(m), "r"(bar), "r"(c0), "r"(c1) : "memory");
}
constexpr uint64_t L2_NORMAL = 0x1000000000000000ull, L2_FIRST = 0x12F0000000000000ull;
__device__ __forceinline__ void tma2d_p(uint32_t dst, const CUtensorMap* m, int c0, int c1, uint32_t bar, uint64_t pol) {
  asm volatile("cp.async.bulk.tensor.2d.shared::cluster.global.mbarrier::complete_tx::bytes.L2::cache_hint [%0], [%1, {%3, %4}], [%2], %5;"
               :: "r"(dst), "l"(m), "r"(bar), "r"(c0), "r"(c1), "l"(pol) : "memory");
}
__device__ __forceinline__ void bulk_g2s_p(uint32_t dst, const void* src, uint32_t bytes, uint32_t bar, uint64_t pol) {
  asm volatile("cp.async.bulk.shared::cluster.global.mbarrier::complete_tx::bytes.L2::cache_hint [%0], [%1], %2, [%3], %4;"
               :: "r"(dst), "l"(src), "r"(bytes), "r"(bar), "l"(pol) : "memory");
}
#define POL_RW L2_FIRST
__device__ __forceinline__ void tma2d_prefetch_p(const CUtensorMap* m, int c0, int c1, uint64_t pol) {
  asm volatile("cp.async.bulk.prefetch.tensor.2d.L2.global.L2::cache_hint [%0, {%1, %2}], %3;" :: "l"(m), "r"(c0), "r"(c1), "l"(pol) : "memory");
}
__device__ __forceinline__ void tma2d_prefetch(const CUtensorMap* m, int c0, int c1) {
  asm volatile("cp.async.bulk.prefetch.tensor.2d.L2.global [%0, {%1, %2}];" :: "l"(m), "r"(c0), "r"(c1) : "memory");
}
__device__ __forceinline__ void bulk_g2s(uint32_t dst, const void* src, uint32_t bytes, uint32_t bar) {
  asm volatile("cp.async.bulk.shared::cluster.global.mbarrier::complete_tx::bytes [%0], [%1], %2, [%3];"
               :: "r"(dst), "l"(src), "r"(bytes), "r"(bar) : "memory");
}
__device__ __forceinline__ void bulk_s2s(uint32_t dst, uint32_t src, uint32_t bytes, uint32_t bar) {
  asm volatile("cp.async.bulk.shared::cluster.shared::cta.mbarrier::complete_tx::bytes [%0], [%1], %2, [%3];"
               :: "r"(dst), "r"(src), "r"(bytes), "r"(bar) : "memory");
}
__device__ __forceinline__ void st_async1(uint32_t dst, uint32_t a, uint32_t bar) {
  asm volatile("st.async.shared::cluster.mbarrier::complete_tx::bytes.b32 [%0], %1, [%2];" :: "r"(dst), "r"(a), "r"(bar) : "memory");
}
__device__ __forceinline__ void st_async2(uint32_t dst, uint32_t a, uint32_t b, uint32_t bar) {
  asm volatile("st.async.shared::cluster.mbarrier::complete_tx::bytes.v2.b32 [%0], {%1, %2}, [%3];" :: "r"(dst), "r"(a), "r"(b), "r"(bar) : "memory");
}
__device__ __forceinline__ void st_async4(uint32_t dst, const uint32_t* r, uint32_t bar) {
  asm volatile("st.async.shared::cluster.mbarrier::complete_tx::bytes.v4.b32 [%0], {%1, %2, %3, %4}, [%5];"
               :: "r"(dst), "r"(r[0]), "r"(r[1]), "r"(r[2]), "r"(r[3]), "r"(bar) : "memory");
}
__device__ __forceinline__ void sts32(uint32_t a, uint32_t v) { asm volatile("st.shared.b32 [%0], %1;" :: "r"(a), "r"(v) : "memory"); }
__device__ __forceinline__ void sts64(uint32_t a, uint32_t x, uint32_t y) { asm volatile("st.shared.v2.b32 [%0], {%1, %2};" :: "r"(a), "r"(x), "r"(y) : "memory"); }
__device__ __forceinline__ void sts128(uint32_t a, uint32_t x, uint32_t y, uint32_t z, uint32_t w) {
  asm volatile("st.shared.v4.b32 [%0], {%1, %2, %3, %4};" :: "r"(a), "r"(x), "r"(y), "r"(z), "r"(w) : "memory");
}
__device__ __forceinline__ void lds128(uint32_t* r, uint32_t a) {
  asm volatile("ld.shared.v4.b32 {%0, %1, %2, %3}, [%4];" : "=r"(r[0]), "=r"(r[1]), "=r"(r[2]), "=r"(r[3]) : "r"(a) : "memory");
}
__device__ __forceinline__ uint32_t lds32(uint32_t a) { uint32_t r; asm volatile("ld.shared.b32 %0, [%1];" : "=r"(r) : "r"(a) : "memory"); return r; }
__device__ __forceinline__ void lds64(uint32_t* r, uint32_t a) {
  asm volatile("ld.shared.v2.b32 {%0, %1}, [%2];" : "=r"(r[0]), "=r"(r[1]) : "r"(a) : "memory");
}
__device__ __forceinline__ void lds128f(float* r, uint32_t a) {
  asm volatile("ld.shared.v4.f32 {%0, %1, %2, %3}, [%4];" : "=f"(r[0]), "=f"(r[1]), "=f"(r[2]), "=f"(r[3]) : "r"(a) : "memory");
}
__device__ __forceinline__ void lds64f(float* r, uint32_t a) {
  asm volatile("ld.shared.v2.f32 {%0, %1}, [%2];" : "=f"(r[0]), "=f"(r[1]) : "r"(a) : "memory");
}
__device__ __forceinline__ void ldsm4(uint32_t* r, uint32_t a) {
  asm volatile("ldmatrix.sync.aligned.m8n8.x4.shared.b16 {%0, %1, %2, %3}, [%4];" : "=r"(r[0]), "=r"(r[1]), "=r"(r[2]), "=r"(r[3]) : "r"(a) : "memory");
}
__device__ __forceinline__ void ldsm4t(uint32_t* r, uint32_t a) {
  asm volatile("ldmatrix.sync.aligned.m8n8.x4.trans.shared.b16 {%0, %1, %2, %3}, [%4];" : "=r"(r[0]), "=r"(r[1]), "=r"(r[2]), "=r"(r[3]) : "r"(a) : "memory");
}
__device__ __forceinline__ void ldsm2(uint32_t* r, uint32_t a) {
  asm volatile("ldmatrix.sync.aligned.m8n8.x2.shared.b16 {%0, %1}, [%2];" : "=r"(r[0]), "=r"(r[1]) : "r"(a) : "memory");
}
__device__ __forceinline__ void stsm4(uint32_t a, const uint32_t* r) {
  asm volatile("stmatrix.sync.aligned.m8n8.x4.shared.b16 [%0], {%1, %2, %3, %4};" :: "r"(a), "r"(r[0]), "r"(r[1]), "r"(r[2]), "r"(r[3]) : "memory");
}
__device__ __forceinline__ uint32_t hadd2(uint32_t a, uint32_t b) { uint32_t t; asm("add.rn.bf16x2 %0, %1, %2;" : "=r"(t) : "r"(a), "r"(b)); return t; }
__device__ __forceinline__ uint32_t hmax2(uint32_t a, uint32_t b) { uint32_t t; asm("max.bf16x2 %0, %1, %2;" : "=r"(t) : "r"(a), "r"(b)); return t; }
__device__ __forceinline__ void ldsm2t(uint32_t* r, uint32_t a) {
  asm volatile("ldmatrix.sync.aligned.m8n8.x2.trans.shared.b16 {%0, %1}, [%2];" : "=r"(r[0]), "=r"(r[1]) : "r"(a) : "memory");
}
__device__ __forceinline__ uint32_t movm(uint32_t x) { uint32_t y; asm volatile("movmatrix.sync.aligned.m8n8.trans.b16 %0, %1;" : "=r"(y) : "r"(x)); return y; }
__device__ __forceinline__ void hmma(float* d, uint32_t a0, uint32_t a1, uint32_t a2, uint32_t a3, uint32_t b0, uint32_t b1) {
  asm volatile("mma.sync.aligned.m16n8k16.row.col.f32.bf16.bf16.f32 {%0,%1,%2,%3}, {%4,%5,%6,%7}, {%8,%9}, {%0,%1,%2,%3};"
               : "+f"(d[0]), "+f"(d[1]), "+f"(d[2]), "+f"(d[3]) : "r"(a0), "r"(a1), "r"(a2), "r"(a3), "r"(b0), "r"(b1));
}
__device__ __forceinline__ void hmma0(float* d, uint32_t a0, uint32_t a1, uint32_t a2, uint32_t a3, uint32_t b0, uint32_t b1) {
  asm volatile("mma.sync.aligned.m16n8k16.row.col.f32.bf16.bf16.f32 {%0,%1,%2,%3}, {%4,%5,%6,%7}, {%8,%9}, {%10,%10,%10,%10};"
               : "=f"(d[0]), "=f"(d[1]), "=f"(d[2]), "=f"(d[3]) : "r"(a0), "r"(a1), "r"(a2), "r"(a3), "r"(b0), "r"(b1), "f"(0.f));
}
__device__ __forceinline__ void hmma_k8(float* d, uint32_t a0, uint32_t a1, uint32_t b0) {
  asm volatile("mma.sync.aligned.m16n8k8.row.col.f32.bf16.bf16.f32 {%0,%1,%2,%3}, {%4,%5}, {%6}, {%0,%1,%2,%3};"
               : "+f"(d[0]), "+f"(d[1]), "+f"(d[2]), "+f"(d[3]) : "r"(a0), "r"(a1), "r"(b0));
}
__host__ __device__ constexpr uint64_t mkdesc(uint32_t addr, uint32_t lbo, uint32_t sbo, uint32_t sw) {
  return (uint64_t)((addr & 0x3FFFF) >> 4) | ((uint64_t)(lbo >> 4) << 16) | ((uint64_t)(sbo >> 4) << 32) | ((uint64_t)sw << 62);
}
#define WG_FENCE() asm volatile("wgmma.fence.sync.aligned;" ::: "memory")
#define WG_COMMIT() asm volatile("wgmma.commit_group.sync.aligned;" ::: "memory")
#define WG_WAIT(n) asm volatile("wgmma.wait_group.sync.aligned " #n ";" ::: "memory")
template <int N> __device__ __forceinline__ void reg_fence(float* d) {
#pragma unroll
  for (int i = 0; i < N; i++) asm volatile("" : "+f"(d[i]) :: "memory");
}
template <int N> __device__ __forceinline__ void zero_regs(float* d) {
#pragma unroll
  for (int i = 0; i < N; i++) asm volatile("mov.b32 %0, 0;" : "=f"(d[i]));
}
template <int SD>
__device__ __forceinline__ void wg_rs32(float* d, uint32_t a0, uint32_t a1, uint32_t a2, uint32_t a3, uint64_t b) {
  asm volatile("wgmma.mma_async.sync.aligned.m64n32k16.f32.bf16.bf16 {%0,%1,%2,%3,%4,%5,%6,%7,%8,%9,%10,%11,%12,%13,%14,%15}, {%16,%17,%18,%19}, %20, %21, 1, 1, 0;"
               : "+f"(d[0]), "+f"(d[1]), "+f"(d[2]), "+f"(d[3]), "+f"(d[4]), "+f"(d[5]), "+f"(d[6]), "+f"(d[7]),
                 "+f"(d[8]), "+f"(d[9]), "+f"(d[10]), "+f"(d[11]), "+f"(d[12]), "+f"(d[13]), "+f"(d[14]), "+f"(d[15])
               : "r"(a0), "r"(a1), "r"(a2), "r"(a3), "l"(b), "n"(SD));
}
template <int SD>
__device__ __forceinline__ void wg_rs40(float* d, const uint32_t* a, uint64_t b) {
  asm volatile("wgmma.mma_async.sync.aligned.m64n40k16.f32.bf16.bf16 {%0,%1,%2,%3,%4,%5,%6,%7,%8,%9,%10,%11,%12,%13,%14,%15,%16,%17,%18,%19}, {%20,%21,%22,%23}, %24, %25, 1, 1, 0;"
               : "+f"(d[0]), "+f"(d[1]), "+f"(d[2]), "+f"(d[3]), "+f"(d[4]), "+f"(d[5]), "+f"(d[6]), "+f"(d[7]),
                 "+f"(d[8]), "+f"(d[9]), "+f"(d[10]), "+f"(d[11]), "+f"(d[12]), "+f"(d[13]), "+f"(d[14]), "+f"(d[15]),
                 "+f"(d[16]), "+f"(d[17]), "+f"(d[18]), "+f"(d[19])
               : "r"(a[0]), "r"(a[1]), "r"(a[2]), "r"(a[3]), "l"(b), "n"(SD));
}
template <int TB>
__device__ __forceinline__ void wg_ss40(float* d, uint64_t a, uint64_t b) {
  asm volatile("wgmma.mma_async.sync.aligned.m64n40k16.f32.bf16.bf16 {%0,%1,%2,%3,%4,%5,%6,%7,%8,%9,%10,%11,%12,%13,%14,%15,%16,%17,%18,%19}, %20, %21, 1, 1, 1, 1, %22;"
               : "+f"(d[0]), "+f"(d[1]), "+f"(d[2]), "+f"(d[3]), "+f"(d[4]), "+f"(d[5]), "+f"(d[6]), "+f"(d[7]),
                 "+f"(d[8]), "+f"(d[9]), "+f"(d[10]), "+f"(d[11]), "+f"(d[12]), "+f"(d[13]), "+f"(d[14]), "+f"(d[15]),
                 "+f"(d[16]), "+f"(d[17]), "+f"(d[18]), "+f"(d[19])
               : "l"(a), "l"(b), "n"(TB));
}
template <int T>
__device__ __forceinline__ void wg_ss32(float* d, uint64_t a, uint64_t b) {
  asm volatile("wgmma.mma_async.sync.aligned.m64n32k16.f32.bf16.bf16 {%0,%1,%2,%3,%4,%5,%6,%7,%8,%9,%10,%11,%12,%13,%14,%15}, %16, %17, 1, 1, 1, %18, %18;"
               : "+f"(d[0]), "+f"(d[1]), "+f"(d[2]), "+f"(d[3]), "+f"(d[4]), "+f"(d[5]), "+f"(d[6]), "+f"(d[7]),
                 "+f"(d[8]), "+f"(d[9]), "+f"(d[10]), "+f"(d[11]), "+f"(d[12]), "+f"(d[13]), "+f"(d[14]), "+f"(d[15])
               : "l"(a), "l"(b), "n"(T));
}

constexpr int R_TAIL = 0;
constexpr int R_WO = 65536;
constexpr int R_QK = R_WO + 86016;
constexpr int R_P = R_QK + 10240;
constexpr int R_GA = R_P + 6400;
constexpr int R_M2 = R_GA + 16384;
constexpr int R_M1 = R_M2 + 7168;
constexpr int R_GB = R_M1 + 9216;
constexpr int R_VT = R_GB + 16384;
constexpr int R_VM = R_VT + 8192;
constexpr int R_XS = R_VM + 2048;
constexpr int R_OX = R_XS + 1280;
constexpr int R_BAR = R_OX + 2048;
constexpr int R_TRC = R_BAR + 256;
constexpr int R_SMEM = R_TRC + 1024;
constexpr int B_MB = 0, B_XS = 32, B_VM = 40, B_VT = 48, B_TS = 56, B_FA = 64, B_FB = 72, B_TAIL = 80, B_WO = 88, B_STG = 96, B_WM = 128, B_X = 136;
constexpr int NB_A = 1, NB_B = 2, NB_X = 3, NB_C = 4, NB_D = 5, NB_E = 6, NB_F = 7, NB_G = 8, NB_H = 9, NB_S = 10, NB_E2 = 11, NB_P = 12, NB_W0 = 13;

#define POLL_DELAY 750
#define POLL_DELAY1 700
#define P1K -1
#define P2K -1
#define ZS 2
#define HPF 4
#define PF1 2
#define PF2 2
#define PF3 2
#define PF4 0
#define WO_POS 1
#define WO_LATE 1
#define S2E 0
#define RF_FIRST 0
#define BX_I 5
#define NCH 4
#define TOP2 0
#define CX_I 13
#define ATT_LATE 0
#define V_FENCE 1
#define SELF_STAS 1
#define Q_FENCE 1
#define ND_K 3
#define TRACE(i)
#define TS(i)

__device__ __forceinline__ int rot_chunk(int c, int rank) {
  int G = c;
  if (c < 9) { G = c + 3 * rank; if (G >= 9) G -= 9; }
  return G;
}
__device__ __forceinline__ int wo_tile(int i, int rank) {
  if (i < 12) return 12 * rank + i;
  const int r = i - 12 + 9 * rank;
  return r < 16 ? 48 + r : 20 + r;
}
__device__ __forceinline__ void load_chunk(uint32_t dst, int seg, int G, uint32_t bar) {
  mbar_expect(bar, 4096);
  bulk_g2s(dst, g_h + (size_t)(seg * 16 + G) * 4096, 4096, bar);
}
__device__ __forceinline__ void load_red(uint32_t* v, const float* p) {
#pragma unroll
  for (int j = 0; j < 2; j++)
    asm volatile("ld.relaxed.gpu.global.v4.u32 {%0, %1, %2, %3}, [%4];"
                 : "=r"(v[4 * j]), "=r"(v[4 * j + 1]), "=r"(v[4 * j + 2]), "=r"(v[4 * j + 3]) : "l"(p + j * 256) : "memory");
}
__device__ __forceinline__ bool red_done(const uint32_t* v) { return __all_sync(0xffffffffu, (v[3] & v[7]) == 0x42000000u); }
__device__ __forceinline__ uint32_t finish_red(uint32_t* v, const float* p) {
  uint32_t tries = 0;
  if (__builtin_expect(!red_done(v), 0)) {
    do { if (++tries > 20000000u) __trap(); load_red(v, p); } while (!red_done(v));
  }
  return tries;
}
__device__ __forceinline__ void exp10(float* sv, const uint32_t* x) {
  constexpr float SC = 0.08838834764831845f * 1.4426950408889634f;
  uint32_t m2 = hmax2(hmax2(hmax2(x[0], x[1]), hmax2(x[2], x[3])), x[4]);
  m2 = hmax2(m2, __shfl_xor_sync(0xffffffffu, m2, 1));
  m2 = hmax2(m2, __shfl_xor_sync(0xffffffffu, m2, 2));
  const float nm = -fmaxf(bf_lo(m2), bf_hi(m2)) * SC;
#pragma unroll
  for (int j = 0; j < 5; j++) { sv[2 * j] = ex2(fmaf(bf_lo(x[j]), SC, nm)); sv[2 * j + 1] = ex2(fmaf(bf_hi(x[j]), SC, nm)); }
}

__device__ __forceinline__ uint32_t arm_size(int w, bool isC) {
  return w == 0 ? (isC ? 1280 : 640) : w == 1 ? (isC ? 0 : 2048) : w == 2 ? (isC ? 0 : 8192) : (isC ? 0 : 1792);
}
__device__ __forceinline__ void forward_initial(uint32_t sb, uint32_t rank, int wg, int w, int lane) {
  const uint32_t bars = sb + R_BAR, to1 = rank == 0 ? 2u << 24 : 0u - (1u << 24), to2 = rank == 2 ? 0u - (2u << 24) : 1u << 24;
  if (wg == 1 && w > 0 && elect_one()) mbar_expect(bars + B_MB + 8 * w, w < 3 ? 3072 : SELF_STAS ? 28 * 256 : rank == 2 ? 18 * 256 : 19 * 256);
  if (wg == 1 && w == 3 && rank != 2) return;
  const float* slot = g_slot + (rank * 1024 + (wg * 4 + w) * 128 + lane) * 4 + 3 * 12288 + 4 * 32;
  uint32_t v[8], u[6];
  load_red(v, slot);
  finish_red(v, slot);
#pragma unroll
  for (int j = 0; j < 6; j++) u[j] = movm(v[4 * (j / 3) + j % 3]);
  if (wg == 0) {
    const uint32_t a = sb + lane * 16 + R_M1 + w * 768, a2 = sb + lane * 8 + R_M1 + 512 + w * 768;
    st_async4(a + to1 + 3072, u, bars + to1 + B_MB + 8); st_async2(a2 + to1 + 3072, u[4], u[5], bars + to1 + B_MB + 8);
    sts128(a, u[0], u[1], u[2], u[3]); sts64(a2, u[4], u[5]);
    __syncwarp();
    if (elect_one()) mbar_arrive(bars + B_MB);
    st_async4(a + to2 + 6144, u, bars + to2 + B_MB + 16); st_async2(a2 + to2 + 6144, u[4], u[5], bars + to2 + B_MB + 16);
  } else {
    const uint32_t a = sb + lane * 4 + R_M2 + rank * 2304 + w * 768;
    const int n = w < 3 ? 6 : 2;
#pragma unroll
    for (int j = 0; j < 6; j++) if (j < n) { st_async1(a + to1 + j * 128, u[j], bars + to1 + B_MB + 24); st_async1(a + to2 + j * 128, u[j], bars + to2 + B_MB + 24); }
    if (SELF_STAS) {
#pragma unroll
      for (int j = 0; j < 6; j++) if (j < n) st_async1(a + j * 128, u[j], bars + B_MB + 24);
    } else {
#pragma unroll
      for (int j = 0; j < 6; j++) if (j < n) sts32(a + j * 128, u[j]);
      __syncwarp();
      if (elect_one()) mbar_arrive(bars + B_MB + 24);
    }
  }
}
struct RDesc { uint64_t tok[32], tail_b[16], tail_a[32]; };

template <int WG>
__device__ __forceinline__ void r_main(const uint32_t (&W)[48][4], const RDesc& dsc, int head, uint32_t rank, int lane_, int w) {
  const uint32_t sb = (rank << 24) + 0x400, bars = sb + R_BAR;
  const uint32_t to1 = rank == 0 ? 2u << 24 : 0u - (1u << 24), to2 = rank == 2 ? 0u - (2u << 24) : 1u << 24;
  const bool isC = rank == 2;
  const int lane = opaque32(lane_), warp = WG * 4 + w;
  const int gl = rot_chunk(4 * (lane & 3) + w, rank);
  const int g0 = __shfl_sync(0xffffffffu, gl, 0), g1 = __shfl_sync(0xffffffffu, gl, 1), g2 = __shfl_sync(0xffffffffu, gl, 2);
  const uint32_t arm_bytes = arm_size(w, isC);

#define L16 opaque32(sb + opaque32(lane) * 16)
#define L8 opaque32(sb + opaque32(lane) * 8)
#define L4 opaque32(sb + opaque32(lane) * 4)
#define LV opaque32(sb + R_VT + ((opaque32(lane) >> 3) & 1) * 512 + (opaque32(lane) >> 4) * 128 + (opaque32(lane) & 7) * 16)
#define SLOT(st) opaque64(slot0 + ((st) & 3) * 12288 + ((st) & 4) * 32)
  float* const slot0 = opaque64(g_slot + (rank * 1024 + warp * 128 + lane) * 4);
  const uint32_t woa = opaque32(sb + R_WO + warp * 12288 + ((lane >> 4) * 8 + (lane & 7)) * 32 + ((((lane >> 3) ^ (lane >> 2)) & 1) << 4));
  const bool has_wo = WG == 0 || isC || w < 3;
  float acc[20];
  uint32_t pk[8] = {0u, 0u, 0u, 0u, 0u, 0u, 0u, 0u};

  auto forward = [&](auto rd, const uint32_t* v, int st, uint32_t tries) {
    constexpr int RD = decltype(rd)::value;
    uint32_t u[6];
#pragma unroll
    for (int j = 0; j < 6; j++) u[j] = movm(v[4 * (j / 3) + j % 3]);
    const bool all3 = RD == 0 || w < 3;
    if (RD == 0) {
      const uint32_t a = L16 + R_M1 + w * 768, a2 = L8 + R_M1 + 512 + w * 768;
      st_async4(a + to1 + 3072, u, bars + to1 + B_MB + 8); st_async2(a2 + to1 + 3072, u[4], u[5], bars + to1 + B_MB + 8);
      sts128(a, u[0], u[1], u[2], u[3]); sts64(a2, u[4], u[5]);
      __syncwarp();
      if (elect_one()) mbar_arrive(bars + B_MB);
      st_async4(a + to2 + 6144, u, bars + to2 + B_MB + 16); st_async2(a2 + to2 + 6144, u[4], u[5], bars + to2 + B_MB + 16);
    } else {
      const uint32_t a = L4 + R_M2 + rank * 2304 + w * 768;
#pragma unroll
      for (int j = 0; j < 6; j++) if (j < 2 || all3) st_async1(a + to1 + j * 128, u[j], bars + to1 + B_MB + 24);
#pragma unroll
      for (int j = 0; j < 6; j++) if (j < 2 || all3) st_async1(a + to2 + j * 128, u[j], bars + to2 + B_MB + 24);
      if (SELF_STAS) {
#pragma unroll
        for (int j = 0; j < 6; j++) if (j < 2 || all3) st_async1(a + j * 128, u[j], bars + B_MB + 24);
      } else {
#pragma unroll
        for (int j = 0; j < 6; j++) if (j < 2 || all3) sts32(a + j * 128, u[j]);
        __syncwarp();
        if (elect_one()) mbar_arrive(bars + B_MB + 24);
      }
    }
  };

  auto send_vt = [&]() {
    if (elect_one()) {
      const uint32_t src = sb + R_VT + warp * 1024;
      bulk_s2s(src + to1, src, 1024, bars + to1 + B_VT);
      bulk_s2s(src + to2, src, 1024, bars + to2 + B_VT);
    }
  };
  auto store_att = [&](int sg) {
    uint32_t* op = reinterpret_cast<uint32_t*>(g_att + (size_t)((sg >> 2) * 64 + head * 2 + rank) * 16384 + (2 * w * 16 + (sg & 3) * 4) * 128) + opaque32(lane);
#pragma unroll
    for (int j = 0; j < 8; j++) op[(j & 1) * 512 + (j >> 1) * 32] = pk[j];
  };

  auto token_softmax = [&](uint32_t par) {
    const int ln = opaque32(lane), kg = w - (ln >> 3);
    const uint32_t r16 = sb + R_P + w * 768 + (ln & 7) * 16;
    const uint32_t ta = r16 + (kg >= 0 ? kg * 128 : 640);
    const int dg = (ln >> 2) - 2 * (ln & 3);
    const uint32_t keep = dg > 0 ? 0xffffffffu : dg == 0 ? 0x0000ffffu : 0u;
    mbar_wait(bars + B_TS, par);
    uint32_t x[6], y[4];
    ldsm4t(x, ta); ldsm4t(y, ta + 3072); ldsm2t(x + 4, r16 + 512 + ((ln >> 3) & 1) * 3072);
#pragma unroll
    for (int j = 0; j < 5; j++) x[j] = hadd2(x[j], j < 4 ? y[j] : x[5]);
    x[0] = (x[0] & keep) | (0xff80ff80u & ~keep);
    float sv[10];
    exp10(sv, x);
    float sum = (((sv[0] + sv[1]) + (sv[2] + sv[3])) + ((sv[4] + sv[5]) + (sv[6] + sv[7]))) + (sv[8] + sv[9]);
    sum += __shfl_xor_sync(0xffffffffu, sum, 1);
    sum += __shfl_xor_sync(0xffffffffu, sum, 2);
    const float inv = rcp(sum);
#pragma unroll
    for (int j = 0; j < 5; j++) x[j] = pack2(sv[2 * j] * inv, sv[2 * j + 1] * inv);
    stsm4(r16 + (kg & 3) * 128, x);
    sts32(sb + ln * 4 + w * 768 + R_P + 512, x[4]);
    fence_async_smem();
    bar_arrive<NB_P, 256>();
  };
  auto first_wo = [&](int s) {
    if (s == 0) {
      mbar_wait_safe(bars + B_WO, 0);
      TS(10);
      if (WG == 1 && head == 0 && rank == 0 && w == 0 && elect_one()) red_add_u32(&g_flags[FL_GO], 1);
    }
  };
  auto mem_proj = [&](uint32_t par, auto mid) {
    float c[NCH][4];
    uint32_t b[3][6];
    const uint32_t ma = L16, m8 = L8;
#pragma unroll
    for (int i = 0; i < 18; i++) {
      if (i < 16) {
        if (i % 4 == 0) mbar_wait(bars + B_MB + (i / 4) * 8, par);
        if (i < 12) { lds128(b[i % 3], ma + R_M1 + i * 768); lds64(b[i % 3] + 4, m8 + R_M1 + 512 + i * 768); }
        else { ldsm4(b[i % 3], ma + R_M2 + 4096 + (i - 12) * 768); ldsm2(b[i % 3] + 4, ma + R_M2 + 4096 + 512 + (i - 12) * 768); }
      }
      mid(i);
      if (i < 16) __syncwarp();
      if (i >= 2) {
        const int j = i - 2;
#pragma unroll
        for (int q = 0; q < 3; q++) {
          const uint32_t* f = W[3 * j + q];
          if (3 * j + q < NCH) hmma0(c[3 * j + q], f[0], f[1], f[2], f[3], b[j % 3][2 * q], b[j % 3][2 * q + 1]);
          else hmma(c[(3 * j + q) % NCH], f[0], f[1], f[2], f[3], b[j % 3][2 * q], b[j % 3][2 * q + 1]);
        }
      }
    }
#pragma unroll
    for (int j = 0; j < 4; j++) acc[16 + j] = NCH == 3 ? (c[0][j] + c[1][j]) + c[2][j] : (c[0][j] + c[1][j]) + (c[2][j] + c[NCH - 1][j]);
  };

  if (WG == 0) bar_arrive<NB_G, 256>();
#pragma unroll 1
  for (int s = 0; s < NSEG - 1; s++) {
    const uint32_t par = s & 1;
    TRACE(0);
    {
      float c[NCH][4];
      uint32_t b[3][6];
      const uint32_t ma = L16, m8 = L8;
#pragma unroll
      for (int i = 0; i < 18; i++) {
        if (i < 16) {
          if (i % 4 == 0 && !(i == 4 && TOP2)) mbar_wait(bars + B_MB + (i / 4) * 8, par);
          if (i == 0 && TOP2) mbar_wait(bars + B_MB + 8, par);
          if (i % 4 == 0) TRACE(1 + i / 4);
          if (i < 12) { lds128(b[i % 3], ma + R_M1 + i * 768); lds64(b[i % 3] + 4, m8 + R_M1 + 512 + i * 768); }
          else { ldsm4(b[i % 3], ma + R_M2 + 4096 + (i - 12) * 768); ldsm2(b[i % 3] + 4, ma + R_M2 + 4096 + 512 + (i - 12) * 768); }
          if (WG == 1 && i == BX_I) {
            bar_sync<NB_G, 256>();
            if (elect_one()) load_chunk(sb + R_GB + w * 4096, s + 1, g0, bars + B_FB);
          }
          if (i == CX_I) {
            if (isC) send_vt();
            if (WG == 1 && ATT_LATE && !isC && s > 0) store_att(s - 1);
          }
          __syncwarp();
        }
        if (i >= 2) {
          const int j = i - 2;
#pragma unroll
          for (int q = 0; q < 3; q++) {
            const uint32_t* f = W[3 * j + q];
            if (3 * j + q < NCH) hmma0(c[3 * j + q], f[0], f[1], f[2], f[3], b[j % 3][2 * q], b[j % 3][2 * q + 1]);
            else hmma(c[(3 * j + q) % NCH], f[0], f[1], f[2], f[3], b[j % 3][2 * q], b[j % 3][2 * q + 1]);
          }
        }
        if (i == 14) zero_regs<16>(acc);
        if (i == 16) mbar_wait(bars + B_FA, 0);
      }
#pragma unroll
      for (int j = 0; j < 4; j++) acc[16 + j] = NCH == 3 ? (c[0][j] + c[1][j]) + c[2][j] : (c[0][j] + c[1][j]) + (c[2][j] + c[NCH - 1][j]);
    }
    TRACE(5);
    bar_sync<NB_H, 256>();
    WG_FENCE();
#pragma unroll
    for (int k = 0; k < 16; k++) wg_ss40<0>(acc, dsc.tail_a[WG * 16 + k], dsc.tail_b[k]);
    WG_COMMIT();
    uint32_t vt[4][4];
    {
      const uint32_t a = opaque32(L4 + w * 256 + (isC ? WG * 1024 + R_VM : R_QK + 4096 + WG * 5120));
      const uint32_t qa = L16 + R_QK, xa = opaque32(LV + w * 2048 + (WG == 0 ? 0 : (opaque32(lane) & 8) * 64 + R_QK + 5120 - R_VT));
      const uint32_t d = opaque32(L4 + R_XS + rank * 640 + w * 256);
      if (!WO_LATE) first_wo(s);
      mbar_wait(bars + B_FB, 0);
      if (WG == 0) mbar_wait(bars + B_VT, par);
      WG_WAIT(0);
      reg_fence<20>(acc);
      TRACE(6);
      const uint32_t p0 = pack2(acc[16], acc[17]), p1 = pack2(acc[18], acc[19]);
      sts32(a, p0); sts32(a + 128, p1);
      if (isC) {
        st_async1(a + to1, p0, bars + B_VM + to1); st_async1(a + to1 + 128, p1, bars + B_VM + to1);
        st_async1(a + to2, p0, bars + B_VM + to2); st_async1(a + to2 + 128, p1, bars + B_VM + to2);
      }
      if (WG == 0) {
        bar_arrive<NB_A, 256>();
        if (Q_FENCE && !isC) fence_async_smem();
#pragma unroll
        for (int i = 0; i < 4; i++) ldsm4(vt[i], xa + (i >> 1) * 1024 + (i & 1) * 256);
        bar_sync<NB_S, 256>();
      } else {
        bar_sync<NB_A, 256>();
        if (!isC) {
          if (w < 3) {
            uint32_t q[8], k[4][4];
            ldsm4t(q, qa + 4096); ldsm4t(k[0], xa); ldsm4t(k[1], xa + 256);
            ldsm4t(q + 4, qa + 4096 + 512); ldsm4t(k[2], xa + 512); ldsm4t(k[3], xa + 768);
            float x[4], y[4];
            hmma0(x, k[0][0], k[0][1], k[0][2], k[0][3], q[0], q[1]); hmma0(y, k[1][0], k[1][1], k[1][2], k[1][3], q[2], q[3]);
            hmma(x, k[2][0], k[2][1], k[2][2], k[2][3], q[4], q[5]); hmma(y, k[3][0], k[3][1], k[3][2], k[3][3], q[6], q[7]);
            const uint32_t s0 = pack2(x[0] + y[0], x[1] + y[1]), s1 = pack2(x[2] + y[2], x[3] + y[3]);
            st_async1(d + to1, s0, bars + B_XS + to1);
            st_async1(d + to2, s0, bars + B_XS + to2);
            if (w < 2) { st_async1(d + to1 + 128, s1, bars + B_XS + to1); st_async1(d + to2 + 128, s1, bars + B_XS + to2); sts32(d + 128, s1); }
            sts32(d, s0);
          }
        }
        bar_arrive<NB_S, 256>();
      }
    }
    if (WG == 1) {
      if (elect_one()) load_chunk(sb + R_GA + w * 4096, s + 1, g1, bars + B_FA);
      {
        if (w > 0 && elect_one()) mbar_expect(bars + B_MB + 8 * w, w < 3 ? 3072 : SELF_STAS ? 28 * 256 : isC ? 18 * 256 : 19 * 256);
      }
      fence_async_smem();
      bar_sync<NB_B, 256>();
    }
    TRACE(7);
    WG_FENCE();
#pragma unroll
    for (int k = 0; k < 16; k++) wg_rs32<1>(acc, W[k][0], W[k][1], W[k][2], W[k][3], dsc.tok[16 + k]);
    WG_COMMIT();
    uint32_t wa[3][4];
    const uint32_t oxa = L16 + R_OX;
    if (WG == 0) {
      const uint32_t vma = oxa - (R_OX - R_VM) + w * 512, oa = opaque32(L4 + w * 512 + R_OX);
      TRACE(8);
      mbar_wait(bars + B_XS, par);
      TRACE(9);
      float sv[10];
      {
        uint32_t x[10];
        ldsm4t(x, oxa - (R_OX - R_XS)); ldsm4t(x + 4, oxa - (R_OX - R_XS) + 512); ldsm2t(x + 8, oxa - (R_OX - R_XS) + 1024);
        bar_arrive<NB_B, 256>();
#pragma unroll
        for (int j = 0; j < 5; j++) x[j] = hadd2(x[j], x[j + 5]);
        exp10(sv, x);
      }
      WG_WAIT(0);
      bar_arrive<NB_X, 256>();
      mbar_wait(bars + B_VM, par);
      uint32_t vm[4];
      ldsm4(vm, vma);
      uint32_t pb[5];
#pragma unroll
      for (int j = 0; j < 5; j++) pb[j] = pack2(sv[2 * j], sv[2 * j + 1]);
      TRACE(10);
      float o0[4], o1[4], sm[4];
      const uint32_t ONE = 0x3f803f80u;
      hmma0(o0, vt[0][0], vt[0][1], vt[0][2], vt[0][3], pb[0], pb[1]);
      hmma0(o1, vt[2][0], vt[2][1], vt[2][2], vt[2][3], pb[0], pb[1]);
      hmma0(sm, ONE, ONE, ONE, ONE, pb[0], pb[1]);
      hmma(sm, ONE, ONE, ONE, ONE, pb[2], pb[3]);
      hmma(o0, vt[1][0], vt[1][1], vt[1][2], vt[1][3], pb[2], pb[3]);
      hmma(o1, vt[3][0], vt[3][1], vt[3][2], vt[3][3], pb[2], pb[3]);
      hmma_k8(sm, ONE, ONE, pb[4]);
      hmma_k8(o0, vm[0], vm[1], pb[4]);
      hmma_k8(o1, vm[2], vm[3], pb[4]);
      if (WO_LATE) first_wo(s);
#pragma unroll
      for (int i = 0; i < 3; i++) ldsm4t(wa[i], woa + i * 4096);
      __syncwarp();
      const float i0 = rcp(sm[0]), i1 = rcp(sm[1]);
      sts32(oa, pack2(o0[0] * i0, o0[1] * i1)); sts32(oa + 128, pack2(o0[2] * i0, o0[3] * i1));
      sts32(oa + 256, pack2(o1[0] * i0, o1[1] * i1)); sts32(oa + 384, pack2(o1[2] * i0, o1[3] * i1));
      TRACE(11);
      bar_sync<NB_C, 128>();
    } else {
      if (!isC) {
        constexpr uint64_t dQ = mkdesc(0x400 + R_QK, 128, 1024, 0), dK = mkdesc(0x400 + R_QK + 5120, 128, 1024, 0);
        float sc[16];
        zero_regs<16>(sc);
        WG_FENCE();
#pragma unroll
        for (int k = 0; k < 4; k++) wg_ss32<1>(sc, dK + k * 16, dQ + k * 16);
        WG_COMMIT();
        const uint32_t top = rank == 0 ? to2 : to1, e = L4 + R_P + w * 256;
        WG_WAIT(0);
        bar_sync<NB_X, 256>();
        if (elect_one()) load_chunk(sb + R_GB + w * 4096, s + 1, g2, bars + B_FB);
        reg_fence<16>(sc);
        if (w < 3) {
#pragma unroll
          for (int j = 0; j < 8; j++) {
            if ((j & 1) ? (j > 1 && (w == 0 || (w == 1 && j == 7))) : (j >= 4 || w != 1)) {
              const uint32_t t = pack2(sc[2 * j], sc[2 * j + 1]), o = (j >> 1) * 768 + (j & 1) * 128;
              st_async1(e + top + 3072 + o, t, bars + top + B_TS);
              sts32(e + o, t);
            }
          }
          __syncwarp();
          if (elect_one()) mbar_arrive(bars + B_TS);
        }
      } else {
        WG_WAIT(0);
        bar_sync<NB_X, 256>();
        if (elect_one()) load_chunk(sb + R_GB + w * 4096, s + 1, g2, bars + B_FB);
      }
      TRACE(8);
      mbar_wait(bars + B_FA, 1);
      TRACE(11);
    }
    if (has_wo) {
      float* rslot = SLOT(s);
      uint32_t ob[4][4];
      float c[3][4];
      if (WG == 1) {
        if (WO_LATE) first_wo(s);
#pragma unroll
        for (int i = 0; i < 3; i++) ldsm4t(wa[i], woa + i * 4096);
        bar_sync<NB_D, 256>();
      }
      ldsm4t(ob[0], oxa);
      __syncwarp();
#pragma unroll
      for (int k = 0; k < 8; k++) {
        uint32_t nx[3][4];
        if ((k & 1) == 0 && k < 6) { ldsm4t(ob[(k >> 1) + 1], oxa + ((k >> 1) + 1) * 512); __syncwarp(); }
#pragma unroll
        for (int i = 0; i < 3; i++) {
          const uint32_t* o = ob[k >> 1] + (k & 1) * 2;
          if (k < 7) { ldsm4t(nx[i], woa + i * 4096 + (k + 1) * 512); if (i == 2) __syncwarp(); }
          if (k == 0) hmma0(c[i], wa[i][0], wa[i][1], wa[i][2], wa[i][3], o[0], o[1]);
          else hmma(c[i], wa[i][0], wa[i][1], wa[i][2], wa[i][3], o[0], o[1]);
#pragma unroll
          for (int q = 0; q < 4; q++) if (k < 7) wa[i][q] = nx[i][q];
        }
        if (k == ND_K && WG == 0) bar_arrive<NB_D, 256>();
      }
      const float* cv = &c[0][0];
      uint32_t r[6];
#pragma unroll
      for (int j = 0; j < 6; j++) r[j] = pack2(cv[2 * j], cv[2 * j + 1]);
      asm volatile("red.relaxed.gpu.global.add.noftz.v4.bf16x2 [%0], {%1, %2, %3, %7};\n"
                   "red.relaxed.gpu.global.add.noftz.v4.bf16x2 [%0+1024], {%4, %5, %6, %7};"
                   :: "l"(rslot), "r"(r[0]), "r"(r[1]), "r"(r[2]), "r"(r[3]), "r"(r[4]), "r"(r[5]), "r"(0x3f800000) : "memory");
    } else {
      bar_arrive<NB_D, 256>();
      if ((s & 3) == 0) {
        fence_gpu();
        if (s > 0 && elect_one()) red_add_u32(&g_flags[FL_ATT + 2 * (s - 4)], 1);
      }
      if (rank == 0 || head < 16)
        reinterpret_cast<uint4*>(g_slot)[((s + ZS) & 3) * 3072 + ((s + ZS) & 4) * 8 + rank * 2048 + head * 64 + opaque32(lane)] = make_uint4(0, 0, 0, 0);
      if (HPF && head < 16 && rank == 0 && s + HPF < NSEG && elect_one())
        asm volatile("cp.async.bulk.prefetch.L2.global [%0], 4096;" :: "l"(g_h + (size_t)((s + HPF) * 16 + head) * 4096) : "memory");
    }
    const uint32_t t_red = clk32();
    uint32_t v[8];
    const float* slot = SLOT(s);
    TRACE(13);
    if (WG == 0) {
      if (!isC) {
        token_softmax(par);
      }
      if (P1K < 0) { while (clk32() - t_red < POLL_DELAY) {} load_red(v, slot); }
      bar_sync<NB_E, 256>();
    } else {
      mbar_wait(bars + B_FB, 1);
    }
    TRACE(14);
    float ao[16];
    uint32_t v2[8];
    if (WG == 1) zero_regs<16>(ao);
    WG_FENCE();
#pragma unroll
    for (int k = 0; k < 32; k++) {
      if (WG == 0 && k == P1K) { sched_fence(head, 101); load_red(v, slot); }
      if (WG == 0 && k == P2K) { sched_fence(head, 102); load_red(v2, slot); }
      if (WG == 0 && k == 16) WG_COMMIT();
      wg_rs32<1>(acc, W[16 + k][0], W[16 + k][1], W[16 + k][2], W[16 + k][3], dsc.tok[k]);
    }
    WG_COMMIT();
    TRACE(12);
    if (WG == 1) {
      if (!isC) {
        constexpr uint64_t dP = mkdesc(0x400 + R_P, 128, 768, 0);
        const uint64_t dV = mkdesc(0x400 + R_VT, 128, 512, 0) + rank * 256, dM = mkdesc(0x400 + R_VM, 0, 128, 0) + rank * 64;
        bar_sync<NB_P, 256>();
        WG_FENCE();
        wg_ss32<0>(ao, dV, dP); wg_ss32<0>(ao, dV + 16, dP + 16); wg_ss32<0>(ao, dM, dP + 32);
        WG_COMMIT();
      }
      bar_arrive<NB_E, 256>();
      if (elect_one()) mbar_expect(bars + B_XS + 8 * w, arm_bytes);
      while (clk32() - t_red < POLL_DELAY1) {}
      load_red(v, slot);
      bar_arrive<NB_W0, 128>();
    } else {
      WG_WAIT(1);
      bar_arrive<NB_F, 256>();
      sched_fence(head, 100);
      v[3] = opaque32(v[3]);
      uint32_t tries = 0;
      if (P2K < 0) tries = finish_red(v, slot);
      else if (__builtin_expect(!red_done(v), 0)) {
#pragma unroll
        for (int j = 0; j < 8; j++) v[j] = v2[j];
        tries = 1;
        while (!red_done(v)) { if (++tries > 20000000u) __trap(); load_red(v, slot); }
      }
      forward(std::integral_constant<int, 0>(), v, s, tries);
      if (P2K >= 0) asm volatile("" :: "r"(v2[0]), "r"(v2[1]), "r"(v2[2]), "r"(v2[3]), "r"(v2[4]), "r"(v2[5]), "r"(v2[6]), "r"(v2[7]));
      TRACE(16);
    }
    WG_WAIT(0);
    reg_fence<16>(acc);
    if (WG == 0) bar_arrive<NB_G, 256>();
    TRACE(15);
    {
      uint32_t pq[8];
#pragma unroll
      for (int j = 0; j < 8; j++) pq[j] = pack2(acc[2 * j], acc[2 * j + 1]);
      if (WG == 1) {
        reg_fence<16>(ao);
#pragma unroll
        for (int j = 0; j < 8; j++) pk[j] = pack2(ao[2 * j], ao[2 * j + 1]);
      }
      if (!isC) {
        const uint32_t q = L4 + w * 256 + R_QK + WG * 5120;
#pragma unroll
        for (int j = 0; j < 8; j++) sts32(q + (j >> 1) * 1024 + (j & 1) * 128, pq[j]);
        if (WG == 1 && !ATT_LATE) store_att(s);
      } else {
        const uint32_t a = LV + warp * 1024;
        stsm4(a, pq); stsm4(a + 256, pq + 4);
      }
    }
    TRACE(17);
    if (WG == 1) {
      auto refill = [&]() {
        bar_sync<NB_F, 256>();
        if (s < NSEG - 2 && elect_one()) load_chunk(sb + R_GA + w * 4096, s + 2, 12 + w, bars + B_FA);
      };
      if (RF_FIRST) refill();
      if (has_wo) { v[3] = opaque32(v[3]); const uint32_t tries = finish_red(v, slot); forward(std::integral_constant<int, 1>(), v, s, tries); }
      if (!RF_FIRST) refill();
      TRACE(16);
    }
    if (isC && V_FENCE) { fence_async_smem(); __syncwarp(); }
    TRACE(18);
  }
  {
    constexpr uint32_t par = (NSEG - 1) & 1;
    if (WG == 1) {
      bar_sync<NB_G, 256>();
      if (ATT_LATE && !isC) store_att(NSEG - 2);
    }
    const bool proj = WG == 1 || isC;
    if (proj) mem_proj(par, [&](int i) { if (i == CX_I && isC) send_vt(); if (i == 15) zero_regs<16>(acc); });
    else fence_async_smem();
    bar_sync<NB_H, 256>();
    if (proj) {
      WG_FENCE();
#pragma unroll
      for (int k = 0; k < 16; k++) wg_ss40<0>(acc, dsc.tail_a[WG * 16 + k], dsc.tail_b[k]);
      WG_COMMIT();
      const uint32_t a = opaque32(L4 + w * 256 + (isC ? WG * 1024 + R_VM : R_QK + 4096 + WG * 5120));
      WG_WAIT(0);
      reg_fence<20>(acc);
      const uint32_t p0 = pack2(acc[16], acc[17]), p1 = pack2(acc[18], acc[19]);
      if (isC) {
        st_async1(a + to1, p0, bars + B_VM + to1); st_async1(a + to1 + 128, p1, bars + B_VM + to1);
        st_async1(a + to2, p0, bars + B_VM + to2); st_async1(a + to2 + 128, p1, bars + B_VM + to2);
      } else { sts32(a, p0); sts32(a + 128, p1); }
    }
    if (!isC) {
      if (WG == 1) {
        fence_async_smem();
        bar_sync<NB_C, 128>();
        constexpr uint64_t dQ = mkdesc(0x400 + R_QK, 128, 1024, 0), dK = mkdesc(0x400 + R_QK + 5120, 128, 1024, 0);
        float sc[16];
        zero_regs<16>(sc);
        WG_FENCE();
#pragma unroll
        for (int k = 0; k < 4; k++) wg_ss32<1>(sc, dK + k * 16, dQ + k * 16);
        WG_COMMIT();
        const uint32_t top = rank == 0 ? to2 : to1, e = L4 + R_P + w * 256;
        WG_WAIT(0);
        reg_fence<16>(sc);
        if (w < 3) {
#pragma unroll
          for (int j = 0; j < 8; j++) {
            if ((j & 1) ? (j > 1 && (w == 0 || (w == 1 && j == 7))) : (j >= 4 || w != 1)) {
              const uint32_t t = pack2(sc[2 * j], sc[2 * j + 1]), o = (j >> 1) * 768 + (j & 1) * 128;
              st_async1(e + top + 3072 + o, t, bars + top + B_TS);
              sts32(e + o, t);
            }
          }
          __syncwarp();
          if (elect_one()) mbar_arrive(bars + B_TS);
        }
        constexpr uint64_t dP = mkdesc(0x400 + R_P, 128, 768, 0);
        const uint64_t dV = mkdesc(0x400 + R_VT, 128, 512, 0) + rank * 256, dM = mkdesc(0x400 + R_VM, 0, 128, 0) + rank * 64;
        float ao[16];
        zero_regs<16>(ao);
        mbar_wait(bars + B_VT, par);
        mbar_wait(bars + B_VM, par);
        bar_sync<NB_P, 256>();
        WG_FENCE();
        wg_ss32<0>(ao, dV, dP); wg_ss32<0>(ao, dV + 16, dP + 16); wg_ss32<0>(ao, dM, dP + 32);
        WG_COMMIT();
        WG_WAIT(0);
        reg_fence<16>(ao);
#pragma unroll
        for (int j = 0; j < 8; j++) pk[j] = pack2(ao[2 * j], ao[2 * j + 1]);
        store_att(NSEG - 1);
      } else {
        token_softmax(par);
      }
    }
  }
#undef L16
#undef L8
#undef L4
#undef SLOT
#undef LV
}

__global__ void __cluster_dims__(3, 1, 1) __launch_bounds__(256, 1)
kernel_R(const __grid_constant__ CUtensorMap tmq, const __grid_constant__ CUtensorMap tmk, const __grid_constant__ CUtensorMap tmv,
         const __grid_constant__ CUtensorMap tmo, const __grid_constant__ CUtensorMap tmm, const __nv_bfloat16* __restrict__ x,
         const __nv_bfloat16* __restrict__ mem0, const __nv_bfloat16* __restrict__ cvec, const __nv_bfloat16* __restrict__ wo,
         const __grid_constant__ RDesc dsc) {
  extern __shared__ __align__(1024) uint8_t smem[];
  const uint32_t sb = smem_u32(smem);
  uint32_t rank; asm("mov.u32 %0, %%cluster_ctarank;" : "=r"(rank));
  rank = __shfl_sync(0xffffffffu, rank, 0);
  const int cta = blockIdx.x, head = __shfl_sync(0xffffffffu, cta / 3, 0);
  const int tid = threadIdx.x, lane = tid & 31;
  const int warp = __shfl_sync(0xffffffffu, tid >> 5, 0);
  const int wg = warp >> 2, w = warp & 3;
  const uint32_t bars = sb + R_BAR;
  const CUtensorMap* tmw = rank == 2 ? &tmv : (wg == 0 ? &tmq : &tmk);
  const int fcol = head * 128 + (rank == 2 ? wg * 64 : (int)rank * 64);

  asm volatile("griddepcontrol.launch_dependents;");
  uint32_t W[48][4];
  {
    const int nwm = rank == 0 ? 6 : 5, wm0 = rank == 0 ? 0 : 5 * rank + 1, nrg = RG_MAP ? (cta < 4 ? 1 : cta < 72 ? 3 : 2) : cta < 64 ? 3 : 2;
    constexpr int RGS = RG_MAP ? 92 : 96;
    uint32_t cv[2] = {0u, 0u}, mv[6] = {0u, 0u, 0u, 0u, 0u, 0u};
    const bool has_mem = cta >= 72 && tid < 128 && (tid & 32);
    if (EARLY_LD) {
      cv[0] = ldg16(cvec + wm0 * 64 + tid);
      if (tid + 256 < nwm * 64) cv[1] = ldg16(cvec + wm0 * 64 + 256 + tid);
      if (has_mem) {
        const __nv_bfloat16* mp = mem0 + 2 * (lane & 3) * D_ + (lane >> 2);
#pragma unroll
        for (int q = 0; q < 3; q++) {
          const int n = 3 * (tid >> 6) + q, col = wo_tile(3 * (cta & 7) + (n >> 1), (cta - 72) >> 3) * 16 + 8 * (n & 1);
          mv[2 * q] = ldg16(mp + col); mv[2 * q + 1] = ldg16(mp + col + D_);
        }
      }
    }
    if (sb != (rank << 24) + 0x400) __trap();
    if (tid == 0) {
      sts64(bars + 248, rank, head);
      mbar_init(bars + B_MB, 4); mbar_init(bars + B_MB + 8, 1); mbar_init(bars + B_MB + 16, 1); mbar_init(bars + B_MB + 24, SELF_STAS ? 1 : rank == 2 ? 5 : 4);
      for (int i = B_XS; i <= B_X; i += 8) mbar_init(bars + i, i == B_FA || i == B_FB || (i == B_TS && rank < 2) ? 4 : 1);
      asm volatile("fence.mbarrier_init.release.cluster;" ::: "memory");
      fence_async_smem();
    }
    __syncthreads();
    asm volatile("barrier.cluster.arrive.relaxed.aligned;" ::: "memory");
    TS(0);
    auto first_wave = [&](int c0, int c1) {
#pragma unroll 1
      for (int p = c0 + w; p < c1; p += 4) {
        const int c = ALIGN1 == 1 && rank == 0 ? (p < 3 ? p + 3 : p - 3) : ALIGN1 == 2 && rank == 1 ? (p < 3 ? p + 3 : p - 3) : p;
        tma2d_p(sb + R_WO + wg * 49152 + c * 8192, tmw, fcol, rot_chunk(c, rank) * 64, bars + B_STG + wg * 16, POL_RW);
        if (PFP && (rank == 0 ? c < 3 : rank == 1 && c >= 3) && c % 3 < PFP) tma2d_prefetch_p(tmw, fcol ^ 64, rot_chunk(c, rank) * 64, POL_RW);
      }
    };
    if (elect_one()) {
      if (warp == 0) { mbar_expect(bars + B_WM, nwm * 8192); mbar_expect(bars + B_X, nrg * 16384); }
      if (warp < nwm) tma2d_p(sb + R_GA + warp * 8192, &tmm, head * 64, (wm0 + warp) * 64, bars + B_WM, POL_RW);
#pragma unroll 1
      for (int r = 0; r < nrg; r++) bulk_g2s(sb + R_TAIL + (r * 8 + warp) * 2064, x + (size_t)((cta + RGS * r) * 8 + warp) * D_, 2048, bars + B_X);
      if (w == 0) mbar_expect(bars + B_STG + wg * 16, 49152);
      first_wave(0, ST_A);
    }
    float* scr = reinterpret_cast<float*>(smem + R_VT);
    if (EARLY_LD) {
#pragma unroll
      for (int i = 0; i < 2; i++) {
        const float c = bf_lo(cv[i]);
        if (i == 0 || tid < 128) scr[tid + 256 * i] = __bfloat162float(__float2bfloat16(c / (1.f + __expf(-c))));
      }
    } else {
#pragma unroll 1
    for (int i = tid; i < nwm * 64; i += 256) {
      const float c = __bfloat162float(cvec[wm0 * 64 + i]);
      scr[i] = __bfloat162float(__float2bfloat16(c / (1.f + __expf(-c))));
    }
    }
    if (tid < 128) {
      uint32_t e[4] = {0u, 0u, 0u, 0u};
      if (EARLY_LD) {
        if (has_mem) { e[0] = mv[0] | mv[1] << 16; e[1] = mv[2] | mv[3] << 16; e[2] = mv[4] | mv[5] << 16; e[3] = 0x42000000u; }
      } else if (cta >= 72 && (tid & 32)) {
        const uint16_t* mp = reinterpret_cast<const uint16_t*>(mem0) + 2 * (lane & 3) * D_ + (lane >> 2);
#pragma unroll
        for (int q = 0; q < 3; q++) {
          const int n = 3 * (tid >> 6) + q, col = wo_tile(3 * (cta & 7) + (n >> 1), (cta - 72) >> 3) * 16 + 8 * (n & 1);
          e[q] = mp[col] | (uint32_t)mp[col + D_] << 16;
        }
        e[3] = 0x42000000u;
      }
      reinterpret_cast<uint4*>(g_slot)[cta * 128 + tid] = make_uint4(e[0], e[1], e[2], e[3]);
    }
    __syncthreads();
    TS(1);
    mbar_wait_safe(bars + B_WM, 0);
    if (ST_B > ST_A && elect_one()) first_wave(ST_A, ST_B);
    {
      float a[8];
#pragma unroll
      for (int j = 0; j < 8; j++) a[j] = 0.f;
#pragma unroll 2
      for (int i = 0; i < 2 * nwm; i++) {
        uint32_t u[4];
        lds128(u, sb + R_GA + i * 4096 + tid * 16);
        const float sc = scr[i * 32 + (tid >> 3)];
#pragma unroll
        for (int j = 0; j < 4; j++) { a[2 * j] += sc * bf_lo(u[j]); a[2 * j + 1] += sc * bf_hi(u[j]); }
      }
#pragma unroll
      for (int j = 0; j < 8; j++) { a[j] += __shfl_xor_sync(0xffffffffu, a[j], 8); a[j] += __shfl_xor_sync(0xffffffffu, a[j], 16); }
      if (lane < 8) {
        sts128(sb + R_VT + 1536 + warp * 256 + lane * 32, __float_as_uint(a[0]), __float_as_uint(a[1]), __float_as_uint(a[2]), __float_as_uint(a[3]));
        sts128(sb + R_VT + 1552 + warp * 256 + lane * 32, __float_as_uint(a[4]), __float_as_uint(a[5]), __float_as_uint(a[6]), __float_as_uint(a[7]));
      }
    }
    __syncthreads();
    TS(2);
    asm volatile("barrier.cluster.wait.aligned;\nbarrier.cluster.arrive.relaxed.aligned;" ::: "memory");
    if (warp == 7) {
      float t0 = 0.f, t1 = 0.f;
#pragma unroll
      for (int i = 0; i < 8; i++) { float t[2]; lds64f(t, sb + R_VT + 1536 + i * 256 + lane * 8); t0 += t[0]; t1 += t[1]; }
      if (SENT) {
        const uint32_t u0 = __float_as_uint(t0), u1 = __float_as_uint(t1);
        asm volatile("st.relaxed.gpu.global.v2.b32 [%0], {%1, %2};" ::"l"(g_modp + rank * 2048 + head * 64 + 2 * lane), "r"(u0 ? u0 : 0x80000000u), "r"(u1 ? u1 : 0x80000000u) : "memory");
      } else {
        reinterpret_cast<float2*>(g_modp + rank * 2048 + head * 64)[lane] = make_float2(t0, t1);
        fence_gpu();
        __syncwarp();
        if (lane == 0) red_add_u32(&g_flags[FL_S1], 1);
        __syncwarp();
      }
    }
    mbar_wait_safe(bars + B_X, 0);
    if (ST_C > ST_B && elect_one()) first_wave(ST_B, ST_C);
    {
      float f[3][32], t[3], mean[3];
#pragma unroll
      for (int r = 0; r < 3; r++)
#pragma unroll
        for (int i = 0; i < 4; i++) {
          uint32_t u[4];
          lds128(u, sb + R_TAIL + (r * 8 + warp) * 2064 + i * 512 + lane * 16);
#pragma unroll
          for (int j = 0; j < 4; j++) { f[r][8 * i + 2 * j] = bf_lo(u[j]); f[r][8 * i + 2 * j + 1] = bf_hi(u[j]); }
        }
#pragma unroll
      for (int r = 0; r < 3; r++) {
        float p[4] = {f[r][0], f[r][1], f[r][2], f[r][3]};
#pragma unroll
        for (int i = 4; i < 32; i++) p[i & 3] += f[r][i];
        t[r] = (p[0] + p[1]) + (p[2] + p[3]);
      }
#pragma unroll
      for (int o = 1; o < 32; o <<= 1)
#pragma unroll
        for (int r = 0; r < 3; r++) t[r] += __shfl_xor_sync(0xffffffffu, t[r], o);
#pragma unroll
      for (int r = 0; r < 3; r++) {
        mean[r] = t[r] * (1.f / D_);
        float p[4] = {0.f, 0.f, 0.f, 0.f};
#pragma unroll
        for (int i = 0; i < 32; i++) p[i & 3] = fmaf(f[r][i] - mean[r], f[r][i] - mean[r], p[i & 3]);
        t[r] = (p[0] + p[1]) + (p[2] + p[3]);
      }
#pragma unroll
      for (int o = 1; o < 32; o <<= 1)
#pragma unroll
        for (int r = 0; r < 3; r++) t[r] += __shfl_xor_sync(0xffffffffu, t[r], o);
#pragma unroll
      for (int r = 0; r < 3; r++) {
        const float rstd = rsqrtf(t[r] * (1.f / D_) + 1e-5f);
        if (lane == 0) sts64(sb + R_VT + 3584 + (r * 8 + warp) * 8, __float_as_uint(rstd), __float_as_uint(-mean[r] * rstd));
      }
    }
    TS(3);
    if (ST_D > ST_C && elect_one()) first_wave(ST_C, ST_D);
    if (PF1_POS == 0 && w < PF1 && elect_one()) tma2d_prefetch_p(tmw, fcol, rot_chunk(6 + w, rank) * 64, POL_RW);
    if (!SENT && tid == 0) wait_flag(&g_flags[FL_S1], 96);
    __syncthreads();
    if (ST_D < 6 && elect_one()) first_wave(ST_D, 6);
    if (PF1_POS == 1 && !SENT && (PFP && rank < 2 ? w >= PFP && w < 3 && PFQ : w < PF1) && elect_one()) tma2d_prefetch_p(tmw, fcol, rot_chunk(6 + w, rank) * 64, POL_RW);
    TS(4);
    {
      const int id = (lane >> 4) * 128 + warp * 16 + (lane & 15);
      float4 p[6];
      if (SENT) {
        uint32_t u[6][4];
        auto ld = [&](int i) {
          asm volatile("ld.relaxed.gpu.global.v4.u32 {%0, %1, %2, %3}, [%4];"
                       : "=r"(u[i][0]), "=r"(u[i][1]), "=r"(u[i][2]), "=r"(u[i][3]) : "l"(g_modp + (i >> 1) * 2048 + 8 * id + 4 * (i & 1)) : "memory");
        };
#pragma unroll
        for (int i = 0; i < 6; i++) ld(i);
        for (uint32_t tries = 0;; tries++) {
          bool all = true;
#pragma unroll
          for (int i = 0; i < 6; i++)
            if (!(u[i][0] && u[i][1] && u[i][2] && u[i][3])) { all = false; ld(i); }
          if (all) break;
          if (tries > 20000000u) __trap();
          if (SENT_NS) __nanosleep(SENT_NS);
        }
        __syncwarp();
#pragma unroll
        for (int i = 0; i < 6; i++) p[i] = make_float4(__uint_as_float(u[i][0]), __uint_as_float(u[i][1]), __uint_as_float(u[i][2]), __uint_as_float(u[i][3]));
        if (w < PF1 && elect_one()) tma2d_prefetch_p(tmw, fcol, rot_chunk(6 + w, rank) * 64, POL_RW);
      } else {
#pragma unroll
        for (int i = 0; i < 6; i++) p[i] = __ldcg(reinterpret_cast<const float4*>(g_modp + (i >> 1) * 2048) + 2 * id + (i & 1));
      }
      if (PF2_POS == 0 && w < PF2 && elect_one()) tma2d_prefetch_p(tmw, fcol, (9 + w) * 64, POL_RW);
      sts128(sb + R_VT + 5120 + id * 16, pack2(p[0].x + p[2].x + p[4].x, p[0].y + p[2].y + p[4].y), pack2(p[0].z + p[2].z + p[4].z, p[0].w + p[2].w + p[4].w),
             pack2(p[1].x + p[3].x + p[5].x, p[1].y + p[3].y + p[5].y), pack2(p[1].z + p[3].z + p[5].z, p[1].w + p[3].w + p[5].w));
      __syncwarp();
      if (PF1_POS == 2 && w < PF1 && elect_one()) tma2d_prefetch_p(tmw, fcol, rot_chunk(6 + w, rank) * 64, POL_RW);
      if (PF2_POS == 1 && w < PF2 && elect_one()) tma2d_prefetch_p(tmw, fcol, (9 + w) * 64, POL_RW);
      float sa[4][8], sc[4][8];
#pragma unroll
      for (int j = 0; j < 4; j++) {
        const int c = 16 * warp + (lane >> 3) + 4 * j;
        uint32_t a[4], b[4];
        lds128(a, sb + R_VT + 5120 + c * 16); lds128(b, sb + R_VT + 7168 + c * 16);
#pragma unroll
        for (int q = 0; q < 4; q++) { sa[j][2 * q] = bf_lo(a[q]); sa[j][2 * q + 1] = bf_hi(a[q]); sc[j][2 * q] = 1.f + bf_lo(b[q]); sc[j][2 * q + 1] = 1.f + bf_hi(b[q]); }
      }
#pragma unroll
      for (int r = 0; r < 3; r++) {
        if (r < nrg) {
          const int rg = cta + RGS * r;
          float t[2];
          lds64f(t, sb + R_VT + 3584 + (r * 8 + (lane & 7)) * 8);
#pragma unroll
          for (int j = 0; j < 4; j++) {
            const int c = 16 * warp + (lane >> 3) + 4 * j;
            uint32_t u[4], o[4];
            lds128(u, sb + R_TAIL + (r * 8 + (lane & 7)) * 2064 + c * 16);
#pragma unroll
            for (int q = 0; q < 4; q++)
              o[q] = pack2(fmaf(fmaf(bf_lo(u[q]), t[0], t[1]), sc[j][2 * q], sa[j][2 * q]), fmaf(fmaf(bf_hi(u[q]), t[0], t[1]), sc[j][2 * q + 1], sa[j][2 * q + 1]));
            *reinterpret_cast<uint4*>(g_h + (size_t)(rg >> 2) * 65536 + (lane & 7) * 16 + (c & 7) * 128 +
                                      (c < 96 ? (c >> 3) * 4096 + (rg & 3) * 1024 : 49152 + (rg & 3) * 4096 + ((c >> 3) - 12) * 1024)) =
                make_uint4(o[0], o[1], o[2], o[3]);
          }
        }
        if (S2A && S2A_POS == 0 && r == 0 && cta < 4) {
          __syncthreads();
          if (warp == 3 && lane == 0) { fence_gpu(); red_add_u32(&g_flags[FL_S1 + 16], 1); if (RG_MAP) red_add_u32(&g_flags[FL_S2], 1); }
          __syncwarp();
        }
      }
    }
    TS(5);
    __syncthreads();
    TS(6);
    if (w < PF3 && elect_one()) tma2d_p(sb + R_TAIL + warp * 8192, tmw, fcol, 768 + w * 64, bars + B_TAIL, POL_RW);
    {
      const bool pa = S2A && S2A_POS == 1 && cta < 4, pb = RG_MAP && cta < 4 ? S2A_POS == 1 : !S2_LATE;
      if (warp == 3 && lane == 0 && (pa || pb)) { fence_gpu(); if (pa) red_add_u32(&g_flags[FL_S1 + 16], 1); if (pb) red_add_u32(&g_flags[FL_S2], 1); }
    }
    __syncwarp();
    asm volatile("barrier.cluster.wait.aligned;" ::: "memory");
    if (!SENT) forward_initial(sb, rank, wg, w, lane);
    if (TOK_E && warp == 0) {
      if (lane == 0) wait_flag(&g_flags[FL_S1 + 16], 4);
      __syncwarp();
      asm volatile("fence.proxy.async.global;" ::: "memory");
      if (elect_one()) {
        mbar_expect(bars + B_X, 8 * 4096);
#pragma unroll 1
        for (int i = 0; i < 8; i++) bulk_g2s(sb + (i < 4 ? R_GB : R_GA) + (i & 3) * 4096, g_h + (size_t)rot_chunk(i, rank) * 4096, 4096, bars + B_X);
      }
      __syncwarp();
    }

    const uint32_t a0 = opaque32(sb + R_WO + wg * 49152 + ((lane >> 4) * 8 + (lane & 7)) * 128 + (((2 * w + ((lane >> 3) & 1)) ^ (lane & 7)) << 4));
    mbar_wait_safe(bars + B_STG + wg * 16, 0);
    TS(7);
#pragma unroll
    for (int i = 0; i < 24; i++) ldsm4t(W[i], a0 + i * 2048);
    auto second_wave = [&]() {
      if (w == 0) mbar_expect(bars + B_STG + wg * 16 + 8, 49152);
#pragma unroll 1
      for (int c = w; c < 6; c += 4) tma2d_p(sb + R_WO + wg * 49152 + c * 8192, tmw, fcol, rot_chunk(6 + c, rank) * 64, bars + B_STG + wg * 16 + 8, POL_RW);
      if (warp == 0) mbar_expect(bars + B_TAIL, 65536);
      if (w >= PF3) tma2d_p(sb + R_TAIL + warp * 8192, tmw, fcol, 768 + w * 64, bars + B_TAIL, POL_RW);
#pragma unroll 1
      for (int i = warp; i < PF4; i += 8) tma2d_prefetch(&tmo, 16 * wo_tile(i, rank), head * 128);
    };
    if (S2E) { __syncthreads(); if (elect_one()) second_wave(); }
    if (!TOK_E && tid == 0) { if (S2A) wait_flag(&g_flags[FL_S1 + 16], 4); else wait_flag(&g_flags[FL_S2], 96); }
    __syncthreads();
    asm volatile("fence.proxy.async.global;" ::: "memory");
    if (elect_one()) {
      if (!TOK_E) {
        if (warp == 0) mbar_expect(bars + B_X, 8 * 4096);
        bulk_g2s(sb + (wg == 0 ? R_GB : R_GA) + w * 4096, g_h + (size_t)rot_chunk(warp, rank) * 4096, 4096, bars + B_X);
      }
      if (!S2E) second_wave();
    }
    if (S2_LATE == 1 && (!RG_MAP || cta >= 4) && warp == 3 && lane == 0) { fence_gpu(); red_add_u32(&g_flags[FL_S2], 1); }
    __syncwarp();
    TS(8);
    float acc[20];
    mbar_wait_safe(bars + B_X, 1);
    WG_FENCE();
    wg_rs40<0>(acc, W[0], dsc.tok[16]);
#pragma unroll
    for (int k = 1; k < 24; k++) wg_rs40<1>(acc, W[k], dsc.tok[k < 16 ? 16 + k : k - 16]);
    WG_COMMIT();
    WG_WAIT(0);
    reg_fence<20>(acc);
    if (SENT && tid == 0) wait_flag(&g_flags[FL_S2], 96);
    __syncthreads();
    if (elect_one()) {
      if (warp == 0) mbar_expect(bars + B_X, 4 * 4096);
      if (wg == 0) bulk_g2s(sb + R_GB + w * 4096, g_h + (size_t)rot_chunk(8 + w, rank) * 4096, 4096, bars + B_X);
    }
    if (SENT) forward_initial(sb, rank, wg, w, lane);
    if (S2_LATE == 2 && (!RG_MAP || cta >= 4) && warp == 3 && lane == 0) { fence_gpu(); red_add_u32(&g_flags[FL_S2], 1); }
    __syncwarp();
    auto prefetch_wo = [&]() {
#pragma unroll
      for (int j = 0; j < 3; j++) {
        const int line = (int)rank * 683 + tid + 256 * j;
        if (tid + 256 * j < 683 && line < 2048) asm volatile("prefetch.global.L2 [%0];" ::"l"(wo + (size_t)head * 131072 + line * 64));
      }
    };
    if (PF5 == 1) prefetch_wo();
    mbar_wait_safe(bars + B_STG + wg * 16 + 8, 0);
    if (PF5 == 2) prefetch_wo();
    TS(9);
#pragma unroll
    for (int i = 0; i < 24; i++) ldsm4t(W[24 + i], a0 + i * 2048);
    __syncthreads();
    asm volatile("barrier.cluster.arrive.relaxed.aligned;" ::: "memory");
    auto load_wo = [&]() {
      const int n = rank == 2 ? 22 : 21;
      if (warp == 0) mbar_expect(bars + B_WO, n * 4096);
#pragma unroll 1
      for (int i = warp; i < n; i += 8) tma2d(sb + R_WO + i * 4096, &tmo, 16 * wo_tile(i, rank), head * 128, bars + B_WO);
    };
    if (PF5 == 3) prefetch_wo();
    if (WO_POS == 0 && elect_one()) load_wo();
    sts32(sb + R_P + warp * 768 + 640 + lane * 4, wg == 0 ? 0u : 0xff80ff80u);
    WG_FENCE();
#pragma unroll
    for (int k = 24; k < 32; k++) wg_rs40<1>(acc, W[k], dsc.tok[k - 16]);
    WG_COMMIT();
    mbar_wait_safe(bars + B_X, 0);
    WG_FENCE();
#pragma unroll
    for (int k = 32; k < 48; k++) wg_rs40<1>(acc, W[k], dsc.tok[k - 16]);
    WG_COMMIT();
    WG_WAIT(1);
    __syncthreads();
    if (elect_one()) {
      if (warp == 0) mbar_expect(bars + B_X, 4 * 4096);
      if (wg == 0) bulk_g2s(sb + R_GA + w * 4096, g_h + (size_t)(12 + w) * 4096, 4096, bars + B_X);
    }
    if (WO_POS == 1) { __syncthreads(); if (elect_one()) load_wo(); }
    if (S2A && !SENT && tid == 0) wait_flag(&g_flags[FL_S2], 96);
    mbar_wait_safe(bars + B_TAIL, 0);
    mbar_wait_safe(bars + B_X, 1);
    WG_FENCE();
#pragma unroll
    for (int k = 0; k < 16; k++) wg_ss40<0>(acc, dsc.tail_a[wg * 16 + k], dsc.tail_b[k]);
    WG_COMMIT();
    WG_WAIT(0);
    reg_fence<20>(acc);
    {
      uint32_t pq[8];
#pragma unroll
      for (int j = 0; j < 8; j++) pq[j] = pack2(acc[2 * j], acc[2 * j + 1]);
      if (rank != 2) {
        const uint32_t q = sb + lane * 4 + w * 256 + R_QK + wg * 5120;
#pragma unroll
        for (int j = 0; j < 8; j++) sts32(q + (j >> 1) * 1024 + (j & 1) * 128, pq[j]);
      } else {
        const uint32_t a = sb + R_VT + ((lane >> 3) & 1) * 512 + (lane >> 4) * 128 + (lane & 7) * 16 + warp * 1024;
        stsm4(a, pq); stsm4(a + 256, pq + 4);
        fence_async_smem();
      }
    }
    __syncthreads();
    if (S2A) asm volatile("fence.proxy.async.global;" ::: "memory");
    if (wg == 1 && elect_one()) {
      load_chunk(sb + R_GA + w * 4096, 1, 12 + w, bars + B_FA);
      mbar_expect(bars + B_XS + 8 * w, arm_size(w, rank == 2));
    }
    asm volatile("barrier.cluster.wait.aligned;" ::: "memory");
  }
  uint32_t rh[2];
  lds64(rh, bars + 248);
  rh[0] = __shfl_sync(0xffffffffu, rh[0], 0); rh[1] = __shfl_sync(0xffffffffu, rh[1], 0);
    if (wg == 0) r_main<0>(W, dsc, rh[1], rh[0], lane, w);
  else r_main<1>(W, dsc, rh[1], rh[0], lane, w);
  __syncthreads();
  if (rank < 2 && threadIdx.x == 0) { fence_gpu(); red_add_u32(&g_flags[FL_ATT + 8 * 15], 1); }
  if (SENT && threadIdx.x >= 224) {
    lds64(rh, bars + 248);
    reinterpret_cast<float2*>(g_modp + rh[0] * 2048 + rh[1] * 64)[threadIdx.x & 31] = make_float2(0.f, 0.f);
  }
  asm volatile("barrier.cluster.arrive.release.aligned;\nbarrier.cluster.wait.acquire.aligned;" ::: "memory");
}

template <int TA> __device__ __forceinline__ void wg_ss256(float* d, uint64_t a, uint64_t b) {
  asm volatile("wgmma.mma_async.sync.aligned.m64n256k16.f32.bf16.bf16 {%0,%1,%2,%3,%4,%5,%6,%7,%8,%9,%10,%11,%12,%13,%14,%15,%16,%17,%18,%19,%20,%21,%22,%23,%24,%25,%26,%27,%28,%29,%30,%31,%32,%33,%34,%35,%36,%37,%38,%39,%40,%41,%42,%43,%44,%45,%46,%47,%48,%49,%50,%51,%52,%53,%54,%55,%56,%57,%58,%59,%60,%61,%62,%63,%64,%65,%66,%67,%68,%69,%70,%71,%72,%73,%74,%75,%76,%77,%78,%79,%80,%81,%82,%83,%84,%85,%86,%87,%88,%89,%90,%91,%92,%93,%94,%95,%96,%97,%98,%99,%100,%101,%102,%103,%104,%105,%106,%107,%108,%109,%110,%111,%112,%113,%114,%115,%116,%117,%118,%119,%120,%121,%122,%123,%124,%125,%126,%127}, %128, %129, 1, 1, 1, %130, 1;"
               : "+f"(d[0]), "+f"(d[1]), "+f"(d[2]), "+f"(d[3]), "+f"(d[4]), "+f"(d[5]), "+f"(d[6]), "+f"(d[7]),
                 "+f"(d[8]), "+f"(d[9]), "+f"(d[10]), "+f"(d[11]), "+f"(d[12]), "+f"(d[13]), "+f"(d[14]), "+f"(d[15]),
                 "+f"(d[16]), "+f"(d[17]), "+f"(d[18]), "+f"(d[19]), "+f"(d[20]), "+f"(d[21]), "+f"(d[22]), "+f"(d[23]),
                 "+f"(d[24]), "+f"(d[25]), "+f"(d[26]), "+f"(d[27]), "+f"(d[28]), "+f"(d[29]), "+f"(d[30]), "+f"(d[31]),
                 "+f"(d[32]), "+f"(d[33]), "+f"(d[34]), "+f"(d[35]), "+f"(d[36]), "+f"(d[37]), "+f"(d[38]), "+f"(d[39]),
                 "+f"(d[40]), "+f"(d[41]), "+f"(d[42]), "+f"(d[43]), "+f"(d[44]), "+f"(d[45]), "+f"(d[46]), "+f"(d[47]),
                 "+f"(d[48]), "+f"(d[49]), "+f"(d[50]), "+f"(d[51]), "+f"(d[52]), "+f"(d[53]), "+f"(d[54]), "+f"(d[55]),
                 "+f"(d[56]), "+f"(d[57]), "+f"(d[58]), "+f"(d[59]), "+f"(d[60]), "+f"(d[61]), "+f"(d[62]), "+f"(d[63]),
                 "+f"(d[64]), "+f"(d[65]), "+f"(d[66]), "+f"(d[67]), "+f"(d[68]), "+f"(d[69]), "+f"(d[70]), "+f"(d[71]),
                 "+f"(d[72]), "+f"(d[73]), "+f"(d[74]), "+f"(d[75]), "+f"(d[76]), "+f"(d[77]), "+f"(d[78]), "+f"(d[79]),
                 "+f"(d[80]), "+f"(d[81]), "+f"(d[82]), "+f"(d[83]), "+f"(d[84]), "+f"(d[85]), "+f"(d[86]), "+f"(d[87]),
                 "+f"(d[88]), "+f"(d[89]), "+f"(d[90]), "+f"(d[91]), "+f"(d[92]), "+f"(d[93]), "+f"(d[94]), "+f"(d[95]),
                 "+f"(d[96]), "+f"(d[97]), "+f"(d[98]), "+f"(d[99]), "+f"(d[100]), "+f"(d[101]), "+f"(d[102]), "+f"(d[103]),
                 "+f"(d[104]), "+f"(d[105]), "+f"(d[106]), "+f"(d[107]), "+f"(d[108]), "+f"(d[109]), "+f"(d[110]), "+f"(d[111]),
                 "+f"(d[112]), "+f"(d[113]), "+f"(d[114]), "+f"(d[115]), "+f"(d[116]), "+f"(d[117]), "+f"(d[118]), "+f"(d[119]),
                 "+f"(d[120]), "+f"(d[121]), "+f"(d[122]), "+f"(d[123]), "+f"(d[124]), "+f"(d[125]), "+f"(d[126]), "+f"(d[127])
               : "l"(a), "l"(b), "n"(TA));
}
template <int TA> __device__ __forceinline__ void wg_ss128(float* d, uint64_t a, uint64_t b) {
  asm volatile("wgmma.mma_async.sync.aligned.m64n128k16.f32.bf16.bf16 {%0,%1,%2,%3,%4,%5,%6,%7,%8,%9,%10,%11,%12,%13,%14,%15,%16,%17,%18,%19,%20,%21,%22,%23,%24,%25,%26,%27,%28,%29,%30,%31,%32,%33,%34,%35,%36,%37,%38,%39,%40,%41,%42,%43,%44,%45,%46,%47,%48,%49,%50,%51,%52,%53,%54,%55,%56,%57,%58,%59,%60,%61,%62,%63}, %64, %65, 1, 1, 1, %66, 1;"
               : "+f"(d[0]), "+f"(d[1]), "+f"(d[2]), "+f"(d[3]), "+f"(d[4]), "+f"(d[5]), "+f"(d[6]), "+f"(d[7]),
                 "+f"(d[8]), "+f"(d[9]), "+f"(d[10]), "+f"(d[11]), "+f"(d[12]), "+f"(d[13]), "+f"(d[14]), "+f"(d[15]),
                 "+f"(d[16]), "+f"(d[17]), "+f"(d[18]), "+f"(d[19]), "+f"(d[20]), "+f"(d[21]), "+f"(d[22]), "+f"(d[23]),
                 "+f"(d[24]), "+f"(d[25]), "+f"(d[26]), "+f"(d[27]), "+f"(d[28]), "+f"(d[29]), "+f"(d[30]), "+f"(d[31]),
                 "+f"(d[32]), "+f"(d[33]), "+f"(d[34]), "+f"(d[35]), "+f"(d[36]), "+f"(d[37]), "+f"(d[38]), "+f"(d[39]),
                 "+f"(d[40]), "+f"(d[41]), "+f"(d[42]), "+f"(d[43]), "+f"(d[44]), "+f"(d[45]), "+f"(d[46]), "+f"(d[47]),
                 "+f"(d[48]), "+f"(d[49]), "+f"(d[50]), "+f"(d[51]), "+f"(d[52]), "+f"(d[53]), "+f"(d[54]), "+f"(d[55]),
                 "+f"(d[56]), "+f"(d[57]), "+f"(d[58]), "+f"(d[59]), "+f"(d[60]), "+f"(d[61]), "+f"(d[62]), "+f"(d[63])
               : "l"(a), "l"(b), "n"(TA));
}
template <int TA> __device__ __forceinline__ void wg_ss256_first(float* d, uint64_t a, uint64_t b) {
  asm volatile("wgmma.mma_async.sync.aligned.m64n256k16.f32.bf16.bf16 {%0,%1,%2,%3,%4,%5,%6,%7,%8,%9,%10,%11,%12,%13,%14,%15,%16,%17,%18,%19,%20,%21,%22,%23,%24,%25,%26,%27,%28,%29,%30,%31,%32,%33,%34,%35,%36,%37,%38,%39,%40,%41,%42,%43,%44,%45,%46,%47,%48,%49,%50,%51,%52,%53,%54,%55,%56,%57,%58,%59,%60,%61,%62,%63,%64,%65,%66,%67,%68,%69,%70,%71,%72,%73,%74,%75,%76,%77,%78,%79,%80,%81,%82,%83,%84,%85,%86,%87,%88,%89,%90,%91,%92,%93,%94,%95,%96,%97,%98,%99,%100,%101,%102,%103,%104,%105,%106,%107,%108,%109,%110,%111,%112,%113,%114,%115,%116,%117,%118,%119,%120,%121,%122,%123,%124,%125,%126,%127}, %128, %129, 0, 1, 1, %130, 1;"
               : "=f"(d[0]), "=f"(d[1]), "=f"(d[2]), "=f"(d[3]), "=f"(d[4]), "=f"(d[5]), "=f"(d[6]), "=f"(d[7]),
                 "=f"(d[8]), "=f"(d[9]), "=f"(d[10]), "=f"(d[11]), "=f"(d[12]), "=f"(d[13]), "=f"(d[14]), "=f"(d[15]),
                 "=f"(d[16]), "=f"(d[17]), "=f"(d[18]), "=f"(d[19]), "=f"(d[20]), "=f"(d[21]), "=f"(d[22]), "=f"(d[23]),
                 "=f"(d[24]), "=f"(d[25]), "=f"(d[26]), "=f"(d[27]), "=f"(d[28]), "=f"(d[29]), "=f"(d[30]), "=f"(d[31]),
                 "=f"(d[32]), "=f"(d[33]), "=f"(d[34]), "=f"(d[35]), "=f"(d[36]), "=f"(d[37]), "=f"(d[38]), "=f"(d[39]),
                 "=f"(d[40]), "=f"(d[41]), "=f"(d[42]), "=f"(d[43]), "=f"(d[44]), "=f"(d[45]), "=f"(d[46]), "=f"(d[47]),
                 "=f"(d[48]), "=f"(d[49]), "=f"(d[50]), "=f"(d[51]), "=f"(d[52]), "=f"(d[53]), "=f"(d[54]), "=f"(d[55]),
                 "=f"(d[56]), "=f"(d[57]), "=f"(d[58]), "=f"(d[59]), "=f"(d[60]), "=f"(d[61]), "=f"(d[62]), "=f"(d[63]),
                 "=f"(d[64]), "=f"(d[65]), "=f"(d[66]), "=f"(d[67]), "=f"(d[68]), "=f"(d[69]), "=f"(d[70]), "=f"(d[71]),
                 "=f"(d[72]), "=f"(d[73]), "=f"(d[74]), "=f"(d[75]), "=f"(d[76]), "=f"(d[77]), "=f"(d[78]), "=f"(d[79]),
                 "=f"(d[80]), "=f"(d[81]), "=f"(d[82]), "=f"(d[83]), "=f"(d[84]), "=f"(d[85]), "=f"(d[86]), "=f"(d[87]),
                 "=f"(d[88]), "=f"(d[89]), "=f"(d[90]), "=f"(d[91]), "=f"(d[92]), "=f"(d[93]), "=f"(d[94]), "=f"(d[95]),
                 "=f"(d[96]), "=f"(d[97]), "=f"(d[98]), "=f"(d[99]), "=f"(d[100]), "=f"(d[101]), "=f"(d[102]), "=f"(d[103]),
                 "=f"(d[104]), "=f"(d[105]), "=f"(d[106]), "=f"(d[107]), "=f"(d[108]), "=f"(d[109]), "=f"(d[110]), "=f"(d[111]),
                 "=f"(d[112]), "=f"(d[113]), "=f"(d[114]), "=f"(d[115]), "=f"(d[116]), "=f"(d[117]), "=f"(d[118]), "=f"(d[119]),
                 "=f"(d[120]), "=f"(d[121]), "=f"(d[122]), "=f"(d[123]), "=f"(d[124]), "=f"(d[125]), "=f"(d[126]), "=f"(d[127])
               : "l"(a), "l"(b), "n"(TA));
}
template <int TA> __device__ __forceinline__ void wg_ss128_first(float* d, uint64_t a, uint64_t b) {
  asm volatile("wgmma.mma_async.sync.aligned.m64n128k16.f32.bf16.bf16 {%0,%1,%2,%3,%4,%5,%6,%7,%8,%9,%10,%11,%12,%13,%14,%15,%16,%17,%18,%19,%20,%21,%22,%23,%24,%25,%26,%27,%28,%29,%30,%31,%32,%33,%34,%35,%36,%37,%38,%39,%40,%41,%42,%43,%44,%45,%46,%47,%48,%49,%50,%51,%52,%53,%54,%55,%56,%57,%58,%59,%60,%61,%62,%63}, %64, %65, 0, 1, 1, %66, 1;"
               : "=f"(d[0]), "=f"(d[1]), "=f"(d[2]), "=f"(d[3]), "=f"(d[4]), "=f"(d[5]), "=f"(d[6]), "=f"(d[7]),
                 "=f"(d[8]), "=f"(d[9]), "=f"(d[10]), "=f"(d[11]), "=f"(d[12]), "=f"(d[13]), "=f"(d[14]), "=f"(d[15]),
                 "=f"(d[16]), "=f"(d[17]), "=f"(d[18]), "=f"(d[19]), "=f"(d[20]), "=f"(d[21]), "=f"(d[22]), "=f"(d[23]),
                 "=f"(d[24]), "=f"(d[25]), "=f"(d[26]), "=f"(d[27]), "=f"(d[28]), "=f"(d[29]), "=f"(d[30]), "=f"(d[31]),
                 "=f"(d[32]), "=f"(d[33]), "=f"(d[34]), "=f"(d[35]), "=f"(d[36]), "=f"(d[37]), "=f"(d[38]), "=f"(d[39]),
                 "=f"(d[40]), "=f"(d[41]), "=f"(d[42]), "=f"(d[43]), "=f"(d[44]), "=f"(d[45]), "=f"(d[46]), "=f"(d[47]),
                 "=f"(d[48]), "=f"(d[49]), "=f"(d[50]), "=f"(d[51]), "=f"(d[52]), "=f"(d[53]), "=f"(d[54]), "=f"(d[55]),
                 "=f"(d[56]), "=f"(d[57]), "=f"(d[58]), "=f"(d[59]), "=f"(d[60]), "=f"(d[61]), "=f"(d[62]), "=f"(d[63])
               : "l"(a), "l"(b), "n"(TA));
}

constexpr uint32_t H_SB = 0x400;
constexpr int H_STAGE = 49152, H_NST = 4;
constexpr int H_STG = H_NST * H_STAGE;
constexpr int H_VEC = H_STG + 3 * 8192;
constexpr int H_GATE = H_VEC + 6656;
constexpr int H_BAR = H_GATE + 1024;
constexpr int H_SMEM = H_BAR + 256;
constexpr int HB_FULL = 0, HB_EMPTY = 32, HB_IFULL = 64, HB_IEMPTY = 80, HB_VFULL = 96, HB_STGF = 112, HB_ITEM = 120, HB_Q = 128, HB_SRDY = 160, HB_SFREE = 184,
              HB_MFULL = 208, HB_MEMPTY = 224, HB_MAIL = 240;
constexpr int NB_HX = 4, NB_HY = 5, NB_HZ = 6;
enum { IT_END = 0, IT_MOD = 1, IT_XT = 2, IT_OUT = 3, IT_WS = 4, IT_F1 = 5, IT_F2 = 6, IT_STAT = 7 };
constexpr int N_MOD = 32, N_WS = 28, N_XT = 2, N_STAT = 4;
constexpr int MAX_ITEMS = 1400;
#define NH2 94
constexpr int NH1 = 36;
struct HList { uint32_t n, head, tbase; uint32_t it[MAX_ITEMS]; };
#define HT(i)

#define POL_WO L2_NORMAL
#define POL_W2 L2_NORMAL
#define POL_ATT L2_FIRST
#define POL_ACT L2_FIRST
#define POL_PRE L2_FIRST
__device__ __forceinline__ void mbar_arrive_n(uint32_t b, uint32_t n) { asm volatile("mbarrier.arrive.shared::cta.b64 _, [%0], %1;" :: "r"(b), "r"(n) : "memory"); }
__device__ __forceinline__ void mbar_arrive_cl(uint32_t b) { asm volatile("mbarrier.arrive.shared::cluster.b64 _, [%0];" :: "r"(b) : "memory"); }
__device__ __forceinline__ void h_free(uint32_t b, uint32_t pm) { mbar_arrive(b); mbar_arrive_cl(b ^ pm); }
__device__ __forceinline__ void tma2d_mc(uint32_t dst, const CUtensorMap* m, int c0, int c1, uint32_t bar, uint64_t pol) {
  asm volatile("cp.async.bulk.tensor.2d.shared::cluster.global.mbarrier::complete_tx::bytes.multicast::cluster.L2::cache_hint [%0], [%1, {%3, %4}], [%2], %5, %6;"
               :: "r"(dst), "l"(m), "r"(bar), "r"(c0), "r"(c1), "h"((uint16_t)3), "l"(pol) : "memory");
}
__device__ __forceinline__ void bulk_mc(uint32_t dst, const void* src, uint32_t bytes, uint32_t bar, uint64_t pol) {
  asm volatile("cp.async.bulk.shared::cluster.global.mbarrier::complete_tx::bytes.multicast::cluster.L2::cache_hint [%0], [%1], %2, [%3], %4, %5;"
               :: "r"(dst), "l"(src), "r"(bytes), "r"(bar), "h"((uint16_t)3), "l"(pol) : "memory");
}
__device__ __forceinline__ void cluster_sync() {
  asm volatile("barrier.cluster.arrive.release.aligned;\nbarrier.cluster.wait.acquire.aligned;" ::: "memory");
}
__device__ __forceinline__ void bulk_s2g(void* dst, uint32_t src, uint32_t bytes) {
  asm volatile("cp.async.bulk.global.shared::cta.bulk_group [%0], [%1], %2;" :: "l"(dst), "r"(src), "r"(bytes) : "memory");
}
__device__ __forceinline__ void tma2d_add(const CUtensorMap* m, int c0, int c1, uint32_t src) {
  asm volatile("cp.reduce.async.bulk.tensor.2d.global.shared::cta.add.tile.bulk_group [%0, {%2, %3}], [%1];" :: "l"(m), "r"(src), "r"(c0), "r"(c1) : "memory");
}
__device__ __forceinline__ void bulk_commit() { asm volatile("cp.async.bulk.commit_group;" ::: "memory"); }
template <int N> __device__ __forceinline__ void bulk_wait_read() { asm volatile("cp.async.bulk.wait_group.read %0;" :: "n"(N) : "memory"); }
__device__ __forceinline__ void bulk_wait_all() { asm volatile("cp.async.bulk.wait_group 0;" ::: "memory"); }
__device__ __forceinline__ uint32_t hfma2(uint32_t a, uint32_t b, uint32_t c) { uint32_t t; asm("fma.rn.bf16x2 %0, %1, %2, %3;" : "=r"(t) : "r"(a), "r"(b), "r"(c)); return t; }
__device__ __forceinline__ float lds32f(uint32_t a) { return __uint_as_float(lds32(a)); }

template <int BN, int TA, int K0, int K1>
__device__ __forceinline__ void h_mma(float* acc, uint64_t da, uint64_t db) {
#pragma unroll
  for (int k = K0; k < K1; k++) {
    const uint64_t a = da + k * (TA ? 256 : 2), b = db + k * 128;
    if (BN == 256) wg_ss256<TA>(acc, a, b); else wg_ss128<TA>(acc, a, b);
  }
}
template <int BN, int TA>
__device__ __forceinline__ void h_mainloop(float* acc, uint32_t sb, uint32_t pm, int nst, uint32_t& st, uint32_t& ph, int wg, bool leader, uint32_t clk_q) {
  const uint64_t da0 = TA ? mkdesc(H_SB + wg * 1024, 2048, 128, 0) : mkdesc(H_SB + wg * 8192, 16, 1024, 1);
  const uint64_t db0 = mkdesc(H_SB + 16384, 8192, 1024, 1);
  const uint32_t full = sb + H_BAR + HB_FULL, empty = sb + H_BAR + HB_EMPTY;
  uint32_t prev = st;
  {
    mbar_wait(full + st * 8, ph);
    HT(1);
    const uint64_t da = da0 + st * (H_STAGE >> 4), db = db0 + st * (H_STAGE >> 4);
    WG_FENCE();
    if (BN == 256) wg_ss256_first<TA>(acc, da, db); else wg_ss128_first<TA>(acc, da, db);
    h_mma<BN, TA, 1, 4>(acc, da, db);
    WG_COMMIT();
    if (++st == H_NST) { st = 0; ph ^= 1; }
  }
  {
    mbar_wait(full + st * 8, ph);
    const uint64_t da = da0 + st * (H_STAGE >> 4), db = db0 + st * (H_STAGE >> 4);
    WG_FENCE();
    h_mma<BN, TA, 0, 3>(acc, da, db);
    WG_COMMIT();
    h_mma<BN, TA, 3, 4>(acc, da, db);
    WG_COMMIT();
    WG_WAIT(1);
    if (leader) h_free(empty + prev * 8, pm);
    if (wg) bar_arrive<NB_HY, 256>(); else bar_sync<NB_HY, 256>();
    prev = st;
    if (++st == H_NST) { st = 0; ph ^= 1; }
  }
#pragma unroll 1
  for (int i = 4; i < nst; i++) {
    mbar_wait(full + st * 8, ph);
    const uint64_t da = da0 + st * (H_STAGE >> 4), db = db0 + st * (H_STAGE >> 4);
    WG_FENCE();
    h_mma<BN, TA, 0, 4>(acc, da, db);
    WG_COMMIT();
    WG_WAIT(1);
    if (leader) h_free(empty + prev * 8, pm);
    prev = st;
    if (++st == H_NST) { st = 0; ph ^= 1; }
  }
  if (wg) {
    WG_WAIT(0);
    if (leader) h_free(empty + prev * 8, pm);
    bar_sync<NB_HX, 256>();
  }
  {
    mbar_wait(full + st * 8, ph);
    const uint64_t da = da0 + st * (H_STAGE >> 4), db = db0 + st * (H_STAGE >> 4);
    WG_FENCE();
    h_mma<BN, TA, 0, 4>(acc, da, db);
    WG_COMMIT();
    WG_WAIT(1);
    if (leader && !wg) h_free(empty + prev * 8, pm);
    prev = st;
    if (++st == H_NST) { st = 0; ph ^= 1; }
  }
  {
    mbar_wait(full + st * 8, ph);
    const uint64_t da = da0 + st * (H_STAGE >> 4), db = db0 + st * (H_STAGE >> 4);
    WG_FENCE();
    h_mma<BN, TA, 0, 3>(acc, da, db);
    WG_COMMIT();
    h_mma<BN, TA, 3, 4>(acc, da, db);
    WG_COMMIT();
    WG_WAIT(1);
    if (leader) h_free(empty + prev * 8, pm);
    if (!wg) bar_arrive<NB_HX, 256>();
  }
}
__device__ __forceinline__ void h_release(uint32_t sb, uint32_t pm, uint32_t& st, uint32_t& ph, bool leader) {
  if (leader) h_free(sb + H_BAR + HB_EMPTY + st * 8, pm);
  if (++st == H_NST) { st = 0; ph ^= 1; }
}

__device__ __forceinline__ uint32_t stg_acquire(uint32_t sb, uint32_t g, uint32_t& b) {
  const uint32_t q = (g * 43691u) >> 17;
  b = g - 3 * q;
  mbar_wait(sb + H_BAR + HB_SFREE + b * 8, (q & 1) ^ 1);
  return sb + H_STG + b * 8192;
}
__device__ __forceinline__ void stg_release(uint32_t sb, uint32_t b, int lane) {
  __syncwarp();
  if (lane == 0) mbar_arrive(sb + H_BAR + HB_SRDY + b * 8);
}
__device__ __forceinline__ uint32_t hmul2(uint32_t a, uint32_t b) { uint32_t t; asm("mul.rn.bf16x2 %0, %1, %2;" : "=r"(t) : "r"(a), "r"(b)); return t; }
template <int BN>
__device__ __forceinline__ void h_gated(float* acc, uint32_t va, uint32_t vb, uint32_t vp, uint32_t sb, uint32_t pm, uint32_t& st, uint32_t& ph, uint32_t g0, int wg, bool leader,
                                        int warp, int lane, uint32_t clk_q) {
  uint32_t gt[BN / 8];
  mbar_wait(vb, vp);
#pragma unroll
  for (int i = 0; i < BN / 32; i++) lds128(gt + 4 * i, va + i * 64 + (lane & 3) * 16);
  WG_WAIT(0);
  reg_fence<BN / 2>(acc);
  h_release(sb, pm, st, ph, leader);
  HT(2);
  const uint32_t ro = ((warp & 3) * 16 + (lane & 7)) * 128, x0 = ((lane >> 3) ^ (lane & 7)) << 4;
  if (BN == 256 && wg) bar_sync<NB_HZ, 256>();
#pragma unroll
  for (int u = 0; u < BN / 64; u++) {
    uint32_t b;
    const uint32_t base = stg_acquire(sb, g0 + u, b) + ro;
    if (BN == 256 && u == 1 && !wg) bar_arrive<NB_HZ, 256>();
#pragma unroll
    for (int c2 = 0; c2 < 2; c2++) {
      const int c = 2 * u + c2;
#pragma unroll
      for (int h = 0; h < 2; h++) {
        uint32_t y[4];
#pragma unroll
        for (int j = 0; j < 4; j++) { const float* a = acc + c * 16 + j * 4 + h * 2; y[j] = hmul2(pack2(a[0], a[1]), gt[4 * c + j]); }
        stsm4(base + h * 1024 + (x0 ^ (c2 << 6)), y);
      }
    }
    stg_release(sb, b, lane);
  }
}

template <int BN>
__device__ __forceinline__ void h_swiglu(float* acc, uint32_t vb, uint32_t vp, uint32_t sb, uint32_t pm, uint32_t& st, uint32_t& ph, uint32_t g0, int wg, bool leader,
                                         int warp, int lane, uint32_t clk_q) {
  float rs[2], rh[2];
  mbar_wait(vb, vp);
  {
    const uint64_t da = mkdesc(H_SB + H_VEC + 4096 + wg * 1024, 0, 128, 0), db = mkdesc(H_SB + H_VEC, 1024, 0, 1);
    WG_FENCE();
    if (BN == 256) wg_ss256<0>(acc, da, db); else wg_ss128<0>(acc, da, db);
    WG_COMMIT();
  }
#pragma unroll
  for (int h = 0; h < 2; h++) { rs[h] = lds32f(sb + H_VEC + 6144 + (warp * 16 + h * 8 + (lane >> 2)) * 4); rh[h] = 0.5f * rs[h]; }
  WG_WAIT(1);
  h_release(sb, pm, st, ph, leader);
  WG_WAIT(0);
  reg_fence<BN / 2>(acc);
  HT(2);
  const uint32_t ro = ((warp & 3) * 16 + (lane & 7)) * 128, x0 = ((lane >> 3) ^ (lane & 7)) << 4;
#pragma unroll
  for (int uu = 0; uu < BN / 128; uu++) {
    uint32_t b;
    const uint32_t base = stg_acquire(sb, g0 + uu, b) + ro;
#pragma unroll
    for (int c2 = 0; c2 < 2; c2++) {
      const int c = 2 * uu + c2;
      uint32_t y[2][4];
#pragma unroll
      for (int j = 0; j < 4; j++) {
        const float* g = acc + 16 * c + 4 * j; const float* u = g + BN / 4;
        float o[4];
#pragma unroll
        for (int e = 0; e < 4; e++) {
          const float g2 = rh[e >> 1] * g[e];
          const float h = g2 * (rs[e >> 1] * u[e]);
          float t; asm("tanh.approx.f32 %0, %1;" : "=f"(t) : "f"(g2));
          o[e] = fmaf(h, t, h);
        }
        y[0][j] = pack2(o[0], o[1]); y[1][j] = pack2(o[2], o[3]);
      }
      stsm4(base + (x0 ^ (c2 << 6)), y[0]); stsm4(base + 1024 + (x0 ^ (c2 << 6)), y[1]);
    }
    stg_release(sb, b, lane);
  }
}

template <bool WS>
__device__ __forceinline__ void h_vecmat(uint32_t sb, int idx, uint32_t& st, uint32_t& ph, int tid, const __nv_bfloat16* cvec, uint8_t* w13s, uint8_t* bext,
                                         __nv_bfloat16* mod, __nv_bfloat16* gate) {
  const uint32_t stg = sb + H_STG, bars = sb + H_BAR;
  const int lane = tid & 31, warp = tid >> 5;
#pragma unroll
  for (int i = 0; i < 4; i++) {
    const int k = tid + 256 * i;
    if (WS) {
      const uint32_t s = __ldcg(reinterpret_cast<const uint16_t*>(mod) + 3 * D_ + k), c = __ldcg(reinterpret_cast<const uint16_t*>(mod) + 4 * D_ + k);
      sts32(stg + k * 4, s << 16); sts32(stg + 4096 + k * 4, c | c << 16);
    } else {
      const float c = __bfloat162float(cvec[k]);
      sts32(stg + k * 4, __float_as_uint(__bfloat162float(__float2bfloat16(c / (1.f + __expf(-c))))));
    }
  }
  bar_sync<1, 256>();
  float v[4][8], u[4][8];
#pragma unroll
  for (int b = 0; b < 4; b++)
#pragma unroll
    for (int e = 0; e < 8; e++) { v[b][e] = 0.f; u[b][e] = 0.f; }
  const int r0 = tid >> 3;
  const uint32_t off = 16384 + r0 * 128 + (((tid & 7) ^ (r0 & 7)) << 4);
  uint32_t prev = 0;
#pragma unroll 1
  for (int i = 0; i < (WS ? 16 : 8); i++) {
    mbar_wait(bars + HB_FULL + st * 8, ph);
    const uint32_t base = sb + st * H_STAGE + off;
#pragma unroll
    for (int ri = 0; ri < 2; ri++) {
      const uint32_t ka = stg + ((WS ? i * 64 : i * 128) + r0 + 32 * ri) * 4;
      const float m0 = lds32f(ka), m1 = WS ? m0 : lds32f(ka + 256);
      const uint32_t c2 = WS ? lds32(ka + 4096) : 0;
#pragma unroll
      for (int b = 0; b < 4; b++) {
        uint32_t w[4];
        lds128(w, base + b * 8192 + ri * 4096);
        const float m = b < 2 ? m0 : m1;
#pragma unroll
        for (int e = 0; e < 4; e++) {
          v[b][2 * e] = fmaf(m, bf_lo(w[e]), v[b][2 * e]); v[b][2 * e + 1] = fmaf(m, bf_hi(w[e]), v[b][2 * e + 1]);
          if (WS) { w[e] = hfma2(w[e], c2, w[e]); u[b][2 * e] += bf_lo(w[e]); u[b][2 * e + 1] += bf_hi(w[e]); }
        }
        if (WS) sts128(base + b * 8192 + ri * 4096, w[0], w[1], w[2], w[3]);
      }
    }
    if (WS) fence_async_smem();
    bar_sync<1, 256>();
    if (tid == 0) {
      if (WS) {
        bulk_s2g(w13s + (size_t)(idx * 16 + i) * 32768, sb + st * H_STAGE + 16384, 32768);
        bulk_commit();
        if (i > 0) { bulk_wait_read<1>(); mbar_arrive_n(bars + HB_EMPTY + prev * 8, 4); }
      } else mbar_arrive_n(bars + HB_EMPTY + st * 8, 4);
    }
    prev = st;
    if (++st == H_NST) { st = 0; ph ^= 1; }
  }
  if (WS && tid == 0) {
    bulk_wait_read<0>(); mbar_arrive_n(bars + HB_EMPTY + prev * 8, 4);
    bulk_wait_all(); fence_async_all(); fence_gpu();
  }
#pragma unroll
  for (int b = 0; b < 4; b++)
#pragma unroll
    for (int e = 0; e < 8; e++) {
      v[b][e] += __shfl_xor_sync(0xffffffffu, v[b][e], 8); v[b][e] += __shfl_xor_sync(0xffffffffu, v[b][e], 16);
      if (WS) { u[b][e] += __shfl_xor_sync(0xffffffffu, u[b][e], 8); u[b][e] += __shfl_xor_sync(0xffffffffu, u[b][e], 16); }
    }
  if (lane < 8) {
#pragma unroll
    for (int b = 0; b < 4; b++) {
      const uint32_t a = stg + warp * 2048 + b * 256 + lane * 32;
      sts128(a, __float_as_uint(v[b][0]), __float_as_uint(v[b][1]), __float_as_uint(v[b][2]), __float_as_uint(v[b][3]));
      sts128(a + 16, __float_as_uint(v[b][4]), __float_as_uint(v[b][5]), __float_as_uint(v[b][6]), __float_as_uint(v[b][7]));
      if (WS) {
        sts128(a + 1024, __float_as_uint(u[b][0]), __float_as_uint(u[b][1]), __float_as_uint(u[b][2]), __float_as_uint(u[b][3]));
        sts128(a + 1040, __float_as_uint(u[b][4]), __float_as_uint(u[b][5]), __float_as_uint(u[b][6]), __float_as_uint(u[b][7]));
      }
    }
  }
  bar_sync<1, 256>();
  float sv = 0.f, su = 0.f;
#pragma unroll
  for (int i = 0; i < 8; i++) {
    sv += lds32f(stg + i * 2048 + tid * 4);
    su += WS ? lds32f(stg + i * 2048 + 1024 + tid * 4) : lds32f(stg + i * 2048 + (tid ^ 128) * 4);
  }
  if (WS) {
    const __nv_bfloat16 uh = __float2bfloat16(su), ul = __float2bfloat16(su - __bfloat162float(uh));
    const __nv_bfloat16 vh = __float2bfloat16(sv), vl = __float2bfloat16(sv - __bfloat162float(vh)), z = __float2bfloat16(0.f);
    uint8_t* p = bext + idx * 4096 + (tid >> 6) * 1024 + (tid & 7) * 2;
#pragma unroll
    for (int r = 0; r < 8; r++)
      *reinterpret_cast<__nv_bfloat16*>(p + r * 128 + ((((tid & 63) >> 3) ^ r) << 4)) = r == 0 || r == 2 ? uh : r == 1 ? ul : r == 3 || r == 5 ? vh : r == 4 ? vl : z;
  } else if (tid < 128) {
    const int n = idx * 128 + tid, vec = n >> 10, col = n & 1023;
    const __nv_bfloat16 r = __float2bfloat16(sv + su);
    mod[2048 + n] = r;
    if (vec == 0 || vec == 3) gate[(vec ? D_ : 0) + (col & ~31) + ((col >> 1) & 3) * 8 + ((col >> 3) & 3) * 2 + (col & 1)] = r;
  }
}

struct HWeights { const uint8_t* p[4]; };
#define HW_T 420
#define HW_D 0
#define HW_U0 0
#define HW_U1 0
__global__ void __launch_bounds__(384, 1)
kernel_H(const __grid_constant__ CUtensorMap tmo, const __grid_constant__ CUtensorMap tm1, const __grid_constant__ CUtensorMap tm3,
         const __grid_constant__ CUtensorMap tm2, const __grid_constant__ CUtensorMap tmm, const __grid_constant__ CUtensorMap tmx,
         const __grid_constant__ CUtensorMap tmy, const __nv_bfloat16* __restrict__ x, const __nv_bfloat16* __restrict__ cvec, __nv_bfloat16* out, const __grid_constant__ HWeights rw, const __grid_constant__ HList list) {
  extern __shared__ __align__(1024) uint8_t smem[];
  uint32_t rank, pair;
  asm("mov.u32 %0, %%cluster_ctarank;" : "=r"(rank)); asm("mov.u32 %0, %%cluster_nctarank;" : "=r"(pair));
  rank = __shfl_sync(0xffffffffu, rank, 0); pair = __shfl_sync(0xffffffffu, pair, 0) - 1;
  const uint32_t sb = H_SB + (rank << 24), bars = sb + H_BAR, pm = pair << 24;
  const int tid = threadIdx.x, lane = tid & 31;
  const int warp = __shfl_sync(0xffffffffu, tid >> 5, 0);
  if (tid == 0) {
    if ((smem_u32(smem) & 0xffffff) != H_SB) __trap();
    for (int i = 0; i < H_NST; i++) { mbar_init(bars + HB_FULL + i * 8, 1); mbar_init(bars + HB_EMPTY + i * 8, 4); }
    for (int i = 0; i < 2; i++) { mbar_init(bars + HB_IFULL + i * 8, 1); mbar_init(bars + HB_IEMPTY + i * 8, 1); mbar_init(bars + HB_VFULL + i * 8, 1);
      mbar_init(bars + HB_MFULL + i * 8, 1); mbar_init(bars + HB_MEMPTY + i * 8, 1); }
    for (int i = 0; i < 3; i++) { mbar_init(bars + HB_SRDY + i * 8, 4); mbar_init(bars + HB_SFREE + i * 8, 1); }
    mbar_init(bars + HB_STGF, 1);
    asm volatile("fence.mbarrier_init.release.cluster;" ::: "memory");
    fence_async_smem();
  }
  __syncthreads();
  cluster_sync();
  asm volatile("griddepcontrol.launch_dependents;");
  if (warp >= 8) {
    asm volatile("setmaxnreg.dec.sync.aligned.u32 56;");
    if (warp == 8) {
      uint32_t st = 0, ph = 1, nv = 0, q = 0;
      uint32_t* const head = &g_flags[list.head];
      const bool claimer = lane == 0 && rank == 0;
      if (claimer) q = atomicAdd(head, 1);
#pragma unroll 1
      for (uint32_t n = 0;; n++) {
        if (pair) {
          const uint32_t o = (n & 1) * 8, p = (n >> 1) & 1;
          if (rank == 0) {
            mbar_wait(bars + HB_MEMPTY + o, p ^ 1);
            if (lane == 0) st_async1((bars + HB_MAIL + o) ^ pm, q, (bars + HB_MFULL + o) ^ pm);
          } else {
            if (lane == 0) mbar_expect(bars + HB_MFULL + o, 4);
            mbar_wait(bars + HB_MFULL + o, p);
            q = lds32(bars + HB_MAIL + o);
            __syncwarp();
            if (lane == 0) mbar_arrive_cl((bars + HB_MEMPTY + o) ^ pm);
          }
        }
        q = __shfl_sync(0xffffffffu, q, 0);
        uint32_t it = q < list.n ? list.it[q] : 0;
        const bool shA = pair && !(it >> 28 & 1), shB = pair && (it >> 28 & 1);
        if (rank && it) it += shA ? 1 << 7 : (it >> 29) << 3;
        const int type = it & 7, mt = (it >> 3) & 15, idx = (it >> 7) & 63, sz = (it >> 13) & 3, kb0 = (it >> 15) & 63, nkb = (it >> 21) & 127;
        {
          int f = FL_GO; uint32_t target = 0;
          if (type == IT_OUT) { f = lane == 0 ? FL_ATT + 8 * mt : lane == 1 ? FL_XT + 8 * mt : FL_MOD; target = lane == 0 ? 64 : lane == 1 ? N_XT : N_MOD; }
          else if (type == IT_F1) { f = lane == 0 ? FL_OUT + 8 * mt : FL_WS; target = lane == 0 ? 1024 : N_WS; }
          else if (type == IT_F2) { f = FL_F1 + 8 * mt; target = 56; }
          else if (type == IT_STAT) { f = FL_OUT + 8 * mt; target = 1024; }
          else if (type == IT_WS) { f = FL_MOD; target = N_MOD; }
          else if (type != IT_END) target = 1;
          if (lane < 3) wait_flag(&g_flags[f], target);
          __syncwarp();
          asm volatile("fence.proxy.async.global;" ::: "memory");
        }
        mbar_wait(bars + HB_IEMPTY + (n & 1) * 8, ((n >> 1) & 1) ^ 1);
        if (elect_one()) {
          sts32(bars + HB_ITEM + (n & 1) * 4, it);
          mbar_arrive(bars + HB_IFULL + (n & 1) * 8);
        }
        if (type == IT_END) break;
        const bool gemm = type == IT_OUT || type == IT_F1 || type == IT_F2;
        const int nst = gemm ? nkb : type == IT_WS ? 16 : type == IT_MOD ? 8 : 0;
        const int bn = 256 >> sz;
        const uint8_t* ap = type == IT_OUT ? g_att + (size_t)mt * 64 * 16384 : g_act + (size_t)mt * 56 * 16384;
        const uint8_t* wp = g_w13s + (size_t)(idx >> sz) * 16 * 32768 + (sz ? (idx & 1) * 8192 : 0);
        const CUtensorMap* tb = type == IT_OUT ? &tmo : type == IT_F2 ? &tm2 : type == IT_WS ? &tm1 : &tmm;
        const CUtensorMap* tc = type == IT_WS ? &tm3 : tb;
        const int c0 = gemm ? idx * bn : type == IT_WS ? idx * 128 : 2048 + idx * 128, dcol = gemm ? 128 : 0, kmul = type == IT_MOD ? 128 : 64, drow = type == IT_MOD ? 64 : 0;
        const uint32_t bytes = gemm ? 16384 + bn * 128 : 32768;
        const uint64_t pa = type == IT_OUT ? POL_ATT : POL_ACT, pb = type == IT_OUT ? POL_WO : type == IT_F2 ? POL_W2 : POL_PRE;
        if (nst < 2 && claimer) q = atomicAdd(head, 1);
#pragma unroll 1
        for (int i = 0; i < nst; i++) {
          const int kb = kb0 + i;
          const uint32_t d = sb + st * H_STAGE, fb = bars + HB_FULL + st * 8;
          if (i == nst - 2 && claimer) q = atomicAdd(head, 1);
          mbar_wait(bars + HB_EMPTY + st * 8, ph);
          if (elect_one()) {
            mbar_expect(fb, bytes);
            if (type == IT_F1) {
              if (shA) tma2d_mc(d + rank * 8192, &tmy, kb * 64, mt * 128 + rank * 64, fb, L2_NORMAL); else tma2d(d, &tmx, kb * 64, mt * 128, fb);
              if (shB) bulk_mc(d + 16384 + rank * (16384 >> sz), wp + (size_t)kb * 32768 + rank * 16384, 16384 >> sz, fb, L2_NORMAL);
              else if (sz == 0) bulk_g2s(d + 16384, wp + (size_t)kb * 32768, 32768, fb);
              else { bulk_g2s(d + 16384, wp + (size_t)kb * 32768, 8192, fb); bulk_g2s(d + 24576, wp + (size_t)kb * 32768 + 16384, 8192, fb); }
            } else {
              if (shA) bulk_mc(d + rank * 8192, ap + (size_t)kb * 16384 + rank * 8192, 8192, fb, pa);
              else if (gemm) bulk_g2s_p(d, ap + (size_t)kb * 16384, 16384, fb, pa);
              if (shB) {
                if (sz == 0) {
                  tma2d_mc(d + 16384 + rank * 16384, tb, c0 + rank * 128, kb * 64, fb, pb);
                  tma2d_mc(d + 24576 + rank * 16384, tb, c0 + rank * 128 + 64, kb * 64, fb, pb);
                } else tma2d_mc(d + 16384 + rank * 8192, tb, c0 + rank * 64, kb * 64, fb, pb);
              } else {
                tma2d_p(d + 16384, tb, c0, kb * kmul, fb, pb);
                tma2d_p(d + 24576, tb, c0 + 64, kb * kmul, fb, pb);
                if (sz == 0) { tma2d_p(d + 32768, tc, c0 + dcol, kb * kmul + drow, fb, pb); tma2d_p(d + 40960, tc, c0 + dcol + 64, kb * kmul + drow, fb, pb); }
              }
            }
          }
          if (++st == H_NST) { st = 0; ph ^= 1; }
        }
        if (gemm) {
          if (type == IT_F1) {
            if (lane == 0) wait_flag(&g_flags[FL_STAT + 8 * mt], N_STAT);
            __syncwarp();
            asm volatile("fence.proxy.async.global;" ::: "memory");
          }
          if (elect_one()) {
            const uint32_t v = sb + H_VEC, fb = bars + HB_VFULL + (nv & 1) * 8;
            if (type == IT_F1) {
              mbar_expect(fb, (4096 >> sz) + 2560);
              if (sz == 0) bulk_g2s(v, g_bext + idx * 4096, 4096, fb);
              else { const uint8_t* p = g_bext + (idx >> 1) * 4096 + (idx & 1) * 1024; bulk_g2s(v, p, 1024, fb); bulk_g2s(v + 1024, p + 2048, 1024, fb); }
              bulk_g2s(v + 4096, g_ext + mt * 2560, 2560, fb);
            } else {
              mbar_expect(fb, bn * 2);
              bulk_g2s(sb + H_GATE + (nv & 1) * 512, g_gate + (type == IT_F2 ? D_ : 0) + c0, bn * 2, fb);
            }
          }
          nv++;
        }
      }
    } else if (warp == 10) {
      if (!pair && lane == 0) {
        const uint32_t t0 = clk32() + HW_D;
        uint32_t n = 0;
#pragma unroll 1
        for (int u = HW_U0 + blockIdx.x; u < HW_U1; u += NH1, n++) {
          int m, o;
          if (u < 768) { const int r = u / 96; m = r < 4 ? r & 1 : r == 4 ? 2 : r - 5; o = (r < 2 ? 384 : r < 4 ? 0 : r == 4 ? 192 : 576) / 2 + u - r * 96; }
          else if (u < 1152) { m = (u - 768) >> 7; o = 384 + (u & 127); }
          else { m = 3; o = u - 1152; }
          while ((int32_t)(clk32() - t0 - n * HW_T) < 0) {}
          asm volatile("cp.async.bulk.prefetch.L2.global [%0], 16384;" :: "l"(rw.p[m] + (size_t)o * 16384) : "memory");
        }
      }
    } else if (warp == 9) {
      uint32_t g = 0;
#pragma unroll 1
      for (uint32_t n = 0;; n++) {
        mbar_wait(bars + HB_IFULL + (n & 1) * 8, (n >> 1) & 1);
        const uint32_t it = lds32(bars + HB_ITEM + (n & 1) * 4);
        const int type = it & 7, mt = (it >> 3) & 15, idx = (it >> 7) & 63, sz = (it >> 13) & 3, nkb = (it >> 21) & 127;
        if (type == IT_END) break;
        const bool gated = type == IT_OUT || type == IT_F2, gemm = gated || type == IT_F1;
        if (!gemm) { if (n & 1) bar_sync<3, 288>(); else bar_sync<2, 288>(); }
        if (lane == 0) {
          if (gemm) {
            const int nu = (gated ? 4 : 2) >> sz;
            uint32_t pb = 0;
#pragma unroll 1
            for (int u = 0; u < 2 * nu; u++, g++) {
              const uint32_t r = (g * 43691u) >> 17, b = g - 3 * r, src = sb + H_STG + b * 8192;
              const int w = u >= nu, uu = u - w * nu;
              mbar_wait(bars + HB_SRDY + b * 8, r & 1);
              if (u == 2 * nu - 1) mbar_arrive(bars + HB_IEMPTY + (n & 1) * 8);
              fence_async_smem();
              if (gated) tma2d_add(&tmy, idx * (256 >> sz) + uu * 64, mt * 128 + w * 64, src);
              else bulk_s2g(g_act + (size_t)(mt * 56 + idx * nu + uu) * 16384 + w * 8192, src, 8192);
              bulk_commit();
              if (u > 0) { bulk_wait_read<1>(); mbar_arrive(bars + HB_SFREE + pb * 8); }
              pb = b;
            }
            bulk_wait_read<0>();
            mbar_arrive(bars + HB_SFREE + pb * 8);
            mbar_arrive(bars + HB_STGF);
            bulk_wait_all(); fence_async_all();
          } else {
            mbar_arrive(bars + HB_STGF);
            mbar_arrive(bars + HB_IEMPTY + (n & 1) * 8);
          }
          if (type != IT_F2) {
            const uint32_t inc = type == IT_OUT ? (4 >> sz) * nkb : type == IT_F1 ? 2 >> sz : 1;
            fence_gpu();
            red_add_u32(&g_flags[type == IT_MOD ? FL_MOD : type == IT_WS ? FL_WS :
                                 (type == IT_XT ? FL_XT : type == IT_OUT ? FL_OUT : type == IT_STAT ? FL_STAT : FL_F1) + 8 * mt], inc);
          }
        }
        __syncwarp();
      }
      if (!pair) asm volatile("griddepcontrol.wait;" ::: "memory");
      uint32_t k = 0;
      if (lane == 0) { fence_gpu(); k = atomicAdd(&g_flags[FL_EXIT], 1); }
      k = __shfl_sync(0xffffffffu, k, 0);
      if (k == NH1 + NH2 - 1) {
        fence_gpu();
        for (int i = lane; i < 1024; i += 32) g_flags[i] = 0;
      }
    }
  } else {
    asm volatile("setmaxnreg.inc.sync.aligned.u32 224;");
    const int wg = warp >> 2;
    const bool leader = (tid & 127) == 0;
    uint32_t st = 0, ph = 0, nv = 0, g = 0;
#pragma unroll 1
    for (uint32_t n = 0;; n++) {
      mbar_wait(bars + HB_IFULL + (n & 1) * 8, (n >> 1) & 1);
      const uint32_t it = __shfl_sync(0xffffffffu, lds32(bars + HB_ITEM + (n & 1) * 4), 0);
      const int type = it & 7, mt = (it >> 3) & 15, idx = (it >> 7) & 63, sz = (it >> 13) & 3, nkb = (it >> 21) & 127;
      if (type == IT_END) break;
      constexpr uint32_t clk_q = 0;
      if (type == IT_OUT || type == IT_F1 || type == IT_F2) {
        const uint32_t va = sb + H_GATE + (nv & 1) * 512, vb = bars + HB_VFULL + (nv & 1) * 8, vp = (nv >> 1) & 1;
        const uint32_t nu = (type == IT_F1 ? 2 : 4) >> sz, g0 = g + wg * nu;
        nv++; g += 2 * nu;
        if (sz == 0) {
          float acc[128];
          if (type == IT_OUT) h_mainloop<256, 1>(acc, sb, pm, nkb, st, ph, wg, leader, clk_q);
          else h_mainloop<256, 0>(acc, sb, pm, nkb, st, ph, wg, leader, clk_q);
          if (type == IT_F1) h_swiglu<256>(acc, vb, vp, sb, pm, st, ph, g0, wg, leader, warp, lane, clk_q);
          else h_gated<256>(acc, va, vb, vp, sb, pm, st, ph, g0, wg, leader, warp, lane, clk_q);
        } else {
          float acc[64];
          if (type == IT_OUT) h_mainloop<128, 1>(acc, sb, pm, nkb, st, ph, wg, leader, clk_q);
          else h_mainloop<128, 0>(acc, sb, pm, nkb, st, ph, wg, leader, clk_q);
          if (type == IT_F1) h_swiglu<128>(acc, vb, vp, sb, pm, st, ph, g0, wg, leader, warp, lane, clk_q);
          else h_gated<128>(acc, va, vb, vp, sb, pm, st, ph, g0, wg, leader, warp, lane, clk_q);
        }
        HT(3);
        continue;
      } else if (type == IT_XT) {
        const uint4* xp = reinterpret_cast<const uint4*>(x + (size_t)(mt * 128 + idx * 64) * D_) + tid;
        uint4* op = reinterpret_cast<uint4*>(out + (size_t)(mt * 128 + idx * 64) * D_) + tid;
#pragma unroll 1
        for (int b = 0; b < 2; b++) {
          uint4 v[16];
#pragma unroll
          for (int i = 0; i < 16; i++) v[i] = __ldcs(xp + (b * 16 + i) * 256);
#pragma unroll
          for (int i = 0; i < 16; i++) op[(b * 16 + i) * 256] = v[i];
        }
      } else if (type == IT_STAT) {
        const int row0 = mt * 128 + idx * 32 + warp * 4;
        const uint4* xp = reinterpret_cast<const uint4*>(out + (size_t)row0 * D_) + lane;
        uint4 v[16];
#pragma unroll
        for (int i = 0; i < 16; i++) v[i] = __ldcg(xp + (i >> 2) * 128 + (i & 3) * 32);
        float s[4], m[4];
#pragma unroll
        for (int r = 0; r < 4; r++) {
          s[r] = 0.f;
#pragma unroll
          for (int i = 0; i < 4; i++) {
            const uint4 w = v[4 * r + i];
            s[r] += ((bf_lo(w.x) + bf_hi(w.x)) + (bf_lo(w.y) + bf_hi(w.y))) + ((bf_lo(w.z) + bf_hi(w.z)) + (bf_lo(w.w) + bf_hi(w.w)));
          }
        }
#pragma unroll
        for (int o = 1; o < 32; o <<= 1)
#pragma unroll
          for (int r = 0; r < 4; r++) s[r] += __shfl_xor_sync(0xffffffffu, s[r], o);
#pragma unroll
        for (int r = 0; r < 4; r++) {
          m[r] = s[r] * (1.f / D_);
          float a = 0.f, b = 0.f;
#pragma unroll
          for (int i = 0; i < 4; i++) {
            const uint4 w = v[4 * r + i];
            const uint32_t ww[4] = {w.x, w.y, w.z, w.w};
#pragma unroll
            for (int e = 0; e < 4; e++) { const float p = bf_lo(ww[e]) - m[r], t = bf_hi(ww[e]) - m[r]; a = fmaf(p, p, a); b = fmaf(t, t, b); }
          }
          s[r] = a + b;
        }
#pragma unroll
        for (int o = 1; o < 32; o <<= 1)
#pragma unroll
          for (int r = 0; r < 4; r++) s[r] += __shfl_xor_sync(0xffffffffu, s[r], o);
        if (lane < 4) {
          const float sr = lane == 0 ? s[0] : lane == 1 ? s[1] : lane == 2 ? s[2] : s[3], mr = lane == 0 ? m[0] : lane == 1 ? m[1] : lane == 2 ? m[2] : m[3];
          const float var = sr * (1.f / D_) + 1e-5f, rs = rsqrtf(var);
          const float a = -0.5f * mr, b = 0.5f * var * rs;
          const float ah = __bfloat162float(__float2bfloat16(a)), bh = __bfloat162float(__float2bfloat16(b));
          const int r = (row0 & 127) + lane;
          *reinterpret_cast<uint4*>(g_ext + mt * 2560 + r * 16) = make_uint4(pack2(ah, ah), pack2(a - ah, bh), pack2(bh, b - bh), 0u);
          *reinterpret_cast<float*>(g_ext + mt * 2560 + 2048 + r * 4) = rs;
        }
      } else {
        mbar_wait(bars + HB_STGF, (n & 1) ^ 1);
        if (type == IT_WS) h_vecmat<true>(sb, idx, st, ph, tid, cvec, g_w13s, g_bext, g_mod, g_gate);
        else h_vecmat<false>(sb, idx, st, ph, tid, cvec, g_w13s, g_bext, g_mod, g_gate);
      }
      HT(3);
      if (n & 1) bar_arrive<3, 288>(); else bar_arrive<2, 288>();
    }
  }
  cluster_sync();
}

const uint32_t h_items1[] = {
  0x1, 0x81, 0x101, 0x181, 0x201, 0x281, 0x301, 0x381, 0x401, 0x481, 0x501, 0x581, 0x601, 0x681,
  0x701, 0x781, 0x801, 0x881, 0x901, 0x981, 0xa01, 0xa81, 0xb01, 0xb81, 0xc01, 0xc81, 0xd01, 0xd81,
  0xe01, 0xe81, 0xf01, 0xf81, 0x2, 0x82, 0xa, 0x8a, 0x12, 0x92, 0x1a, 0x9a, 0x22, 0xa2,
  0x2a, 0xaa, 0x4, 0x84, 0x104, 0x184, 0x32, 0xb2, 0x3a, 0xba, 0x42, 0xc2, 0x4a, 0xca,
  0x52, 0xd2, 0x5a, 0xda, 0x62, 0xe2, 0x6a, 0xea, 0x72, 0xf2, 0x7a, 0xfa, 0x204, 0x284,
  0x304, 0x384, 0x404, 0x484, 0x504, 0x584, 0x604, 0x684, 0x704, 0x784, 0x804, 0x884, 0x904, 0x984,
  0xa04, 0xa84, 0xb04, 0xb84, 0xc04, 0xc84, 0xd04, 0xd84, 0x1000003, 0x1000083, 0x1000103, 0x1000183, 0x1040003, 0x1040083,
  0x1040103, 0x1040183, 0x1080003, 0x1080083, 0x1080103, 0x1080183, 0x10c0003, 0x10c0083, 0x10c0103, 0x10c0183, 0x1100003, 0x1100083, 0x1100103, 0x1100183,
  0x1140003, 0x1140083, 0x1140103, 0x1140183, 0x1180003, 0x1180083, 0x1180103, 0x1180183, 0x11c0003, 0x11c0083, 0x11c0103, 0x11c0183, 0x200000b, 0x200008b,
  0x200010b, 0x200018b, 0x208000b, 0x208008b, 0x208010b, 0x208018b, 0x210000b, 0x210008b, 0x210010b, 0x210018b, 0x218000b, 0x218008b, 0x218010b, 0x218018b,
  0x7, 0x87, 0x107, 0x187, 0x2000005, 0x2000085, 0x2000105, 0x2000185, 0x2000205, 0x2000285, 0x2000305, 0x2000385, 0x2000405, 0x2000485,
  0x2000505, 0x2000585, 0x2000605, 0x2000685, 0x2000705, 0x2000785, 0x2000805, 0x2000885, 0x2000905, 0x2000985, 0x2000a05, 0x2000a85, 0x2000b05, 0x2000b85,
  0x2000c05, 0x2000c85, 0x2000d05, 0x2000d85, 0x4000013, 0x4000093, 0x4000113, 0x4000193, 0x4100013, 0x4100093, 0x4100113, 0x4100193, 0xf, 0x8f,
  0x10f, 0x18f, 0x200000d, 0x200008d, 0x200010d, 0x200018d, 0x200020d, 0x200028d, 0x200030d, 0x200038d, 0x200040d, 0x200048d, 0x200050d, 0x200058d,
  0x200060d, 0x200068d, 0x200070d, 0x200078d, 0x200080d, 0x200088d, 0x200090d, 0x200098d, 0x2000a0d, 0x2000a8d, 0x2000b0d, 0x2000b8d, 0x2000c0d, 0x2000c8d,
  0x2000d0d, 0x2000d8d, 0x3800006, 0x3800086, 0x3800106, 0x3800186, 0x38e0006, 0x38e0086, 0x38e0106, 0x38e0186, 0x400001b, 0x400009b, 0x400011b, 0x400019b,
  0x410001b, 0x410009b, 0x410011b, 0x410019b, 0x380000e, 0x380008e, 0x380010e, 0x380018e, 0x38e000e, 0x38e008e, 0x38e010e, 0x38e018e, 0x17, 0x97,
  0x117, 0x197, 0x2000015, 0x2000095, 0x2000115, 0x2000195, 0x2000215, 0x2000295, 0x2000315, 0x2000395, 0x2000415, 0x2000495, 0x2000515, 0x2000595,
  0x4000023, 0x40000a3, 0x4000123, 0x40001a3, 0x4100023, 0x41000a3, 0x4100123, 0x41001a3, 0x2000615, 0x2000695, 0x2000715, 0x2000795, 0x2000815, 0x2000895,
  0x2000915, 0x2000995, 0x2000a15, 0x2000a95, 0x2000b15, 0x2000b95, 0x2000c15, 0x2000c95, 0x2000d15, 0x2000d95, 0x1f, 0x9f, 0x11f, 0x19f,
  0x200001d, 0x200009d, 0x200011d, 0x200019d, 0x200021d, 0x200029d, 0x200031d, 0x200039d, 0x200041d, 0x200049d, 0x200051d, 0x200059d, 0x400002b, 0x40000ab,
  0x400012b, 0x40001ab, 0x410002b, 0x41000ab, 0x410012b, 0x41001ab, 0x200061d, 0x200069d, 0x200071d, 0x200079d, 0x200081d, 0x200089d, 0x200091d, 0x200099d,
  0x2000a1d, 0x2000a9d, 0x2000b1d, 0x2000b9d, 0x2000c1d, 0x2000c9d, 0x2000d1d, 0x2000d9d, 0x27, 0xa7, 0x127, 0x1a7, 0x2000025, 0x20000a5,
  0x2000125, 0x20001a5, 0x2000225, 0x20002a5, 0x2000325, 0x20003a5, 0x4000033, 0x40000b3, 0x4000133, 0x40001b3, 0x4100033, 0x41000b3, 0x4100133, 0x41001b3,
  0x2000425, 0x20004a5, 0x2000525, 0x20005a5, 0x2000625, 0x20006a5, 0x2000725, 0x20007a5, 0x2000825, 0x20008a5, 0x2000925, 0x20009a5, 0x2000a25, 0x2000aa5,
  0x2000b25, 0x2000ba5, 0x2000c25, 0x2000ca5, 0x2000d25, 0x2000da5, 0x2f, 0xaf, 0x12f, 0x1af, 0x200002d, 0x20000ad, 0x200012d, 0x20001ad,
  0x200022d, 0x20002ad, 0x200032d, 0x20003ad, 0x400003b, 0x40000bb, 0x400013b, 0x40001bb, 0x410003b, 0x41000bb, 0x410013b, 0x41001bb, 0x200042d, 0x20004ad,
  0x200052d, 0x20005ad, 0x200062d, 0x20006ad, 0x200072d, 0x20007ad, 0x200082d, 0x20008ad, 0x200092d, 0x20009ad, 0x2000a2d, 0x2000aad, 0x2000b2d, 0x2000bad,
  0x2000c2d, 0x2000cad, 0x2000d2d, 0x2000dad, 0x37, 0xb7, 0x137, 0x1b7, 0x2000035, 0x20000b5, 0x2000135, 0x20001b5, 0x2000235, 0x20002b5,
  0x2000335, 0x20003b5, 0x2000435, 0x20004b5, 0x2000535, 0x20005b5, 0x4000043, 0x40000c3, 0x4000143, 0x40001c3, 0x4100043, 0x41000c3, 0x4100143, 0x41001c3,
  0x2000635, 0x20006b5, 0x2000735, 0x20007b5, 0x2000835, 0x20008b5, 0x2000935, 0x20009b5, 0x2000a35, 0x2000ab5, 0x2000b35, 0x2000bb5, 0x2000c35, 0x2000cb5,
  0x2000d35, 0x2000db5, 0x3f, 0xbf, 0x13f, 0x1bf, 0x200003d, 0x20000bd, 0x200013d, 0x20001bd, 0x200023d, 0x20002bd, 0x200033d, 0x20003bd,
  0x400004b, 0x40000cb, 0x400014b, 0x40001cb, 0x410004b, 0x41000cb, 0x410014b, 0x41001cb, 0x200043d, 0x20004bd, 0x200053d, 0x20005bd, 0x200063d, 0x20006bd,
  0x200073d, 0x20007bd, 0x200083d, 0x20008bd, 0x200093d, 0x20009bd, 0x2000a3d, 0x2000abd, 0x2000b3d, 0x2000bbd, 0x2000c3d, 0x2000cbd, 0x2000d3d, 0x2000dbd,
  0x47, 0xc7, 0x147, 0x1c7, 0x2000045, 0x20000c5, 0x2000145, 0x20001c5, 0x2000245, 0x20002c5, 0x2000345, 0x20003c5, 0x4000053, 0x40000d3,
  0x4000153, 0x40001d3, 0x4100053, 0x41000d3, 0x4100153, 0x41001d3, 0x2000445, 0x20004c5, 0x2000545, 0x20005c5, 0x2000645, 0x20006c5, 0x2000745, 0x20007c5,
  0x2000845, 0x20008c5, 0x2000945, 0x20009c5, 0x2000a45, 0x2000ac5, 0x2000b45, 0x2000bc5, 0x2000c45, 0x2000cc5, 0x2000d45, 0x2000dc5, 0x4f, 0xcf,
  0x14f, 0x1cf, 0x200004d, 0x20000cd, 0x200014d, 0x20001cd, 0x200024d, 0x20002cd, 0x200034d, 0x20003cd, 0x200044d, 0x20004cd, 0x200054d, 0x20005cd,
  0x400005b, 0x40000db, 0x400015b, 0x40001db, 0x410005b, 0x41000db, 0x410015b, 0x41001db, 0x200064d, 0x20006cd, 0x200074d, 0x20007cd, 0x200084d, 0x20008cd,
  0x200094d, 0x20009cd, 0x2000a4d, 0x2000acd, 0x2000b4d, 0x2000bcd, 0x2000c4d, 0x2000ccd, 0x2000d4d, 0x2000dcd, 0x57, 0xd7, 0x157, 0x1d7,
  0x2000055, 0x20000d5, 0x2000155, 0x20001d5, 0x2000255, 0x20002d5, 0x2000355, 0x20003d5, 0x4000063, 0x40000e3, 0x4000163, 0x40001e3, 0x4100063, 0x41000e3,
  0x4100163, 0x41001e3, 0x2000455, 0x20004d5, 0x2000555, 0x20005d5, 0x2000655, 0x20006d5, 0x2000755, 0x20007d5, 0x2000855, 0x20008d5, 0x2000955, 0x20009d5,
  0x2000a55, 0x2000ad5, 0x2000b55, 0x2000bd5, 0x2000c55, 0x2000cd5, 0x2000d55, 0x2000dd5, 0x5f, 0xdf, 0x15f, 0x1df, 0x200005d, 0x20000dd,
  0x200015d, 0x20001dd, 0x200025d, 0x20002dd, 0x200035d, 0x20003dd, 0x200006b, 0x20000eb, 0x200016b, 0x20001eb, 0x208006b, 0x20800eb, 0x208016b, 0x20801eb,
  0x210006b, 0x21000eb, 0x210016b, 0x21001eb, 0x218006b, 0x21800eb, 0x218016b, 0x21801eb, 0x200045d, 0x20004dd, 0x200055d, 0x20005dd, 0x200065d, 0x20006dd,
  0x200075d, 0x20007dd, 0x200085d, 0x20008dd, 0x200095d, 0x20009dd, 0x2000a5d, 0x2000add, 0x2000b5d, 0x2000bdd, 0x2000c5d, 0x2000cdd, 0x2000d5d, 0x2000ddd,
  0x67, 0xe7, 0x167, 0x1e7, 0x2000065, 0x20000e5, 0x2000165, 0x20001e5, 0x2000265, 0x20002e5, 0x2000365, 0x20003e5, 0x2000465, 0x20004e5,
  0x2000565, 0x20005e5, 0x2000073, 0x20000f3, 0x2000173, 0x20001f3, 0x2080073, 0x20800f3, 0x2080173, 0x20801f3, 0x2100073, 0x21000f3, 0x2100173, 0x21001f3,
  0x2180073, 0x21800f3, 0x2180173, 0x21801f3, 0x6f, 0xef, 0x16f, 0x1ef, 0x2000665, 0x20006e5, 0x2000765, 0x20007e5, 0x2000865, 0x20008e5,
  0x2000965, 0x20009e5, 0x2000a65, 0x2000ae5, 0x2000b65, 0x2000be5, 0x2000c65, 0x2000ce5, 0x2000d65, 0x2000de5, 0x200006d, 0x20000ed, 0x200016d, 0x20001ed,
  0x200026d, 0x20002ed, 0x200036d, 0x20003ed, 0x200046d, 0x20004ed, 0x200056d, 0x20005ed, 0x200066d, 0x20006ed, 0x200076d, 0x20007ed, 0x200086d, 0x20008ed,
  0x200096d, 0x20009ed, 0x2000a6d, 0x2000aed, 0x2000b6d, 0x2000bed, 0x77, 0xf7, 0x177, 0x1f7, 0x2000c6d, 0x2000ced, 0x2000d6d, 0x2000ded,
  0x2000075, 0x20000f5, 0x2000175, 0x20001f5, 0x2000275, 0x20002f5, 0x2000375, 0x20003f5, 0x2000475, 0x20004f5, 0x2000575, 0x20005f5, 0x2000675, 0x20006f5,
  0x2000775, 0x20007f5, 0x2000875, 0x20008f5, 0x2000975, 0x20009f5, 0x2000a75, 0x2000af5, 0x2000b75, 0x2000bf5, 0x2000c75, 0x2000cf5, 0x2000d75, 0x2000df5,
  0x1c0006e, 0x1c000ee, 0x1c0016e, 0x1c001ee, 0x1c7006e, 0x1c700ee, 0x1c7016e, 0x1c701ee, 0x1ce006e, 0x1ce00ee, 0x1ce016e, 0x1ce01ee, 0x1d5006e, 0x1d500ee,
  0x1d5016e, 0x1d501ee, 0x1c00076, 0x1c000f6, 0x1c00176, 0x1c001f6, 0x1c70076, 0x1c700f6, 0x1c70176, 0x1c701f6, 0x1ce0076, 0x1ce00f6, 0x1ce0176, 0x1ce01f6,
  0x1d50076, 0x1d500f6, 0x1d50176, 0x1d501f6,
};
const uint32_t h_items2[] = {
  0x100207b, 0x100217b, 0x100227b, 0x100237b, 0x104207b, 0x104217b, 0x104227b, 0x104237b, 0x108207b, 0x108217b, 0x108227b, 0x108237b, 0x10c207b, 0x10c217b,
  0x10c227b, 0x10c237b, 0x110207b, 0x110217b, 0x110227b, 0x110237b, 0x114207b, 0x114217b, 0x114227b, 0x114237b, 0x118207b, 0x118217b, 0x118227b, 0x118237b,
  0x11c207b, 0x11c217b, 0x11c227b, 0x11c237b, 0x31c00016, 0x31c00096, 0x31c00116, 0x31c00196, 0x31c70016, 0x31c70096, 0x31c70116, 0x31c70196, 0x31ce0016, 0x31ce0096,
  0x31ce0116, 0x31ce0196, 0x31d50016, 0x31d50096, 0x31d50116, 0x7f, 0x17f, 0x31d50196, 0x31c00026, 0x31c000a6, 0x31c00126, 0x31c001a6, 0x31c70026, 0x31c700a6,
  0x31c70126, 0x31c701a6, 0x31ce0026, 0x31ce00a6, 0x31ce0126, 0x31ce01a6, 0x31d50026, 0x31d500a6, 0x31d50126, 0x31d501a6, 0x31c00036, 0x31c000b6, 0x31c00136, 0x31c001b6,
  0x31c70036, 0x31c700b6, 0x31c70136, 0x31c701b6, 0x31ce0036, 0x31ce00b6, 0x31ce0136, 0x31ce01b6, 0x31d50036, 0x200207d, 0x200217d, 0x200227d, 0x200237d, 0x200247d,
  0x200257d, 0x200267d, 0x200277d, 0x200287d, 0x200297d, 0x2002a7d, 0x2002b7d, 0x2002c7d, 0x2002d7d, 0x2002e7d, 0x2002f7d, 0x200307d, 0x200317d, 0x200327d,
  0x200337d, 0x200347d, 0x200357d, 0x200367d, 0x200377d, 0x200387d, 0x200397d, 0x2003a7d, 0x2003b7d, 0x31d500b6, 0x31d50136, 0x31d501b6, 0x31c00046, 0x31c000c6,
  0x31c00146, 0x31c001c6, 0x31c70046, 0x31c700c6, 0x31c70146, 0x31c701c6, 0x31ce0046, 0x31ce00c6, 0x31ce0146, 0x31ce01c6, 0x31d50046, 0x31d500c6, 0x31d50146, 0x31d501c6,
  0x31c00056, 0x31c000d6, 0x31c00156, 0x31c001d6, 0x31c70056, 0x31c700d6, 0x31c70156, 0x31c701d6, 0x31ce0056, 0x31ce00d6, 0x31ce0156, 0x31ce01d6, 0x31d50056, 0x31d500d6,
  0x31d50156, 0x31d501d6, 0x1c00066, 0x1c00166, 0x1c70066, 0x1c70166, 0x1ce0066, 0x1ce0166, 0x1d50066, 0x1d50166, 0xe0207e, 0xe0217e, 0xe0227e, 0xe0237e,
  0xe3a07e, 0xe3a17e, 0xe3a27e, 0xe3a37e, 0xe7207e, 0xe7217e, 0xe7227e, 0xe7237e, 0xeaa07e, 0xeaa17e, 0xeaa27e, 0xeaa37e, 0xee207e, 0xee217e,
  0xee227e, 0xee237e, 0xf1a07e, 0xf1a17e, 0xf1a27e, 0xf1a37e, 0xf5207e, 0xf5217e, 0xf5227e, 0xf5237e, 0xf8a07e, 0xf8a17e, 0xf8a27e, 0xf8a37e,
};

void build_lists(HList& a, HList& b) {
  a.n = b.n = 0;
  for (uint32_t v : h_items1) a.it[a.n++] = v;
  for (uint32_t v : h_items2) b.it[b.n++] = v;
  a.head = FL_HEAD; a.tbase = 0;
  b.head = FL_HEAD2; b.tbase = a.n;
}

typedef CUresult (*EncodeFn)(CUtensorMap*, CUtensorMapDataType, cuuint32_t, void*, const cuuint64_t*, const cuuint64_t*,
                             const cuuint32_t*, const cuuint32_t*, CUtensorMapInterleave, CUtensorMapSwizzle,
                             CUtensorMapL2promotion, CUtensorMapFloatOOBfill);

void make_map(EncodeFn fn, CUtensorMap* m, const void* p, uint64_t cols, uint64_t rows, uint32_t bc, uint32_t br, CUtensorMapSwizzle sw) {
  cuuint64_t dims[2] = {cols, rows};
  cuuint64_t strides[1] = {cols * 2};
  cuuint32_t box[2] = {bc, br};
  cuuint32_t es[2] = {1, 1};
  fn(m, CU_TENSOR_MAP_DATA_TYPE_BFLOAT16, 2, const_cast<void*>(p), dims, strides, box, es, CU_TENSOR_MAP_INTERLEAVE_NONE, sw,
     CU_TENSOR_MAP_L2_PROMOTION_L2_128B, CU_TENSOR_MAP_FLOAT_OOB_FILL_NONE);
}

}

extern "C" void kernel_launch(void* const* d_in, const int* in_sizes, int n_in, void* d_out, int out_size) {
  const __nv_bfloat16* x = (const __nv_bfloat16*)d_in[0];
  const __nv_bfloat16* mem0 = (const __nv_bfloat16*)d_in[1];
  const __nv_bfloat16* cvec = (const __nv_bfloat16*)d_in[11];
  const __nv_bfloat16* wo_p = (const __nv_bfloat16*)d_in[5];
  static EncodeFn enc = nullptr;
  if (!enc) {
    cudaDriverEntryPointQueryResult qr;
    void* fp = nullptr;
    cudaGetDriverEntryPoint("cuTensorMapEncodeTiled", &fp, cudaEnableDefault, &qr);
    enc = (EncodeFn)fp;
    cudaFuncSetAttribute(kernel_R, cudaFuncAttributeMaxDynamicSharedMemorySize, R_SMEM);
    cudaFuncSetAttribute(kernel_H, cudaFuncAttributeMaxDynamicSharedMemorySize, H_SMEM);
  }
  CUtensorMap tmq, tmk, tmv, tmo, tmm;
  make_map(enc, &tmm, d_in[12], 6144, 1024, 64, 64, CU_TENSOR_MAP_SWIZZLE_NONE);
  make_map(enc, &tmq, d_in[2], 4096, 1024, 64, 64, CU_TENSOR_MAP_SWIZZLE_128B);
  make_map(enc, &tmk, d_in[3], 4096, 1024, 64, 64, CU_TENSOR_MAP_SWIZZLE_128B);
  make_map(enc, &tmv, d_in[4], 4096, 1024, 64, 64, CU_TENSOR_MAP_SWIZZLE_128B);
  make_map(enc, &tmo, d_in[5], 1024, 4096, 16, 128, CU_TENSOR_MAP_SWIZZLE_32B);
  RDesc dsc;
  for (int k = 0; k < 32; k++) {
    dsc.tok[k] = mkdesc(0x400 + (k < 16 ? R_GA : R_GB) + ((k & 15) >> 2) * 4096 + (k & 3) * 256, 128, 1024, 0);
    dsc.tail_a[k] = mkdesc(0x400 + R_TAIL + k * 2048, 1024, 1024, 1);
    if (k < 16) dsc.tail_b[k] = mkdesc(0x400 + R_GA + k * 256, 128, 4096, 0);
  }
  kernel_R<<<96, 256, R_SMEM, cudaStreamPerThread>>>(tmq, tmk, tmv, tmo, tmm, x, mem0, cvec, wo_p, dsc);

  CUtensorMap ho, h1, h3, h2, hm, hx, hy;
  make_map(enc, &ho, d_in[5], 1024, 4096, 64, 64, CU_TENSOR_MAP_SWIZZLE_128B);
  make_map(enc, &h1, d_in[8], F_, 1024, 64, 64, CU_TENSOR_MAP_SWIZZLE_128B);
  make_map(enc, &h3, d_in[9], F_, 1024, 64, 64, CU_TENSOR_MAP_SWIZZLE_128B);
  make_map(enc, &h2, d_in[10], 1024, F_, 64, 64, CU_TENSOR_MAP_SWIZZLE_128B);
  make_map(enc, &hm, d_in[12], 6144, 1024, 64, 64, CU_TENSOR_MAP_SWIZZLE_128B);
  make_map(enc, &hx, d_out, 1024, S_, 64, 128, CU_TENSOR_MAP_SWIZZLE_128B);
  make_map(enc, &hy, d_out, 1024, S_, 64, 64, CU_TENSOR_MAP_SWIZZLE_128B);
  HList list1, list2;
  build_lists(list1, list2);
  HWeights rw;
  for (int i = 0; i < 4; i++) rw.p[i] = (const uint8_t*)d_in[2 + i];
  cudaLaunchConfig_t cfg = {};
  cfg.gridDim = dim3(NH1); cfg.blockDim = dim3(384); cfg.dynamicSmemBytes = H_SMEM; cfg.stream = cudaStreamPerThread;
  cudaLaunchAttribute at[2];
  at[0].id = cudaLaunchAttributeProgrammaticStreamSerialization;
  at[0].val.programmaticStreamSerializationAllowed = 1;
  at[1].id = cudaLaunchAttributeClusterDimension;
  at[1].val.clusterDim.x = 2; at[1].val.clusterDim.y = 1; at[1].val.clusterDim.z = 1;
  cfg.attrs = at; cfg.numAttrs = 1;
  cudaLaunchKernelEx(&cfg, kernel_H, ho, h1, h3, h2, hm, hx, hy, x, cvec, (__nv_bfloat16*)d_out, rw, list1);
  cfg.numAttrs = 2; cfg.gridDim = dim3(NH2);
  cudaLaunchKernelEx(&cfg, kernel_H, ho, h1, h3, h2, hm, hx, hy, x, cvec, (__nv_bfloat16*)d_out, rw, list2);
}
```
